```python
import torch

def _softmax(x, axis=-1):
    return torch.softmax(x, dim=axis)

def _gelu(x):
    return torch.nn.functional.gelu(x, approximate='tanh')

def _silu(x):
    return torch.nn.functional.silu(x)

def _sigmoid(x):
    return torch.sigmoid(x)

def _layernorm(x, axis=-1, eps=1e-05):
    m = x.mean(dim=axis, keepdim=True)
    v = x.var(dim=axis, keepdim=True, unbiased=False)
    return (x - m) / torch.sqrt(v + eps)

def _scatter_add(tgt, idx, src, axis=0):
    return tgt.clone().index_add_(axis, idx, src)

def _segment_sum(src, seg, n):
    out = torch.zeros((n,) + src.shape[1:], dtype=src.dtype)
    return out.index_add_(0, seg, src)

def _pad(x, pw):
    flat = tuple((v for pair in reversed(pw) for v in pair))
    return torch.nn.functional.pad(x, flat)
kernel_name = 'adaLN_cond__sliding_local_dilated__moe_arch_mod__prompt'

def setup_inputs():

    _w = lambda a: (lambda t: t.to(torch.bfloat16) if t.is_floating_point() else t)(torch.as_tensor(a))

    def _A_setup():
        B, S, D = (1, 2048, 640)
        return {'x': _w((lambda *s: torch.randn(*s, dtype=torch.bfloat16) * 0.05)(B, S, D)), 'wqkv': _w((lambda *s: torch.randn(*s, dtype=torch.bfloat16) * 0.05)(D, 3 * D)), 'wo': _w((lambda *s: torch.randn(*s, dtype=torch.bfloat16) * 0.05)(D, D))}
    _A_in = _A_setup()

    def _B_setup():
        B, S, D, F, C = (1, 2048, 640, 1728, 1)
        return {'x': _w((lambda *s: torch.randn(*s, dtype=torch.bfloat16) * 0.05)(B, S, D)), 'w_r': _w((lambda *s: torch.randn(*s, dtype=torch.bfloat16) * 3.2)(D)), 'w_gate': _w((lambda *s: torch.randn(*s, dtype=torch.bfloat16) * 0.1)(D, F)), 'w_up': _w((lambda *s: torch.randn(*s, dtype=torch.bfloat16) * 0.1)(D, F)), 'w_down': _w((lambda *s: torch.randn(*s, dtype=torch.bfloat16) * 0.1)(F, D))}
    _B_in = _B_setup()
    return {'A_x': _A_in['x'], 'A_wqkv': _A_in['wqkv'], 'A_wo': _A_in['wo'], 'B_x': _B_in['x'], 'B_w_r': _B_in['w_r'], 'B_w_gate': _B_in['w_gate'], 'B_w_up': _B_in['w_up'], 'B_w_down': _B_in['w_down'], 'c': _w((lambda *s: torch.randn(*s, dtype=torch.bfloat16) * 0.1)(1, 640) * 8.0), 'w_mod': _w((lambda *s: torch.randn(*s, dtype=torch.bfloat16) * 0.1)(640, 6 * 640) * 640 ** (-0.5) * 8.0)}

def reference(A_x, A_wqkv, A_wo, B_x, B_w_r, B_w_gate, B_w_up, B_w_down, c, w_mod):

    def _A_ref(x, wqkv, wo):
        B, S, D = x.shape
        H = 32
        Dh = D // H
        W, dil = (8, 2)
        qkv = (lambda x, *d: x.permute(*d))((x @ wqkv).reshape(B, S, 3, H, Dh), 2, 0, 3, 1, 4)
        q, k, v = (qkv[0], qkv[1], qkv[2])
        scale = Dh ** (-0.5)
        pos = torch.arange(S)
        off = torch.arange(W) * dil
        idx = pos[:, None] - off[None, :]
        mask = idx >= 0
        idx_c = torch.where(mask, idx, 0).reshape(-1)
        kg = k[:, :, idx_c, :].reshape(B, H, S, W, Dh)
        vg = v[:, :, idx_c, :].reshape(B, H, S, W, Dh)
        logits = torch.einsum('bhsd,bhswd->bhsw', q, kg) * scale
        logits = torch.where(mask[None, None, :, :], logits, -1000000000.0)
        attn = _softmax(logits, axis=-1)
        o = torch.einsum('bhsw,bhswd->bhsd', attn, vg)
        return (lambda x, *d: x.permute(*d))(o, 0, 2, 1, 3).reshape(B, S, D) @ wo

    def _B_ref(x, w_r, w_gate, w_up, w_down):
        B, S, D = x.shape
        C = 1
        r = x @ w_r
        idx = torch.argsort(-r, axis=-1)[:, :C]
        idx_e = (lambda x, n, axis: torch.repeat_interleave(x, n, dim=axis))(idx.reshape(B, C, 1), D, axis=2)
        x_sel = (lambda x, i, axis: torch.take_along_dim(x, i, dim=axis))(x, idx_e, axis=1)
        g = _silu(x_sel @ w_gate)
        u = x_sel @ w_up
        y = g * u @ w_down
        r_sel = _sigmoid((lambda x, i, axis: torch.take_along_dim(x, i, dim=axis))(r, idx, axis=1))
        y = y * r_sel.reshape(B, C, 1)
        b_off = (torch.arange(B) * S).reshape(B, 1)
        flat_idx = (idx + b_off).reshape(B * C)
        zero = (x * 0.0).reshape(B * S, D)
        upd = _scatter_add(zero, flat_idx, y.reshape(B * C, D), axis=0)
        return x + upd.reshape(B, S, D)
    x = A_x
    mod = (_silu(c) @ w_mod).reshape(c.shape[0], 6, 1, -1)
    sa, ca, ga, sb, cb, gb = (mod[:, 0].clone(), mod[:, 1].clone(), mod[:, 2].clone(), mod[:, 3].clone(), mod[:, 4].clone(), mod[:, 5].clone())
    h = _layernorm(x, axis=-1) * (1 + ca) + sa
    x = x + ga * _A_ref(h, A_wqkv, A_wo)
    h = _layernorm(x, axis=-1) * (1 + cb) + sb
    x = x + gb * _B_ref(h, B_w_r, B_w_gate, B_w_up, B_w_down)
    return x
```

```cpp
#include <cuda_runtime.h>
#include <cuda_bf16.h>
#include <cuda.h>
#include <stdint.h>

#define SENT 0xFFFFFFFFu
#define SPIN_LIMIT (1 << 17)

__device__ unsigned g_epoch;
__device__ __align__(128) unsigned g_mod[3840];
__device__ __align__(128) unsigned g_ready[128];
__device__ __align__(128) uint4 g_halo[128 * 160];
__device__ __align__(128) uint4 g_o[128 * 8 * 160];
__device__ __align__(128) uint4 g_stats[2048 * 8];
__device__ __align__(128) uint2 g_rec[128];
__device__ __align__(128) uint4 g_cand[128 * 8 * 32];
__device__ __align__(128) uint2 g_a[112 * 4];
#define STAMP(n)
#define STAMPT(n, t)

constexpr uint32_t OFF_W = 163840, WST = 15360;
constexpr uint32_t OFF_WD = 129024, OFF_WG = 184320, OFF_WU = OFF_WG + 20480;
constexpr uint32_t OFF_TAB = 225280;
constexpr uint32_t OFF_EP = OFF_TAB + 2560;
constexpr uint32_t OFF_RED = OFF_EP + 1792;
constexpr uint32_t OFF_RED2 = OFF_RED + 1024;
constexpr uint32_t OFF_BAR = OFF_RED2 + 512;
constexpr uint32_t SMEM_BYTES = OFF_BAR + 256;
constexpr uint32_t B_XF = 0, B_WF = 80, B_WE = 112, B_WO = 144, B_FG = 208, B_FD = 216, B_G1 = 224, B_RDY = 232, B_EP = 240;

__device__ __forceinline__ uint32_t smem_u32(const void* p) { return (uint32_t)__cvta_generic_to_shared(p); }
__device__ __forceinline__ void mbar_init(uint32_t b, int cnt) { asm volatile("mbarrier.init.shared::cta.b64 [%0], %1;" ::"r"(b), "r"(cnt) : "memory"); }
__device__ __forceinline__ void mbar_expect_tx(uint32_t b, uint32_t bytes) { asm volatile("mbarrier.arrive.expect_tx.shared::cta.b64 _, [%0], %1;" ::"r"(b), "r"(bytes) : "memory"); }
__device__ __forceinline__ void mbar_arrive(uint32_t b) { asm volatile("mbarrier.arrive.shared::cta.b64 _, [%0];" ::"r"(b) : "memory"); }
__device__ __forceinline__ bool mbar_try(uint32_t b, uint32_t par) {
    uint32_t ok;
    asm volatile("{.reg .pred p; mbarrier.try_wait.parity.shared::cta.b64 p, [%1], %2; selp.u32 %0, 1, 0, p;}" : "=r"(ok) : "r"(b), "r"(par) : "memory");
    return ok;
}
__device__ __forceinline__ void mbar_wait(uint32_t b, uint32_t par) { int g = 0; while (!mbar_try(b, par)) { if (++g > SPIN_LIMIT) break; } }
__device__ __forceinline__ void bar_sync(int id, int n) { asm volatile("bar.sync %0, %1;" ::"r"(id), "r"(n) : "memory"); }
__device__ __forceinline__ void tma2d(uint32_t dst, const CUtensorMap* m, int c0, int c1, uint32_t bar) {
    asm volatile("cp.async.bulk.tensor.2d.shared::cluster.global.mbarrier::complete_tx::bytes [%0], [%1, {%3, %4}], [%2];" ::"r"(dst), "l"(m), "r"(bar), "r"(c0), "r"(c1) : "memory");
}
__device__ __forceinline__ void tma3d(uint32_t dst, const CUtensorMap* m, int c0, int c1, int c2, uint32_t bar) {
    asm volatile("cp.async.bulk.tensor.3d.shared::cluster.global.mbarrier::complete_tx::bytes [%0], [%1, {%3, %4, %5}], [%2];" ::"r"(dst), "l"(m), "r"(bar), "r"(c0), "r"(c1), "r"(c2) : "memory");
}
__device__ __forceinline__ void tma4d(uint32_t dst, const CUtensorMap* m, int c0, int c1, int c2, int c3, uint32_t bar) {
    asm volatile("cp.async.bulk.tensor.4d.shared::cluster.global.mbarrier::complete_tx::bytes [%0], [%1, {%3, %4, %5, %6}], [%2];" ::"r"(dst), "l"(m), "r"(bar), "r"(c0), "r"(c1), "r"(c2), "r"(c3) : "memory");
}
__device__ __forceinline__ void l2_prefetch(const void* p, uint32_t bytes) { asm volatile("cp.async.bulk.prefetch.L2.global [%0], %1;" ::"l"(p), "r"(bytes) : "memory"); }
__device__ __forceinline__ void pf_map(const CUtensorMap* m) { asm volatile("prefetch.tensormap [%0];" ::"l"(m) : "memory"); }
__device__ __forceinline__ void wg_fence() { asm volatile("wgmma.fence.sync.aligned;" ::: "memory"); }
__device__ __forceinline__ void wg_commit() { asm volatile("wgmma.commit_group.sync.aligned;" ::: "memory"); }
template <int N> __device__ __forceinline__ void wg_wait() { asm volatile("wgmma.wait_group.sync.aligned %0;" ::"n"(N) : "memory"); }
__device__ __forceinline__ void ldsm4(uint32_t* r, uint32_t addr) { asm volatile("ldmatrix.sync.aligned.m8n8.x4.shared.b16 {%0,%1,%2,%3}, [%4];" : "=r"(r[0]), "=r"(r[1]), "=r"(r[2]), "=r"(r[3]) : "r"(addr) : "memory"); }
__device__ __forceinline__ void ldsm4t(uint32_t* r, uint32_t addr) { asm volatile("ldmatrix.sync.aligned.m8n8.x4.trans.shared.b16 {%0,%1,%2,%3}, [%4];" : "=r"(r[0]), "=r"(r[1]), "=r"(r[2]), "=r"(r[3]) : "r"(addr) : "memory"); }
__device__ __forceinline__ void stsm4(uint32_t addr, const uint32_t* r) { asm volatile("stmatrix.sync.aligned.m8n8.x4.shared.b16 [%4], {%0,%1,%2,%3};" ::"r"(r[0]), "r"(r[1]), "r"(r[2]), "r"(r[3]), "r"(addr) : "memory"); }
__device__ __forceinline__ void lds4(uint32_t* r, uint32_t addr) { asm volatile("ld.shared.v4.u32 {%0,%1,%2,%3}, [%4];" : "=r"(r[0]), "=r"(r[1]), "=r"(r[2]), "=r"(r[3]) : "r"(addr) : "memory"); }
__device__ __forceinline__ void sts4(uint32_t addr, const uint32_t* r) { asm volatile("st.shared.v4.u32 [%4], {%0,%1,%2,%3};" ::"r"(r[0]), "r"(r[1]), "r"(r[2]), "r"(r[3]), "r"(addr) : "memory"); }
__device__ __forceinline__ float2 lds2f(uint32_t addr) { float2 v; asm volatile("ld.shared.v2.f32 {%0,%1}, [%2];" : "=f"(v.x), "=f"(v.y) : "r"(addr) : "memory"); return v; }
__device__ __forceinline__ float lds1f(uint32_t addr) { float v; asm volatile("ld.shared.f32 %0, [%1];" : "=f"(v) : "r"(addr) : "memory"); return v; }
__device__ __forceinline__ void sts1f(uint32_t addr, float v) { asm volatile("st.shared.f32 [%0], %1;" ::"r"(addr), "f"(v) : "memory"); }
__device__ __forceinline__ void sts1(uint32_t addr, uint32_t v) { asm volatile("st.shared.u32 [%0], %1;" ::"r"(addr), "r"(v) : "memory"); }
__device__ __forceinline__ void ldg4_rlx(uint32_t* r, const void* p) { asm volatile("ld.relaxed.gpu.global.v4.u32 {%0,%1,%2,%3}, [%4];" : "=r"(r[0]), "=r"(r[1]), "=r"(r[2]), "=r"(r[3]) : "l"(p) : "memory"); }
__device__ __forceinline__ void ldg2_rlx(uint32_t* r, const void* p) { asm volatile("ld.relaxed.gpu.global.v2.u32 {%0,%1}, [%2];" : "=r"(r[0]), "=r"(r[1]) : "l"(p) : "memory"); }
__device__ __forceinline__ uint32_t ldg1_rlx(const void* p) { uint32_t v; asm volatile("ld.relaxed.gpu.global.u32 %0, [%1];" : "=r"(v) : "l"(p) : "memory"); return v; }
__device__ __forceinline__ void stg4_rlx(void* p, uint32_t a, uint32_t b, uint32_t c, uint32_t d) { asm volatile("st.relaxed.gpu.global.v4.u32 [%0], {%1,%2,%3,%4};" ::"l"(p), "r"(a), "r"(b), "r"(c), "r"(d) : "memory"); }
__device__ __forceinline__ void stg2_rlx(void* p, uint32_t a, uint32_t b) { asm volatile("st.relaxed.gpu.global.v2.u32 [%0], {%1,%2};" ::"l"(p), "r"(a), "r"(b) : "memory"); }
__device__ __forceinline__ void stg1_rlx(void* p, uint32_t a) { asm volatile("st.relaxed.gpu.global.u32 [%0], %1;" ::"l"(p), "r"(a) : "memory"); }
__device__ __forceinline__ void ldg4_nc(uint32_t* r, const void* p) { asm volatile("ld.global.nc.L1::no_allocate.v4.u32 {%0,%1,%2,%3}, [%4];" : "=r"(r[0]), "=r"(r[1]), "=r"(r[2]), "=r"(r[3]) : "l"(p)); }
__device__ __forceinline__ uint64_t mkdesc(uint32_t addr, uint32_t lbo, uint32_t sbo, uint32_t sw) { return (uint64_t)((addr & 0x3FFFF) >> 4) | ((uint64_t)(lbo >> 4) << 16) | ((uint64_t)(sbo >> 4) << 32) | ((uint64_t)sw << 62); }
__device__ __forceinline__ uint32_t pack2(float lo, float hi) { uint32_t r; asm("cvt.rn.bf16x2.f32 %0, %1, %2;" : "=r"(r) : "f"(hi), "f"(lo)); return r; }
__device__ __forceinline__ float blo(uint32_t v) { return __uint_as_float(v << 16); }
__device__ __forceinline__ float bhi(uint32_t v) { return __uint_as_float(v & 0xffff0000u); }
__device__ __forceinline__ float rbf(float x) { return blo(pack2(x, 0.f)); }
__device__ __forceinline__ uint32_t hf2(uint32_t a, uint32_t b, uint32_t c) { uint32_t r; asm("fma.rn.bf16x2 %0, %1, %2, %3;" : "=r"(r) : "r"(a), "r"(b), "r"(c)); return r; }
__device__ __forceinline__ uint32_t movm(uint32_t a) { uint32_t r; asm volatile("movmatrix.sync.aligned.m8n8.trans.b16 %0, %1;" : "=r"(r) : "r"(a)); return r; }
__device__ __forceinline__ float ex2(float x) { float r; asm("ex2.approx.ftz.f32 %0, %1;" : "=f"(r) : "f"(x)); return r; }
__device__ __forceinline__ void mma16(float* d, uint32_t a0, uint32_t a1, uint32_t a2, uint32_t a3, uint32_t b0, uint32_t b1) {
    asm volatile("mma.sync.aligned.m16n8k16.row.col.f32.bf16.bf16.f32 {%0,%1,%2,%3}, {%4,%5,%6,%7}, {%8,%9}, {%0,%1,%2,%3};"
                 : "+f"(d[0]), "+f"(d[1]), "+f"(d[2]), "+f"(d[3]) : "r"(a0), "r"(a1), "r"(a2), "r"(a3), "r"(b0), "r"(b1));
}
__device__ __forceinline__ void mma8(float* d, uint32_t a0, uint32_t a1, uint32_t b0) {
    asm volatile("mma.sync.aligned.m16n8k8.row.col.f32.bf16.bf16.f32 {%0,%1,%2,%3}, {%4,%5}, {%6}, {%0,%1,%2,%3};"
                 : "+f"(d[0]), "+f"(d[1]), "+f"(d[2]), "+f"(d[3]) : "r"(a0), "r"(a1), "r"(b0));
}
__device__ __forceinline__ uint32_t umax4(const uint32_t* v, uint32_t m) { return max(max(max(v[0], v[1]), max(v[2], v[3])), m); }
__device__ __forceinline__ uint32_t fkey(float f) { uint32_t u = __float_as_uint(f); return (u & 0x80000000u) ? ~u : (u | 0x80000000u); }
__device__ __forceinline__ float silu_f(float x) { return x / (1.f + __expf(-x)); }
__device__ __forceinline__ void wgmma_rs_n192(float* d, const uint32_t* a, uint64_t bdesc) {
    asm volatile("wgmma.mma_async.sync.aligned.m64n192k16.f32.bf16.bf16 {%0,%1,%2,%3,%4,%5,%6,%7,%8,%9,%10,%11,%12,%13,%14,%15,%16,%17,%18,%19,%20,%21,%22,%23,%24,%25,%26,%27,%28,%29,%30,%31,%32,%33,%34,%35,%36,%37,%38,%39,%40,%41,%42,%43,%44,%45,%46,%47,%48,%49,%50,%51,%52,%53,%54,%55,%56,%57,%58,%59,%60,%61,%62,%63,%64,%65,%66,%67,%68,%69,%70,%71,%72,%73,%74,%75,%76,%77,%78,%79,%80,%81,%82,%83,%84,%85,%86,%87,%88,%89,%90,%91,%92,%93,%94,%95}, {%96,%97,%98,%99}, %100, 1, 1, 1, 1;"
        : "+f"(d[0]),"+f"(d[1]),"+f"(d[2]),"+f"(d[3]),"+f"(d[4]),"+f"(d[5]),"+f"(d[6]),"+f"(d[7]),"+f"(d[8]),"+f"(d[9]),"+f"(d[10]),"+f"(d[11]),"+f"(d[12]),"+f"(d[13]),"+f"(d[14]),"+f"(d[15]),"+f"(d[16]),"+f"(d[17]),"+f"(d[18]),"+f"(d[19]),"+f"(d[20]),"+f"(d[21]),"+f"(d[22]),"+f"(d[23]),"+f"(d[24]),"+f"(d[25]),"+f"(d[26]),"+f"(d[27]),"+f"(d[28]),"+f"(d[29]),"+f"(d[30]),"+f"(d[31]),"+f"(d[32]),"+f"(d[33]),"+f"(d[34]),"+f"(d[35]),"+f"(d[36]),"+f"(d[37]),"+f"(d[38]),"+f"(d[39]),"+f"(d[40]),"+f"(d[41]),"+f"(d[42]),"+f"(d[43]),"+f"(d[44]),"+f"(d[45]),"+f"(d[46]),"+f"(d[47]),"+f"(d[48]),"+f"(d[49]),"+f"(d[50]),"+f"(d[51]),"+f"(d[52]),"+f"(d[53]),"+f"(d[54]),"+f"(d[55]),"+f"(d[56]),"+f"(d[57]),"+f"(d[58]),"+f"(d[59]),"+f"(d[60]),"+f"(d[61]),"+f"(d[62]),"+f"(d[63]),"+f"(d[64]),"+f"(d[65]),"+f"(d[66]),"+f"(d[67]),"+f"(d[68]),"+f"(d[69]),"+f"(d[70]),"+f"(d[71]),"+f"(d[72]),"+f"(d[73]),"+f"(d[74]),"+f"(d[75]),"+f"(d[76]),"+f"(d[77]),"+f"(d[78]),"+f"(d[79]),"+f"(d[80]),"+f"(d[81]),"+f"(d[82]),"+f"(d[83]),"+f"(d[84]),"+f"(d[85]),"+f"(d[86]),"+f"(d[87]),"+f"(d[88]),"+f"(d[89]),"+f"(d[90]),"+f"(d[91]),"+f"(d[92]),"+f"(d[93]),"+f"(d[94]),"+f"(d[95])
        : "r"(a[0]), "r"(a[1]), "r"(a[2]), "r"(a[3]), "l"(bdesc));
}
__device__ __forceinline__ void wgmma_rs_n48(float* d, const uint32_t* a, uint64_t bdesc) {
    asm volatile("wgmma.mma_async.sync.aligned.m64n48k16.f32.bf16.bf16 {%0,%1,%2,%3,%4,%5,%6,%7,%8,%9,%10,%11,%12,%13,%14,%15,%16,%17,%18,%19,%20,%21,%22,%23}, {%24,%25,%26,%27}, %28, 1, 1, 1, 1;"
        : "+f"(d[0]),"+f"(d[1]),"+f"(d[2]),"+f"(d[3]),"+f"(d[4]),"+f"(d[5]),"+f"(d[6]),"+f"(d[7]),"+f"(d[8]),"+f"(d[9]),"+f"(d[10]),"+f"(d[11]),"+f"(d[12]),"+f"(d[13]),"+f"(d[14]),"+f"(d[15]),"+f"(d[16]),"+f"(d[17]),"+f"(d[18]),"+f"(d[19]),"+f"(d[20]),"+f"(d[21]),"+f"(d[22]),"+f"(d[23])
        : "r"(a[0]), "r"(a[1]), "r"(a[2]), "r"(a[3]), "l"(bdesc));
}
__device__ __forceinline__ void wgmma_rs_n80(float* d, const uint32_t* a, uint64_t bdesc) {
    asm volatile("wgmma.mma_async.sync.aligned.m64n80k16.f32.bf16.bf16 {%0,%1,%2,%3,%4,%5,%6,%7,%8,%9,%10,%11,%12,%13,%14,%15,%16,%17,%18,%19,%20,%21,%22,%23,%24,%25,%26,%27,%28,%29,%30,%31,%32,%33,%34,%35,%36,%37,%38,%39}, {%40,%41,%42,%43}, %44, 1, 1, 1, 1;"
        : "+f"(d[0]),"+f"(d[1]),"+f"(d[2]),"+f"(d[3]),"+f"(d[4]),"+f"(d[5]),"+f"(d[6]),"+f"(d[7]),"+f"(d[8]),"+f"(d[9]),"+f"(d[10]),"+f"(d[11]),"+f"(d[12]),"+f"(d[13]),"+f"(d[14]),"+f"(d[15]),"+f"(d[16]),"+f"(d[17]),"+f"(d[18]),"+f"(d[19]),"+f"(d[20]),"+f"(d[21]),"+f"(d[22]),"+f"(d[23]),"+f"(d[24]),"+f"(d[25]),"+f"(d[26]),"+f"(d[27]),"+f"(d[28]),"+f"(d[29]),"+f"(d[30]),"+f"(d[31]),"+f"(d[32]),"+f"(d[33]),"+f"(d[34]),"+f"(d[35]),"+f"(d[36]),"+f"(d[37]),"+f"(d[38]),"+f"(d[39])
        : "r"(a[0]), "r"(a[1]), "r"(a[2]), "r"(a[3]), "l"(bdesc));
}

template <int NT, int NB, int NL, class F>
__device__ __forceinline__ void mod_unit(int unit, int tid, const __nv_bfloat16* __restrict__ cvec, const __nv_bfloat16* __restrict__ wmod,
                                         uint32_t red, int barid, uint32_t tag, F between) {
    float s[8];
#pragma unroll
    for (int e = 0; e < 8; e++) s[e] = 0.f;
    const int r0 = tid >> 1;
    const __nv_bfloat16* wp = wmod + unit * 16 + (tid & 1) * 8;
#pragma unroll
    for (int b = 0; b < NB; b++) {
        uint32_t w[NL][4]; float cv[NL];
#pragma unroll
        for (int l = 0; l < NL; l++) {
            int r = r0 + (b * NL + l) * (NT / 2);
            bool ok = (NB * NL * (NT / 2) == 640) || r < 640;
            r = ok ? r : 0;
            ldg4_nc(w[l], wp + (size_t)r * 3840);
            cv[l] = ok ? __bfloat162float(cvec[r]) : 0.f;
        }
        if (b == 0) between();
#pragma unroll
        for (int l = 0; l < NL; l++) {
            float sv = rbf(silu_f(cv[l]));
#pragma unroll
            for (int e = 0; e < 4; e++) { s[2 * e] = fmaf(sv, blo(w[l][e]), s[2 * e]); s[2 * e + 1] = fmaf(sv, bhi(w[l][e]), s[2 * e + 1]); }
        }
    }
    const int lane = tid & 31;
    {
        bool u = lane & 2;
#pragma unroll
        for (int e = 0; e < 4; e++) { float snd = u ? s[e] : s[e + 4], keep = u ? s[e + 4] : s[e]; s[e] = keep + __shfl_xor_sync(~0u, snd, 2); }
        u = lane & 4;
#pragma unroll
        for (int e = 0; e < 2; e++) { float snd = u ? s[e] : s[e + 2], keep = u ? s[e + 2] : s[e]; s[e] = keep + __shfl_xor_sync(~0u, snd, 4); }
        u = lane & 8;
        { float snd = u ? s[0] : s[1], keep = u ? s[1] : s[0]; s[0] = keep + __shfl_xor_sync(~0u, snd, 8); }
        s[0] += __shfl_xor_sync(~0u, s[0], 16);
    }
    if (lane < 16) { int col = (lane & 1) * 8 + ((lane >> 1) & 1) * 4 + ((lane >> 2) & 1) * 2 + ((lane >> 3) & 1); sts1f(red + ((tid >> 5) * 16 + col) * 4, s[0]); }
    bar_sync(barid, NT);
    if (tid < 16) {
        float t = 0.f;
#pragma unroll
        for (int w = 0; w < NT / 32; w++) t += lds1f(red + (w * 16 + tid) * 4);
        t = rbf(t);
        int vec = unit / 40;
        if (vec == 1 || vec == 4) t = rbf(1.f + t);
        stg1_rlx(&g_mod[unit * 16 + tid], __float_as_uint(t) | tag);
    }
}

__global__ void __launch_bounds__(384, 1)
fused_kernel(const __grid_constant__ CUtensorMap mx, const __grid_constant__ CUtensorMap mw, const __grid_constant__ CUtensorMap mt,
             const __grid_constant__ CUtensorMap mo, const __grid_constant__ CUtensorMap mg, const __grid_constant__ CUtensorMap mu,
             const __grid_constant__ CUtensorMap md,
             const __nv_bfloat16* __restrict__ xin, const __nv_bfloat16* __restrict__ wqkv, const __nv_bfloat16* __restrict__ wo,
             const __nv_bfloat16* __restrict__ wr, const __nv_bfloat16* __restrict__ wg, const __nv_bfloat16* __restrict__ wu,
             const __nv_bfloat16* __restrict__ wd, const __nv_bfloat16* __restrict__ cvec, const __nv_bfloat16* __restrict__ wmod,
             __nv_bfloat16* __restrict__ out) {
    extern __shared__ __align__(1024) char sm_raw[];
    const uint32_t sm = smem_u32(sm_raw), bars = sm + OFF_BAR;
    const int gp = blockIdx.x >> 4, ix = blockIdx.x & 15;
    const int ti = (gp & 3) * 4 + (ix >> 2), j = (gp >> 2) * 4 + (ix & 3);
    const int role = ti * 8 + j, odd = j & 1;
    const int tid = threadIdx.x, warp = tid >> 5, lane = tid & 31;
    if (tid == 256) {
        pf_map(&mx); pf_map(&mw); pf_map(&mt);
        for (int i = 0; i < 10; i++) mbar_init(bars + B_XF + 8 * i, 1);
        for (int i = 0; i < 4; i++) { mbar_init(bars + B_WF + 8 * i, 1); mbar_init(bars + B_WE + 8 * i, 8); }
        for (int i = 0; i < 8; i++) mbar_init(bars + B_WO + 8 * i, 1);
        mbar_init(bars + B_FG, 1); mbar_init(bars + B_FD, 1); mbar_init(bars + B_G1, 8); mbar_init(bars + B_RDY, 1); mbar_init(bars + B_EP, 3);
        asm volatile("fence.mbarrier_init.release.cluster;" ::: "memory");
    }
    const uint32_t epoch = ldg1_rlx(&g_epoch) + 1;
    const uint32_t tag = epoch & 0xffffu;

    if (warp >= 8) {
        asm volatile("setmaxnreg.dec.sync.aligned.u32 104;");
        if (warp == 8) {
            const int col_main = 80 * j + 16 * odd, col_tail = 80 * j + (odd ? 0 : 64);
            if (lane == 0) {
                for (int c = 0; c < 10; c++) { mbar_expect_tx(bars + B_XF + 8 * c, 16384); tma3d(sm + c * 16384, &mx, c * 64, ti >> 3, (ti & 7) * 128, bars + B_XF + 8 * c); }
                for (int it = 0; it < 4; it++) {
                    mbar_expect_tx(bars + B_WF + 8 * it, WST);
                    tma4d(sm + OFF_W + it * WST, &mw, 0, it * 32, col_main >> 5, 0, bars + B_WF + 8 * it);
                    tma3d(sm + OFF_W + it * WST + 12288, &mt, col_tail, it * 32, 0, bars + B_WF + 8 * it);
                }
                l2_prefetch(wqkv + (size_t)(128 + role * 4) * 1920, 4 * 3840);
                pf_map(&mo); pf_map(&mg); pf_map(&mu); pf_map(&md);
            }
            __syncwarp();
            bar_sync(0, 384);
            if (lane == 0) {
                for (int it = 4; it < 20; it++) {
                    const int s = it & 3;
                    mbar_wait(bars + B_WE + 8 * s, ((it >> 2) & 1) ^ 1);
                    mbar_expect_tx(bars + B_WF + 8 * s, WST);
                    tma4d(sm + OFF_W + s * WST, &mw, 0, it * 32, col_main >> 5, 0, bars + B_WF + 8 * s);
                    tma3d(sm + OFF_W + s * WST + 12288, &mt, col_tail, it * 32, 0, bars + B_WF + 8 * s);
                    if (!(it & 1)) {
                        const int w = (it - 4) >> 1;
                        const int src = w == 0 ? j : (w <= j ? w - 1 : w);
                        const uint32_t b = bars + B_WO + 8 * w, dst = sm + w * WST;
                        mbar_expect_tx(b, WST);
                        tma2d(dst, &mo, col_main, src * 80, b); tma2d(dst + 5120, &mo, col_main + 32, src * 80, b); tma2d(dst + 10240, &mo, col_tail, src * 80, b);
                    }
                }
                mbar_wait(bars + B_G1, 0);
                if (role < 108) { mbar_expect_tx(bars + B_FG, 40960); tma3d(sm + OFF_WG, &mg, role * 16, 0, 0, bars + B_FG); tma3d(sm + OFF_WU, &mu, role * 16, 0, 0, bars + B_FG); }
                if (role >= 88) { mbar_expect_tx(bars + B_FD, 55296); tma3d(sm + OFF_WD, &md, (role - 88) * 16, 0, 0, bars + B_FD); }
            }
        } else {
            const int at = tid - 288;
            bar_sync(0, 384);
#pragma unroll 1
            for (int v = at; v < 320; v += 96) {
                uint32_t w[4]; int g = 0;
                do { ldg4_rlx(w, &g_mod[v * 4]); if (++g > SPIN_LIMIT) break; } while (((w[0] ^ tag) | (w[1] ^ tag) | (w[2] ^ tag) | (w[3] ^ tag)) & 0xffffu);
                const int isc = v >= 160, k0 = (v - isc * 160) * 4;
                const uint32_t a = sm + OFF_TAB + (k0 >> 4) * 64 + ((k0 & 7) >> 1) * 16 + ((k0 >> 3) & 1) * 4 + (isc ? 0 : 8);
                sts1(a, __byte_perm(w[0], w[1], 0x7632)); sts1(a + 16, __byte_perm(w[2], w[3], 0x7632));
            }
            STAMPT(2, 288);
            bar_sync(1, 352);
            if (at == 0) {
                asm volatile("fence.acq_rel.gpu;" ::: "memory");
                stg1_rlx(&g_ready[role], epoch);
            }
            if (at == 32) {
                l2_prefetch(wo + (size_t)role * 3200, 6400);
                for (int r = 0; r < 5; r++) l2_prefetch(wmod + (size_t)(role * 5 + r) * 3840 + 1280, 5120);
                l2_prefetch(wg + (size_t)role * 8640, 17280); l2_prefetch(wu + (size_t)role * 8640, 17280); l2_prefetch(wd + (size_t)role * 8640, 17280);
            }
            const int nun = role >= 80 ? 2 : (role < 64 ? 1 : 0);
#pragma unroll 1
            for (int u = 0; u < nun; u++) {
                const int unit = role >= 80 ? 144 + (role - 80) * 2 + u : 80 + role;
                mod_unit<96, 2, 7>(unit, at, cvec, wmod, sm + OFF_RED2 + u * 192, 3, tag, [] {});
            }
            if (warp == 9) {
                uint32_t w[4]; int g = 0;
                do { ldg4_rlx(w, &g_ready[lane * 4]); if (++g > SPIN_LIMIT) break; } while (w[0] != epoch || w[1] != epoch || w[2] != epoch || w[3] != epoch);
                asm volatile("fence.acq_rel.gpu;" ::: "memory");
                __syncwarp();
                if (lane == 0) mbar_arrive(bars + B_RDY);
            }
            float us = 0.f, ss = 0.f;
#pragma unroll 1
            for (int k = at; k < 640; k += 96) {
                uint32_t sb, cb; int g = 0;
                do { sb = ldg1_rlx(&g_mod[1920 + k]); cb = ldg1_rlx(&g_mod[2560 + k]); if (++g > SPIN_LIMIT) break; } while (((sb ^ tag) | (cb ^ tag)) & 0xffffu);
                const float w = __bfloat162float(wr[k]);
                us = fmaf(bhi(cb), w, us); ss = fmaf(bhi(sb), w, ss);
                const int c = k - 80 * j;
                if (c >= 0 && c < 80) {
                    const int p = odd ? (c < 16 ? c + 64 : c - 16) : c;
                    sts1f(sm + OFF_EP + (80 + p) * 4, bhi(cb) * w); sts1f(sm + OFF_EP + (160 + p) * 4, bhi(cb)); sts1f(sm + OFF_EP + (240 + p) * 4, bhi(sb));
                }
            }
            {
                const int k = at < 80 ? 80 * j + at : (role >= 88 ? (role - 88) * 16 + at - 80 : 0);
                uint32_t ga, gb; int g = 0;
                do { ga = ldg1_rlx(&g_mod[1280 + k]); gb = ldg1_rlx(&g_mod[3200 + k]); if (++g > SPIN_LIMIT) break; } while (((ga ^ tag) | (gb ^ tag)) & 0xffffu);
                if (at < 80) { const int p = odd ? (at < 16 ? at + 64 : at - 16) : at; sts1f(sm + OFF_EP + p * 4, bhi(ga)); sts1f(sm + OFF_EP + (320 + p) * 4, bhi(gb)); }
                else sts1f(sm + OFF_EP + (400 + at - 80) * 4, bhi(gb));
            }
#pragma unroll
            for (int o = 16; o; o >>= 1) { us += __shfl_xor_sync(~0u, us, o); ss += __shfl_xor_sync(~0u, ss, o); }
            if (lane == 0) { sts1f(sm + OFF_EP + (416 + (warp - 9) * 2) * 4, us); sts1f(sm + OFF_EP + (417 + (warp - 9) * 2) * 4, ss); }
            __syncwarp();
            if (lane == 0) mbar_arrive(bars + B_EP);
            STAMPT(20, 288);
        }
    } else {
        asm volatile("setmaxnreg.inc.sync.aligned.u32 200;");
        const int g = lane >> 2, q = lane & 3;
        const int tw = ti * 8 + warp;
        auto resets = [&] {
#pragma unroll
            for (int s = 0; s < 5; s++) stg4_rlx(&g_o[(tw * 8 + j) * 160 + s * 32 + lane], SENT, SENT, SENT, SENT);
            stg4_rlx(&g_cand[(tw * 8 + j) * 32 + lane], SENT, SENT, SENT, SENT);
            if (tid < 160) stg4_rlx(&g_halo[role * 160 + tid], SENT, SENT, SENT, SENT);
            if (tid >= 128) stg4_rlx(&g_stats[(ti * 128 + j * 16) * 8 + tid - 128], SENT, SENT, SENT, SENT);
            if (tid == 160) stg2_rlx(&g_rec[ti * 8 + j], SENT, SENT);
            if (tid >= 164 && tid < 168 && role < 112) stg2_rlx(&g_a[role * 4 + tid - 164], SENT, SENT);
        };
        if (role < 80) mod_unit<256, 1, 5>(role, tid, cvec, wmod, sm + OFF_RED, 2, tag, resets);
        else resets();
        STAMP(0);
        bar_sync(0, 384);
        const int row = warp * 16 + (lane & 15);
        const uint32_t xrow = sm + row * 128, hi = lane >> 4, sw = row & 7;
        const uint32_t xa0 = xrow + (((0 + hi) ^ sw) << 4), xa1 = xrow + (((2 + hi) ^ sw) << 4), xa2 = xrow + (((4 + hi) ^ sw) << 4), xa3 = xrow + (((6 + hi) ^ sw) << 4);
        uint32_t rr0, rr1, nn0, nn1;
        {
            float gA[2][4] = {}, gB[2][4] = {}, sd[2][4] = {};
#pragma unroll 1
            for (int c = 0; c < 10; c++) {
                mbar_wait(bars + B_XF + 8 * c, 0);
                uint32_t a[4][4];
                ldsm4(a[0], xa0 + c * 16384); ldsm4(a[1], xa1 + c * 16384); ldsm4(a[2], xa2 + c * 16384); ldsm4(a[3], xa3 + c * 16384);
#pragma unroll
                for (int k = 0; k < 4; k++) {
                    mma16(gA[k & 1], a[k][0], a[k][1], a[k][2], a[k][3], a[k][0], a[k][2]);
                    mma16(gB[k & 1], a[k][0], a[k][1], a[k][2], a[k][3], a[k][1], a[k][3]);
                    mma16(sd[k & 1], a[k][0], a[k][1], a[k][2], a[k][3], 0x3f803f80u, 0x3f803f80u);
                }
            }
            const float ss0 = __shfl_sync(~0u, (g & 1) ? gA[0][1] + gA[1][1] : gA[0][0] + gA[1][0], (lane & ~3) | (g >> 1));
            const float ss1 = __shfl_sync(~0u, (g & 1) ? gB[0][3] + gB[1][3] : gB[0][2] + gB[1][2], (lane & ~3) | (g >> 1));
            const float m0 = (sd[0][0] + sd[1][0]) * (1.f / 640), m1 = (sd[0][2] + sd[1][2]) * (1.f / 640);
            const float r0 = rbf(rsqrtf(fmaxf(ss0 * (1.f / 640) - m0 * m0, 0.f) + 1e-5f)), r1 = rbf(rsqrtf(fmaxf(ss1 * (1.f / 640) - m1 * m1, 0.f) + 1e-5f));
            rr0 = pack2(r0, r0); rr1 = pack2(r1, r1); nn0 = pack2(-m0 * r0, -m0 * r0); nn1 = pack2(-m1 * r1, -m1 * r1);
        }
        uint32_t xr[5][4];
#pragma unroll
        for (int s = 0; s < 5; s++) {
            const int ks = 5 * j + (odd ? (s == 4 ? 0 : s + 1) : s);
            ldsm4(xr[s], xrow + (ks >> 2) * 16384 + ((((ks & 3) * 2 + hi) ^ sw) << 4));
        }
        STAMP(1);
        bar_sync(1, 352);
        STAMP(3);
        float acc[120];
#pragma unroll
        for (int i = 0; i < 120; i++) acc[i] = 0.f;
        {
            uint32_t a[2][2][4], raw[2][4], tt[2][4];
            const uint32_t tb = sm + OFF_TAB + q * 16;
            auto load = [&](int it) {
                const uint32_t off = (it >> 1) * 16384;
                ldsm4(raw[0], ((it & 1) ? xa2 : xa0) + off); ldsm4(raw[1], ((it & 1) ? xa3 : xa1) + off);
                lds4(tt[0], tb + it * 128); lds4(tt[1], tb + it * 128 + 64);
            };
            auto xform = [&](uint32_t (*dst)[4]) {
#pragma unroll
                for (int h = 0; h < 2; h++) {
                    dst[h][0] = hf2(hf2(raw[h][0], rr0, nn0), tt[h][0], tt[h][2]); dst[h][1] = hf2(hf2(raw[h][1], rr1, nn1), tt[h][0], tt[h][2]);
                    dst[h][2] = hf2(hf2(raw[h][2], rr0, nn0), tt[h][1], tt[h][3]); dst[h][3] = hf2(hf2(raw[h][3], rr1, nn1), tt[h][1], tt[h][3]);
                }
            };
            const uint64_t dm0 = mkdesc(sm + OFF_W, 2048, 512, 2), dt0 = mkdesc(sm + OFF_W + 12288, 1024, 256, 3);
            load(0); xform(a[0]);
#pragma unroll 1
            for (int i4 = 0; i4 < 5; i4++) {
#pragma unroll
                for (int u = 0; u < 4; u++) {
                    const int it = i4 * 4 + u;
                    mbar_wait(bars + B_WF + 8 * u, i4 & 1);
                    wg_fence();
#pragma unroll
                    for (int h = 0; h < 2; h++) { wgmma_rs_n192(acc, a[u & 1][h], dm0 + (u * WST + h * 1024) / 16); wgmma_rs_n48(acc + 96, a[u & 1][h], dt0 + (u * WST + h * 512) / 16); }
                    wg_commit();
                    if (u < 3 || i4 < 4) load(it + 1);
                    wg_wait<1>();
                    if (lane == 0 && it > 0) mbar_arrive(bars + B_WE + 8 * ((u + 3) & 3));
                    xform(a[(u + 1) & 1]);
                }
            }
            wg_wait<0>();
        }
        STAMP(4);
        uint32_t o[5][4];
        {
            uint32_t Q[10][2], K[10][2], V[10][2];
            if (!odd) {
#pragma unroll
                for (int t = 0; t < 10; t++) {
                    const int iq = t < 8 ? t * 4 : 96 + (t - 8) * 4, ik = t < 8 ? 32 + t * 4 : 104 + (t - 8) * 4, iv = t < 8 ? 64 + t * 4 : 112 + (t - 8) * 4;
                    Q[t][0] = pack2(acc[iq], acc[iq + 1]); Q[t][1] = pack2(acc[iq + 2], acc[iq + 3]);
                    K[t][0] = pack2(acc[ik], acc[ik + 1]); K[t][1] = pack2(acc[ik + 2], acc[ik + 3]);
                    V[t][0] = pack2(acc[iv], acc[iv + 1]); V[t][1] = pack2(acc[iv + 2], acc[iv + 3]);
                }
            } else {
#pragma unroll
                for (int t = 0; t < 10; t++) {
                    const int iq = t >= 2 ? (t - 2) * 4 : 96 + t * 4, ik = t >= 2 ? 32 + (t - 2) * 4 : 104 + t * 4, iv = t >= 2 ? 64 + (t - 2) * 4 : 112 + t * 4;
                    Q[t][0] = pack2(acc[iq], acc[iq + 1]); Q[t][1] = pack2(acc[iq + 2], acc[iq + 3]);
                    K[t][0] = pack2(acc[ik], acc[ik + 1]); K[t][1] = pack2(acc[ik + 2], acc[ik + 3]);
                    V[t][0] = pack2(acc[iv], acc[iv + 1]); V[t][1] = pack2(acc[iv + 2], acc[iv + 3]);
                }
            }
            uint32_t hs[20];
#pragma unroll
            for (int t = 0; t < 10; t++) { V[t][1] = movm(V[t][1]); hs[t] = K[t][1]; hs[10 + t] = V[t][1]; }
            mbar_wait(bars + B_RDY, 0);
            if (warp == 7) {
#pragma unroll
                for (int s = 0; s < 5; s++) stg4_rlx(&g_halo[role * 160 + s * 32 + lane], hs[4 * s], hs[4 * s + 1], hs[4 * s + 2], hs[4 * s + 3]);
            } else {
#pragma unroll
                for (int s = 0; s < 5; s++) sts4(sm + (8 + (s >> 2)) * 16384 + warp * 2048 + (s & 3) * 512 + lane * 16, hs + 4 * s);
            }
#pragma unroll
            for (int t = 0; t < 10; t++) V[t][0] = movm(V[t][0]);
            bar_sync(2, 256);
            uint32_t hl[20];
            const bool first = (ti & 7) == 0 && warp == 0;
            if (warp > 0) {
#pragma unroll
                for (int s = 0; s < 5; s++) lds4(hl + 4 * s, sm + (8 + (s >> 2)) * 16384 + (warp - 1) * 2048 + (s & 3) * 512 + lane * 16);
            } else if (first) {
#pragma unroll
                for (int s = 0; s < 20; s++) hl[s] = 0;
            } else {
                int gd = 0; uint32_t m;
                do {
                    m = 0;
#pragma unroll
                    for (int s = 0; s < 5; s++) ldg4_rlx(hl + 4 * s, &g_halo[(role - 8) * 160 + s * 32 + lane]);
#pragma unroll
                    for (int s = 0; s < 5; s++) m = umax4(hl + 4 * s, m);
                    if (++gd > SPIN_LIMIT) break;
                } while (m == SENT);
                __syncwarp();
            }
            if (lane == 0) mbar_arrive(bars + B_G1);
            STAMP(5);
            const bool gt0 = 2 * q > g, gt1 = 2 * q + 1 > g;
            const uint32_t mgt = (gt0 ? 0xffffu : 0u) | (gt1 ? 0xffff0000u : 0u);
            const float cs = 0.22360679774997896f * 1.4426950408889634f;
            float O[12][4];
#pragma unroll
            for (int h = 0; h < 4; h++) {
                const int ts = (h >> 1) * 5 + 2, ta = (h >> 1) * 5 + (h & 1) * 3, tb2 = ta + 1;
                const bool mine = ((q >> 1) == (h & 1));
                const uint32_t qs0 = mine ? Q[ts][0] : 0u, qs1 = mine ? Q[ts][1] : 0u;
                float sa[4] = {}, sb[4] = {};
                mma16(sa, Q[ta][0], 0u, 0u, Q[ta][1], hl[ta], K[ta][1]);
                mma16(sa, Q[tb2][0], 0u, 0u, Q[tb2][1], hl[tb2], K[tb2][1]);
                mma16(sa, qs0, 0u, 0u, qs1, hl[ts], K[ts][1]);
                mma16(sb, Q[ta][0], Q[ta][1], Q[tb2][0], Q[tb2][1], K[ta][0], K[tb2][0]);
                mma8(sb, qs0, qs1, K[ts][0]);
                float t0 = gt0 ? (first ? -INFINITY : sa[0]) : sb[0], t1 = gt1 ? (first ? -INFINITY : sa[1]) : sb[1];
                float b0 = gt0 ? sb[2] : sa[2], b1 = gt1 ? sb[3] : sa[3];
                float mt_ = fmaxf(t0, t1), mb = fmaxf(b0, b1);
                mt_ = fmaxf(mt_, __shfl_xor_sync(~0u, mt_, 1)); mb = fmaxf(mb, __shfl_xor_sync(~0u, mb, 1));
                mt_ = fmaxf(mt_, __shfl_xor_sync(~0u, mt_, 2)); mb = fmaxf(mb, __shfl_xor_sync(~0u, mb, 2));
                t0 = ex2((t0 - mt_) * cs); t1 = ex2((t1 - mt_) * cs); b0 = ex2((b0 - mb) * cs); b1 = ex2((b1 - mb) * cs);
                float lt = t0 + t1, lb = b0 + b1;
                lt += __shfl_xor_sync(~0u, lt, 1); lb += __shfl_xor_sync(~0u, lb, 1);
                lt += __shfl_xor_sync(~0u, lt, 2); lb += __shfl_xor_sync(~0u, lb, 2);
                lt = __frcp_rn(lt); lb = __frcp_rn(lb);
                const uint32_t pt = pack2(t0 * lt, t1 * lt), pb = pack2(b0 * lb, b1 * lb);
                const uint32_t pA = pt & mgt, pBt = pt & ~mgt, pBb = pb & mgt, pC = pb & ~mgt;
#pragma unroll
                for (int e = 0; e < 3; e++) {
                    const int t = e == 0 ? ta : (e == 1 ? tb2 : ts);
                    float* d = O[h * 3 + e];
                    d[0] = d[1] = d[2] = d[3] = 0.f;
                    mma16(d, pA, 0u, pBt, pBb, hl[10 + t], V[t][0]);
                    mma8(d, 0u, pC, V[t][1]);
                }
            }
            uint32_t of[10][2];
#pragma unroll
            for (int p = 0; p < 2; p++) {
                const float* e0 = O[p * 6], *e1 = O[p * 6 + 1], *s0 = O[p * 6 + 2], *f0 = O[p * 6 + 3], *f1 = O[p * 6 + 4], *s1 = O[p * 6 + 5];
                of[p * 5][0] = pack2(e0[0], e0[1]); of[p * 5][1] = pack2(e0[2], e0[3]);
                of[p * 5 + 1][0] = pack2(e1[0], e1[1]); of[p * 5 + 1][1] = pack2(e1[2], e1[3]);
                of[p * 5 + 2][0] = (q & 2) ? pack2(s1[0], s1[1]) : pack2(s0[0], s0[1]); of[p * 5 + 2][1] = (q & 2) ? pack2(s1[2], s1[3]) : pack2(s0[2], s0[3]);
                of[p * 5 + 3][0] = pack2(f0[0], f0[1]); of[p * 5 + 3][1] = pack2(f0[2], f0[3]);
                of[p * 5 + 4][0] = pack2(f1[0], f1[1]); of[p * 5 + 4][1] = pack2(f1[2], f1[3]);
            }
#pragma unroll
            for (int s = 0; s < 5; s++) {
                o[s][0] = of[2 * s][0]; o[s][1] = of[2 * s][1]; o[s][2] = of[2 * s + 1][0]; o[s][3] = of[2 * s + 1][1];
                stg4_rlx(&g_o[(tw * 8 + j) * 160 + s * 32 + lane], o[s][0], o[s][1], o[s][2], o[s][3]);
            }
        }
        STAMP(6);
        float ac2[40];
#pragma unroll
        for (int i = 0; i < 40; i++) ac2[i] = 0.f;
        {
            const uint64_t d0 = mkdesc(sm, 5120, 512, 2);
            uint32_t ab[3][5][4];
            const uint4* ob = &g_o[tw * 8 * 160 + lane];
            auto ldsrc = [&](int w, uint32_t (*dst)[4]) {
                const int src = w <= j ? w - 1 : w;
#pragma unroll
                for (int s = 0; s < 5; s++) ldg4_rlx(dst[s], ob + src * 160 + s * 32);
            };
            mbar_wait(bars + B_WO, 0);
            wg_fence();
#pragma unroll
            for (int s = 0; s < 5; s++) wgmma_rs_n80(ac2, o[s], d0 + s * 64);
            wg_commit();
            ldsrc(1, ab[1]); ldsrc(2, ab[2]); ldsrc(3, ab[0]);
#pragma unroll
            for (int w = 1; w < 8; w++) {
                uint32_t (*cur)[4] = ab[w % 3];
                int gd = 0;
                while (true) {
                    uint32_t m = 0;
#pragma unroll
                    for (int s = 0; s < 5; s++) m = umax4(cur[s], m);
                    if (m != SENT) break;
                    if (++gd > SPIN_LIMIT) break;
                    ldsrc(w, cur);
                }
                __syncwarp();
                if (w == 1) STAMP(7);
                mbar_wait(bars + B_WO + 8 * w, 0);
                wg_fence();
#pragma unroll
                for (int s = 0; s < 5; s++) wgmma_rs_n80(ac2, cur[s], d0 + (w * WST) / 16 + s * 64);
                wg_commit();
                if (w >= 2 && w + 2 < 8) { wg_wait<1>(); ldsrc(w + 2, ab[(w + 2) % 3]); }
            }
            wg_wait<0>();
        }
        STAMP(8);
        mbar_wait(bars + B_EP, 0);
        const uint32_t ep = sm + OFF_EP + q * 8;
        {
            float s0 = 0.f, s1 = 0.f, q0 = 0.f, q1 = 0.f, d0 = 0.f, d1 = 0.f;
#pragma unroll
            for (int t = 0; t < 10; t++) {
                const float2 ga = lds2f(ep + t * 32), u2 = lds2f(ep + 320 + t * 32);
                const uint32_t x0 = xr[t >> 1][(t & 1) * 2], x1 = xr[t >> 1][(t & 1) * 2 + 1];
                float* a = ac2 + t * 4;
                a[0] = fmaf(ga.x, a[0], blo(x0)); a[1] = fmaf(ga.y, a[1], bhi(x0)); a[2] = fmaf(ga.x, a[2], blo(x1)); a[3] = fmaf(ga.y, a[3], bhi(x1));
                s0 += a[0] + a[1]; s1 += a[2] + a[3];
                q0 = fmaf(a[0], a[0], fmaf(a[1], a[1], q0)); q1 = fmaf(a[2], a[2], fmaf(a[3], a[3], q1));
                d0 = fmaf(a[0], u2.x, fmaf(a[1], u2.y, d0)); d1 = fmaf(a[2], u2.x, fmaf(a[3], u2.y, d1));
            }
            const bool u = q & 1;
            float s = (u ? s1 : s0) + __shfl_xor_sync(~0u, u ? s0 : s1, 1), qq = (u ? q1 : q0) + __shfl_xor_sync(~0u, u ? q0 : q1, 1), d = (u ? d1 : d0) + __shfl_xor_sync(~0u, u ? d0 : d1, 1);
            s += __shfl_xor_sync(~0u, s, 2); qq += __shfl_xor_sync(~0u, qq, 2); d += __shfl_xor_sync(~0u, d, 2);
            if (q < 2) stg4_rlx(&g_stats[(tw * 16 + g + q * 8) * 8 + j], __float_as_uint(s), __float_as_uint(qq), __float_as_uint(d), 0u);
        }
        STAMP(9);
        float mean0, mean1, rs0, rs1, r0, r1;
        {
            uint32_t st[4][4]; int gd = 0; uint32_t m;
            const uint4* sp = &g_stats[(tw * 16 + g) * 8 + 2 * q];
            do {
                ldg4_rlx(st[0], sp); ldg4_rlx(st[1], sp + 1); ldg4_rlx(st[2], sp + 64); ldg4_rlx(st[3], sp + 65);
                m = umax4(st[0], umax4(st[1], umax4(st[2], umax4(st[3], 0))));
                if (++gd > SPIN_LIMIT) break;
            } while (m == SENT);
            __syncwarp();
            float v[6];
#pragma unroll
            for (int e = 0; e < 3; e++) { v[e] = __uint_as_float(st[0][e]) + __uint_as_float(st[1][e]); v[3 + e] = __uint_as_float(st[2][e]) + __uint_as_float(st[3][e]); }
#pragma unroll
            for (int e = 0; e < 6; e++) { v[e] += __shfl_xor_sync(~0u, v[e], 1); v[e] += __shfl_xor_sync(~0u, v[e], 2); }
            const float2 u0 = lds2f(sm + OFF_EP + 416 * 4), u1 = lds2f(sm + OFF_EP + 418 * 4), u2 = lds2f(sm + OFF_EP + 420 * 4);
            const float U = u0.x + u1.x + u2.x, S = u0.y + u1.y + u2.y;
            mean0 = v[0] * (1.f / 640); mean1 = v[3] * (1.f / 640);
            rs0 = rsqrtf(fmaxf(v[1] * (1.f / 640) - mean0 * mean0, 0.f) + 1e-5f); rs1 = rsqrtf(fmaxf(v[4] * (1.f / 640) - mean1 * mean1, 0.f) + 1e-5f);
            r0 = fmaf(rs0, v[2] - mean0 * U, S); r1 = fmaf(rs1, v[5] - mean1 * U, S);
        }
        STAMP(10);
        const uint32_t k0 = fkey(r0), k1 = fkey(r1);
        const uint32_t kmax = __reduce_max_sync(~0u, max(k0, k1));
        const int crow = __reduce_min_sync(~0u, k0 == kmax ? g : (k1 == kmax ? g + 8 : 99));
        const int tok_base = ((ti & 7) * 128 + warp * 16) * 2 + (ti >> 3);
        if (warp == j && lane == (crow & 7) * 4) stg2_rlx(&g_rec[tw], __float_as_uint(crow < 8 ? r0 : r1), tok_base + 2 * crow);
        uint32_t ov[5][4];
        {
            uint32_t hw[10]; float bs[20];
            const bool up = crow >= 8;
#pragma unroll
            for (int t = 0; t < 10; t++) {
                const float2 cb = lds2f(ep + 640 + t * 32), sb = lds2f(ep + 960 + t * 32), gb = lds2f(ep + 1280 + t * 32);
                const float* a = ac2 + t * 4;
                const float h0 = fmaf((a[0] - mean0) * rs0, cb.x, sb.x), h1 = fmaf((a[1] - mean0) * rs0, cb.y, sb.y);
                const float h2 = fmaf((a[2] - mean1) * rs1, cb.x, sb.x), h3 = fmaf((a[3] - mean1) * rs1, cb.y, sb.y);
                const float o0 = fmaf(gb.x, h0, a[0]), o1 = fmaf(gb.y, h1, a[1]), o2 = fmaf(gb.x, h2, a[2]), o3 = fmaf(gb.y, h3, a[3]);
                hw[t] = up ? pack2(h2, h3) : pack2(h0, h1); bs[2 * t] = up ? o2 : o0; bs[2 * t + 1] = up ? o3 : o1;
                ov[t >> 1][(t & 1) * 2] = pack2(o0, o1); ov[t >> 1][(t & 1) * 2 + 1] = pack2(o2, o3);
            }
            if (g == (crow & 7)) {
                uint4* cp = &g_cand[(tw * 8 + j) * 32 + q * 8];
                stg4_rlx(cp, hw[0], hw[1], hw[2], hw[3]); stg4_rlx(cp + 1, hw[4], hw[5], hw[6], hw[7]); stg4_rlx(cp + 2, hw[8], hw[9], 0u, 0u);
#pragma unroll
                for (int s = 0; s < 5; s++) stg4_rlx(cp + 3 + s, __float_as_uint(bs[4 * s]), __float_as_uint(bs[4 * s + 1]), __float_as_uint(bs[4 * s + 2]), __float_as_uint(bs[4 * s + 3]));
            }
        }
        STAMP(11);
        bar_sync(2, 256);
        const uint32_t stg = sm + warp * 2816;
#pragma unroll
        for (int s = 0; s < 5; s++) { const int c16 = odd ? (s == 4 ? 0 : s + 1) : s; stsm4(stg + (lane & 15) * 176 + c16 * 32 + hi * 16, ov[s]); }
        __syncwarp();
        uint32_t oc[5][4];
#pragma unroll
        for (int s = 0; s < 5; s++) { const int c = s * 32 + lane, r = c / 10; lds4(oc[s], stg + r * 176 + (c - r * 10) * 16); }
#pragma unroll
        for (int s = 0; s < 5; s++) {
            const int c = s * 32 + lane, r = c / 10;
            if (r != crow) *(uint4*)(out + (size_t)(tok_base + 2 * r) * 640 + 80 * j + (c - r * 10) * 8) = make_uint4(oc[s][0], oc[s][1], oc[s][2], oc[s][3]);
        }
        uint32_t fg[5][4], fu[5][4];
        const uint32_t frow = (lane & 7) + (lane >> 4) * 8, fh = (lane >> 3) & 1;
        if (role < 108) {
            mbar_wait(bars + B_FG, 0);
#pragma unroll
            for (int s = 0; s < 5; s++) {
                const int k = 80 * warp + ((warp & 1) ? (s == 4 ? 0 : 16 * s + 16) : 16 * s) + frow;
                const uint32_t off = k * 32 + ((fh ^ ((k >> 2) & 1)) << 4);
                ldsm4t(fg[s], sm + OFF_WG + off); ldsm4t(fu[s], sm + OFF_WU + off);
            }
        }
        STAMP(12);
        int win; float rwin; int tokwin;
        {
            uint32_t rc[2][4]; int gd = 0;
            do {
                ldg4_rlx(rc[0], &g_rec[lane * 4]); ldg4_rlx(rc[1], &g_rec[lane * 4 + 2]);
                if (++gd > SPIN_LIMIT) break;
            } while (umax4(rc[0], umax4(rc[1], 0)) == SENT);
            __syncwarp();
            uint32_t bk = 0, bt = 0xffffu, bi = 0, br = 0;
#pragma unroll
            for (int e = 0; e < 4; e++) {
                const uint32_t rb = rc[e >> 1][(e & 1) * 2], tk = rc[e >> 1][(e & 1) * 2 + 1], kk = fkey(__uint_as_float(rb));
                if (e == 0 || kk > bk || (kk == bk && tk < bt)) { bk = kk; bt = tk; bi = lane * 4 + e; br = rb; }
            }
            const uint32_t gk = __reduce_max_sync(~0u, bk);
            const uint32_t sel = __reduce_min_sync(~0u, bk == gk ? (bt << 8 | bi) : 0xffffffffu);
            win = sel & 0xff; tokwin = sel >> 8;
            rwin = __uint_as_float(__shfl_sync(~0u, br, win >> 2));
        }
        STAMP(13);
        if (role == 0 && tid == 0) stg1_rlx(&g_epoch, epoch);
        if (role < 108) {
            uint32_t hb[3][4]; int gd = 0;
            const uint4* cp = &g_cand[(win * 8 + warp) * 32 + q * 8];
            do {
                ldg4_rlx(hb[0], cp); ldg4_rlx(hb[1], cp + 1); ldg4_rlx(hb[2], cp + 2);
                if (++gd > SPIN_LIMIT) break;
            } while (umax4(hb[0], umax4(hb[1], umax4(hb[2], 0))) == SENT);
            __syncwarp();
            float dg[2][4] = {}, du[2][4] = {};
#pragma unroll
            for (int s = 0; s < 5; s++) {
                const uint32_t b0 = hb[s >> 1][(s & 1) * 2], b1 = hb[s >> 1][(s & 1) * 2 + 1];
                mma16(dg[s & 1], fg[s][0], fg[s][1], fg[s][2], fg[s][3], b0, b1);
                mma16(du[s & 1], fu[s][0], fu[s][1], fu[s][2], fu[s][3], b0, b1);
            }
            const float mine = q == 0 ? dg[0][0] + dg[1][0] : q == 1 ? dg[0][2] + dg[1][2] : q == 2 ? du[0][0] + du[1][0] : du[0][2] + du[1][2];
            sts1f(sm + OFF_RED + (warp * 32 + q * 8 + g) * 4, mine);
            bar_sync(2, 256);
            if (warp == 0) {
                float t = 0.f;
#pragma unroll
                for (int w = 0; w < 8; w++) t += lds1f(sm + OFF_RED + (w * 32 + lane) * 4);
                t = rbf(t);
                const float uu = __shfl_down_sync(~0u, t, 16);
                const float av = rbf(silu_f(t)) * uu;
                const float a0 = __shfl_sync(~0u, av, (lane & 3) * 2), a1 = __shfl_sync(~0u, av, (lane & 3) * 2 + 1);
                const float a2 = __shfl_sync(~0u, av, (lane & 3) * 2 + 8), a3 = __shfl_sync(~0u, av, (lane & 3) * 2 + 9);
                if (lane < 4) stg2_rlx(&g_a[role * 4 + lane], pack2(a0, a1), pack2(a2, a3));
            }
        }
        STAMP(14);
        if (win != tw) {
#pragma unroll
            for (int s = 0; s < 5; s++) {
                const int c = s * 32 + lane, r = c / 10;
                if (r == crow) *(uint4*)(out + (size_t)(tok_base + 2 * r) * 640 + 80 * j + (c - r * 10) * 8) = make_uint4(oc[s][0], oc[s][1], oc[s][2], oc[s][3]);
            }
        }
        if (role >= 88) {
            const int d = role - 88, dj = d / 5, dm = d - dj * 5, sp = (dj & 1) ? (dm == 0 ? 4 : dm - 1) : dm;
            uint32_t fd[14][4];
            mbar_wait(bars + B_FD, 0);
#pragma unroll
            for (int s = 0; s < 14; s++) {
                const int ks = min(warp + 8 * s, 107), k = ks * 16 + frow;
                ldsm4t(fd[s], sm + OFF_WD + k * 32 + ((fh ^ ((k >> 2) & 1)) << 4));
            }
            uint32_t bsv[4]; int gd = 0;
            do { ldg4_rlx(bsv, &g_cand[(win * 8 + dj) * 32 + q * 8 + 3 + sp]); if (++gd > SPIN_LIMIT) break; } while (umax4(bsv, 0) == SENT);
            uint32_t av[14][2]; uint32_t m;
            do {
                m = 0;
#pragma unroll
                for (int s = 0; s < 14; s++) ldg2_rlx(av[s], &g_a[min(warp + 8 * s, 107) * 4 + q]);
#pragma unroll
                for (int s = 0; s < 14; s++) m = max(m, max(av[s][0], av[s][1]));
                if (++gd > SPIN_LIMIT) break;
            } while (m == SENT);
            __syncwarp();
            STAMP(15);
            if (warp >= 4) av[13][0] = av[13][1] = 0u;
            float dy[4][4] = {};
#pragma unroll
            for (int s = 0; s < 14; s++) mma16(dy[s & 3], fd[s][0], fd[s][1], fd[s][2], fd[s][3], av[s][0], av[s][1]);
            if (q < 2) sts1f(sm + OFF_RED2 + (warp * 16 + q * 8 + g) * 4, q == 0 ? (dy[0][0] + dy[1][0]) + (dy[2][0] + dy[3][0]) : (dy[0][2] + dy[1][2]) + (dy[2][2] + dy[3][2]));
            bar_sync(2, 256);
            if (tid < 8) {
                const int c = (tid >> 2) * 8 + q * 2;
                float y0 = 0.f, y1 = 0.f;
#pragma unroll
                for (int w = 0; w < 8; w++) { const float2 v = lds2f(sm + OFF_RED2 + (w * 16 + c) * 4); y0 += v.x; y1 += v.y; }
                const float sg = rbf(1.f / (1.f + __expf(-rbf(rwin))));
                const float2 gb = lds2f(sm + OFF_EP + (400 + c) * 4);
                const float b0 = __uint_as_float(tid < 4 ? bsv[0] : bsv[2]), b1 = __uint_as_float(tid < 4 ? bsv[1] : bsv[3]);
                *(uint32_t*)(out + (size_t)tokwin * 640 + d * 16 + c) = pack2(fmaf(gb.x, rbf(rbf(y0) * sg), b0), fmaf(gb.y, rbf(rbf(y1) * sg), b1));
            }
        }
        STAMP(16);
    }
}

typedef CUresult (*EncFn)(CUtensorMap*, CUtensorMapDataType, cuuint32_t, void*, const cuuint64_t*, const cuuint64_t*, const cuuint32_t*, const cuuint32_t*,
                          CUtensorMapInterleave, CUtensorMapSwizzle, CUtensorMapL2promotion, CUtensorMapFloatOOBfill);
static void make_map(EncFn enc, CUtensorMap* m, const void* base, int rank, const cuuint64_t* dims, const cuuint64_t* strides, const cuuint32_t* box, CUtensorMapSwizzle sw) {
    const cuuint32_t es[5] = {1, 1, 1, 1, 1};
    enc(m, CU_TENSOR_MAP_DATA_TYPE_BFLOAT16, rank, (void*)base, dims, strides, box, es, CU_TENSOR_MAP_INTERLEAVE_NONE, sw, CU_TENSOR_MAP_L2_PROMOTION_NONE, CU_TENSOR_MAP_FLOAT_OOB_FILL_NONE);
}

extern "C" void kernel_launch(void* const* d_in, const int* in_sizes, int n_in, void* d_out, int out_size) {
    typedef const __nv_bfloat16* P;
    P x = (P)d_in[0], wqkv = (P)d_in[1], wo = (P)d_in[2], wr = (P)d_in[4], wg = (P)d_in[5], wu = (P)d_in[6], wd = (P)d_in[7], c = (P)d_in[8], wmod = (P)d_in[9];
    void* fn = nullptr; cudaDriverEntryPointQueryResult qr;
    cudaGetDriverEntryPoint("cuTensorMapEncodeTiled", &fn, cudaEnableDefault, &qr);
    EncFn enc = (EncFn)fn;
    CUtensorMap mx, mw, mt, mo, mg, mu, md;
    { cuuint64_t d[] = {640, 2, 1024}, s[] = {1280, 2560}; cuuint32_t b[] = {64, 1, 128}; make_map(enc, &mx, x, 3, d, s, b, CU_TENSOR_MAP_SWIZZLE_128B); }
    { cuuint64_t d[] = {32, 640, 20, 3}, s[] = {3840, 64, 1280}; cuuint32_t b[] = {32, 32, 2, 3}; make_map(enc, &mw, wqkv, 4, d, s, b, CU_TENSOR_MAP_SWIZZLE_64B); }
    { cuuint64_t d[] = {640, 640, 3}, s[] = {3840, 1280}; cuuint32_t b[] = {16, 32, 3}; make_map(enc, &mt, wqkv, 3, d, s, b, CU_TENSOR_MAP_SWIZZLE_32B); }
    { cuuint64_t d[] = {640, 640}, s[] = {1280}; cuuint32_t b[] = {32, 80}; make_map(enc, &mo, wo, 2, d, s, b, CU_TENSOR_MAP_SWIZZLE_64B); }
    { cuuint64_t d[] = {1728, 160, 4}, s[] = {3456, 3456 * 160}; cuuint32_t b[] = {16, 160, 4}; make_map(enc, &mg, wg, 3, d, s, b, CU_TENSOR_MAP_SWIZZLE_32B); make_map(enc, &mu, wu, 3, d, s, b, CU_TENSOR_MAP_SWIZZLE_32B); }
    { cuuint64_t d[] = {640, 216, 8}, s[] = {1280, 1280 * 216}; cuuint32_t b[] = {16, 216, 8}; make_map(enc, &md, wd, 3, d, s, b, CU_TENSOR_MAP_SWIZZLE_32B); }
    cudaFuncSetAttribute(fused_kernel, cudaFuncAttributeMaxDynamicSharedMemorySize, SMEM_BYTES);
    fused_kernel<<<128, 384, SMEM_BYTES>>>(mx, mw, mt, mo, mg, mu, md, x, wqkv, wo, wr, wg, wu, wd, c, wmod, (__nv_bfloat16*)d_out);
}
```

```cpp
#include <cuda_runtime.h>
#include <cuda_bf16.h>
#include <cuda.h>
#include <stdint.h>

#define SENT 0xFFFFFFFFu
#define SPIN_LIMIT (1 << 17)

__device__ unsigned g_epoch;
__device__ __align__(128) unsigned g_mod[3840];
__device__ __align__(128) unsigned g_ready[128];
__device__ __align__(128) uint4 g_halo[128 * 160];
__device__ __align__(128) uint4 g_o[128 * 8 * 160];
__device__ __align__(128) uint4 g_stats[2048 * 8];
__device__ __align__(128) uint2 g_rec[128];
__device__ __align__(128) uint4 g_cand[128 * 8 * 24];
__device__ __align__(128) uint2 g_a[112 * 4];
#define STAMP(n)
#define STAMPT(n, t)

constexpr uint32_t OFF_W = 163840, WST = 15360;
constexpr uint32_t OFF_WM = OFF_W + 2 * WST;
constexpr uint32_t OFF_V = 122880, VP = 176;
constexpr uint32_t OFF_KH = OFF_W;
constexpr uint32_t OFF_WD = 129024, OFF_WG = 184320, OFF_WU = OFF_WG + 20480;
constexpr uint32_t OFF_TAB = 225280;
constexpr uint32_t OFF_S = OFF_TAB + 2560;
constexpr uint32_t OFF_EP = OFF_S + 1280;
constexpr uint32_t EP_GD = 1344, EP_US = 1376;
constexpr uint32_t OFF_RED = OFF_EP + 1408;
constexpr uint32_t OFF_RED2 = OFF_RED + 1024;
constexpr uint32_t OFF_BAR = OFF_RED2 + 512;
constexpr uint32_t SMEM_BYTES = OFF_BAR + 352;
constexpr uint32_t B_XF = 0, B_WF = 80, B_WE = 112, B_WO = 144, B_HL = 208, B_FG = 280, B_FD = 288, B_G1 = 296, B_RDY = 304, B_EP = 312, B_L16 = 320, B_WM = 328;

__device__ __forceinline__ uint32_t smem_u32(const void* p) { return (uint32_t)__cvta_generic_to_shared(p); }
__device__ __forceinline__ void mbar_init(uint32_t b, int cnt) { asm volatile("mbarrier.init.shared::cta.b64 [%0], %1;" ::"r"(b), "r"(cnt) : "memory"); }
__device__ __forceinline__ void mbar_expect_tx(uint32_t b, uint32_t bytes) { asm volatile("mbarrier.arrive.expect_tx.shared::cta.b64 _, [%0], %1;" ::"r"(b), "r"(bytes) : "memory"); }
__device__ __forceinline__ void mbar_arrive(uint32_t b) { asm volatile("mbarrier.arrive.shared::cta.b64 _, [%0];" ::"r"(b) : "memory"); }
__device__ __forceinline__ bool mbar_try(uint32_t b, uint32_t par) {
    uint32_t ok;
    asm volatile("{.reg .pred p; mbarrier.try_wait.parity.shared::cta.b64 p, [%1], %2; selp.u32 %0, 1, 0, p;}" : "=r"(ok) : "r"(b), "r"(par) : "memory");
    return ok;
}
__device__ __forceinline__ void mbar_wait(uint32_t b, uint32_t par) { int g = 0; while (!mbar_try(b, par)) { if (++g > SPIN_LIMIT) break; } }
__device__ __forceinline__ void bar_sync(int id, int n) { __syncwarp(); asm volatile("bar.sync %0, %1;" ::"r"(id), "r"(n) : "memory"); }
__device__ __forceinline__ void tma2d(uint32_t dst, const CUtensorMap* m, int c0, int c1, uint32_t bar) {
    asm volatile("cp.async.bulk.tensor.2d.shared::cluster.global.mbarrier::complete_tx::bytes [%0], [%1, {%3, %4}], [%2];" ::"r"(dst), "l"(m), "r"(bar), "r"(c0), "r"(c1) : "memory");
}
__device__ __forceinline__ void tma3d(uint32_t dst, const CUtensorMap* m, int c0, int c1, int c2, uint32_t bar) {
    asm volatile("cp.async.bulk.tensor.3d.shared::cluster.global.mbarrier::complete_tx::bytes [%0], [%1, {%3, %4, %5}], [%2];" ::"r"(dst), "l"(m), "r"(bar), "r"(c0), "r"(c1), "r"(c2) : "memory");
}
__device__ __forceinline__ void tma4d(uint32_t dst, const CUtensorMap* m, int c0, int c1, int c2, int c3, uint32_t bar) {
    asm volatile("cp.async.bulk.tensor.4d.shared::cluster.global.mbarrier::complete_tx::bytes [%0], [%1, {%3, %4, %5, %6}], [%2];" ::"r"(dst), "l"(m), "r"(bar), "r"(c0), "r"(c1), "r"(c2), "r"(c3) : "memory");
}
__device__ __forceinline__ void l2_prefetch(const void* p, uint32_t bytes) { asm volatile("cp.async.bulk.prefetch.L2.global [%0], %1;" ::"l"(p), "r"(bytes) : "memory"); }
__device__ __forceinline__ void pf_map(const CUtensorMap* m) { asm volatile("prefetch.tensormap [%0];" ::"l"(m) : "memory"); }
__device__ __forceinline__ void wg_fence() { asm volatile("wgmma.fence.sync.aligned;" ::: "memory"); }
__device__ __forceinline__ void wg_commit() { asm volatile("wgmma.commit_group.sync.aligned;" ::: "memory"); }
template <int N> __device__ __forceinline__ void wg_wait() { asm volatile("wgmma.wait_group.sync.aligned %0;" ::"n"(N) : "memory"); }
__device__ __forceinline__ void ldsm4(uint32_t* r, uint32_t addr) { asm volatile("ldmatrix.sync.aligned.m8n8.x4.shared.b16 {%0,%1,%2,%3}, [%4];" : "=r"(r[0]), "=r"(r[1]), "=r"(r[2]), "=r"(r[3]) : "r"(addr) : "memory"); }
__device__ __forceinline__ void ldsm4t(uint32_t* r, uint32_t addr) { asm volatile("ldmatrix.sync.aligned.m8n8.x4.trans.shared.b16 {%0,%1,%2,%3}, [%4];" : "=r"(r[0]), "=r"(r[1]), "=r"(r[2]), "=r"(r[3]) : "r"(addr) : "memory"); }
__device__ __forceinline__ void stsm4(uint32_t addr, const uint32_t* r) { asm volatile("stmatrix.sync.aligned.m8n8.x4.shared.b16 [%4], {%0,%1,%2,%3};" ::"r"(r[0]), "r"(r[1]), "r"(r[2]), "r"(r[3]), "r"(addr) : "memory"); }
__device__ __forceinline__ void lds4(uint32_t* r, uint32_t addr) { asm volatile("ld.shared.v4.u32 {%0,%1,%2,%3}, [%4];" : "=r"(r[0]), "=r"(r[1]), "=r"(r[2]), "=r"(r[3]) : "r"(addr) : "memory"); }
__device__ __forceinline__ void sts4(uint32_t addr, const uint32_t* r) { asm volatile("st.shared.v4.u32 [%4], {%0,%1,%2,%3};" ::"r"(r[0]), "r"(r[1]), "r"(r[2]), "r"(r[3]), "r"(addr) : "memory"); }
__device__ __forceinline__ float2 lds2f(uint32_t addr) { float2 v; asm volatile("ld.shared.v2.f32 {%0,%1}, [%2];" : "=f"(v.x), "=f"(v.y) : "r"(addr) : "memory"); return v; }
__device__ __forceinline__ float lds1f(uint32_t addr) { float v; asm volatile("ld.shared.f32 %0, [%1];" : "=f"(v) : "r"(addr) : "memory"); return v; }
__device__ __forceinline__ void sts1f(uint32_t addr, float v) { asm volatile("st.shared.f32 [%0], %1;" ::"r"(addr), "f"(v) : "memory"); }
__device__ __forceinline__ void sts1(uint32_t addr, uint32_t v) { asm volatile("st.shared.u32 [%0], %1;" ::"r"(addr), "r"(v) : "memory"); }
__device__ __forceinline__ void ldg4_rlx(uint32_t* r, const void* p) { asm volatile("{.reg .b128 t; ld.relaxed.gpu.global.b128 t, [%4]; mov.b128 {%0,%1,%2,%3}, t;}" : "=r"(r[0]), "=r"(r[1]), "=r"(r[2]), "=r"(r[3]) : "l"(p) : "memory"); }
__device__ __forceinline__ void ldg2_rlx(uint32_t* r, const void* p) { asm volatile("{.reg .b64 t; ld.relaxed.gpu.global.b64 t, [%2]; mov.b64 {%0,%1}, t;}" : "=r"(r[0]), "=r"(r[1]) : "l"(p) : "memory"); }
__device__ __forceinline__ uint32_t ldg1_rlx(const void* p) { uint32_t v; asm volatile("ld.relaxed.gpu.global.u32 %0, [%1];" : "=r"(v) : "l"(p) : "memory"); return v; }
__device__ __forceinline__ void stg4_rlx(void* p, uint32_t a, uint32_t b, uint32_t c, uint32_t d) { asm volatile("{.reg .b128 t; mov.b128 t, {%1,%2,%3,%4}; st.relaxed.gpu.global.b128 [%0], t;}" ::"l"(p), "r"(a), "r"(b), "r"(c), "r"(d) : "memory"); }
__device__ __forceinline__ void stg2_rlx(void* p, uint32_t a, uint32_t b) { asm volatile("{.reg .b64 t; mov.b64 t, {%1,%2}; st.relaxed.gpu.global.b64 [%0], t;}" ::"l"(p), "r"(a), "r"(b) : "memory"); }
__device__ __forceinline__ void stg1_rlx(void* p, uint32_t a) { asm volatile("st.relaxed.gpu.global.u32 [%0], %1;" ::"l"(p), "r"(a) : "memory"); }
__device__ __forceinline__ void ldg4_nc(uint32_t* r, const void* p) { asm volatile("ld.global.nc.L1::no_allocate.v4.u32 {%0,%1,%2,%3}, [%4];" : "=r"(r[0]), "=r"(r[1]), "=r"(r[2]), "=r"(r[3]) : "l"(p)); }
__device__ __forceinline__ uint64_t mkdesc(uint32_t addr, uint32_t lbo, uint32_t sbo, uint32_t sw) { return (uint64_t)((addr & 0x3FFFF) >> 4) | ((uint64_t)(lbo >> 4) << 16) | ((uint64_t)(sbo >> 4) << 32) | ((uint64_t)sw << 62); }
__device__ __forceinline__ uint32_t pack2(float lo, float hi) { uint32_t r; asm("cvt.rn.bf16x2.f32 %0, %1, %2;" : "=r"(r) : "f"(hi), "f"(lo)); return r; }
__device__ __forceinline__ float blo(uint32_t v) { return __uint_as_float(v << 16); }
__device__ __forceinline__ float bhi(uint32_t v) { return __uint_as_float(v & 0xffff0000u); }
__device__ __forceinline__ float rbf(float x) { return blo(pack2(x, 0.f)); }
__device__ __forceinline__ uint32_t hf2(uint32_t a, uint32_t b, uint32_t c) { uint32_t r; asm("fma.rn.bf16x2 %0, %1, %2, %3;" : "=r"(r) : "r"(a), "r"(b), "r"(c)); return r; }
__device__ __forceinline__ uint32_t movm(uint32_t a) { uint32_t r; asm volatile("movmatrix.sync.aligned.m8n8.trans.b16 %0, %1;" : "=r"(r) : "r"(a)); return r; }
__device__ __forceinline__ float ex2(float x) { float r; asm("ex2.approx.ftz.f32 %0, %1;" : "=f"(r) : "f"(x)); return r; }
__device__ __forceinline__ void mma16(float* d, uint32_t a0, uint32_t a1, uint32_t a2, uint32_t a3, uint32_t b0, uint32_t b1) {
    asm volatile("mma.sync.aligned.m16n8k16.row.col.f32.bf16.bf16.f32 {%0,%1,%2,%3}, {%4,%5,%6,%7}, {%8,%9}, {%0,%1,%2,%3};"
                 : "+f"(d[0]), "+f"(d[1]), "+f"(d[2]), "+f"(d[3]) : "r"(a0), "r"(a1), "r"(a2), "r"(a3), "r"(b0), "r"(b1));
}
__device__ __forceinline__ void mma8(float* d, uint32_t a0, uint32_t a1, uint32_t b0) {
    asm volatile("mma.sync.aligned.m16n8k8.row.col.f32.bf16.bf16.f32 {%0,%1,%2,%3}, {%4,%5}, {%6}, {%0,%1,%2,%3};"
                 : "+f"(d[0]), "+f"(d[1]), "+f"(d[2]), "+f"(d[3]) : "r"(a0), "r"(a1), "r"(b0));
}
__device__ __forceinline__ uint32_t umax4(const uint32_t* v, uint32_t m) { return max(max(max(v[0], v[1]), max(v[2], v[3])), m); }
__device__ __forceinline__ uint32_t fkey(float f) { uint32_t u = __float_as_uint(f); return (u & 0x80000000u) ? ~u : (u | 0x80000000u); }
__device__ __forceinline__ float rcp(float x) { float r; asm("rcp.approx.ftz.f32 %0, %1;" : "=f"(r) : "f"(x)); return r; }
__device__ __forceinline__ float sigm(float x) { return rcp(1.f + ex2(x * -1.4426950408889634f)); }
__device__ __forceinline__ void mma16c(float* d, uint32_t a0, uint32_t a1, uint32_t a2, uint32_t a3, uint32_t b0, uint32_t b1, float c0, float c1) {
    asm volatile("mma.sync.aligned.m16n8k16.row.col.f32.bf16.bf16.f32 {%0,%1,%2,%3}, {%4,%5,%6,%7}, {%8,%9}, {%10,%11,%12,%12};"
                 : "=f"(d[0]), "=f"(d[1]), "=f"(d[2]), "=f"(d[3]) : "r"(a0), "r"(a1), "r"(a2), "r"(a3), "r"(b0), "r"(b1), "f"(c0), "f"(c1), "f"(0.f));
}
__device__ __forceinline__ void ldsm2t(uint32_t* r, uint32_t addr) { asm volatile("ldmatrix.sync.aligned.m8n8.x2.trans.shared.b16 {%0,%1}, [%2];" : "=r"(r[0]), "=r"(r[1]) : "r"(addr) : "memory"); }
__device__ __forceinline__ void stsm2(uint32_t addr, uint32_t a, uint32_t b) { asm volatile("stmatrix.sync.aligned.m8n8.x2.shared.b16 [%2], {%0,%1};" ::"r"(a), "r"(b), "r"(addr) : "memory"); }
__device__ __forceinline__ void lds2(uint32_t* r, uint32_t addr) { asm volatile("ld.shared.v2.u32 {%0,%1}, [%2];" : "=r"(r[0]), "=r"(r[1]) : "r"(addr) : "memory"); }
__device__ __forceinline__ void sts2(uint32_t addr, uint32_t a, uint32_t b) { asm volatile("st.shared.v2.u32 [%2], {%0,%1};" ::"r"(a), "r"(b), "r"(addr) : "memory"); }
__device__ __forceinline__ void sts16(uint32_t addr, uint32_t v) { asm volatile("st.shared.u16 [%0], %1;" ::"r"(addr), "h"((unsigned short)v) : "memory"); }
__device__ __forceinline__ uint32_t lds1(uint32_t addr) { uint32_t v; asm volatile("ld.shared.u32 %0, [%1];" : "=r"(v) : "r"(addr) : "memory"); return v; }
__device__ __forceinline__ void wgmma_rs_n192(float* d, const uint32_t* a, uint64_t bdesc) {
    asm volatile("wgmma.mma_async.sync.aligned.m64n192k16.f32.bf16.bf16 {%0,%1,%2,%3,%4,%5,%6,%7,%8,%9,%10,%11,%12,%13,%14,%15,%16,%17,%18,%19,%20,%21,%22,%23,%24,%25,%26,%27,%28,%29,%30,%31,%32,%33,%34,%35,%36,%37,%38,%39,%40,%41,%42,%43,%44,%45,%46,%47,%48,%49,%50,%51,%52,%53,%54,%55,%56,%57,%58,%59,%60,%61,%62,%63,%64,%65,%66,%67,%68,%69,%70,%71,%72,%73,%74,%75,%76,%77,%78,%79,%80,%81,%82,%83,%84,%85,%86,%87,%88,%89,%90,%91,%92,%93,%94,%95}, {%96,%97,%98,%99}, %100, 1, 1, 1, 1;"
        : "+f"(d[0]),"+f"(d[1]),"+f"(d[2]),"+f"(d[3]),"+f"(d[4]),"+f"(d[5]),"+f"(d[6]),"+f"(d[7]),"+f"(d[8]),"+f"(d[9]),"+f"(d[10]),"+f"(d[11]),"+f"(d[12]),"+f"(d[13]),"+f"(d[14]),"+f"(d[15]),"+f"(d[16]),"+f"(d[17]),"+f"(d[18]),"+f"(d[19]),"+f"(d[20]),"+f"(d[21]),"+f"(d[22]),"+f"(d[23]),"+f"(d[24]),"+f"(d[25]),"+f"(d[26]),"+f"(d[27]),"+f"(d[28]),"+f"(d[29]),"+f"(d[30]),"+f"(d[31]),"+f"(d[32]),"+f"(d[33]),"+f"(d[34]),"+f"(d[35]),"+f"(d[36]),"+f"(d[37]),"+f"(d[38]),"+f"(d[39]),"+f"(d[40]),"+f"(d[41]),"+f"(d[42]),"+f"(d[43]),"+f"(d[44]),"+f"(d[45]),"+f"(d[46]),"+f"(d[47]),"+f"(d[48]),"+f"(d[49]),"+f"(d[50]),"+f"(d[51]),"+f"(d[52]),"+f"(d[53]),"+f"(d[54]),"+f"(d[55]),"+f"(d[56]),"+f"(d[57]),"+f"(d[58]),"+f"(d[59]),"+f"(d[60]),"+f"(d[61]),"+f"(d[62]),"+f"(d[63]),"+f"(d[64]),"+f"(d[65]),"+f"(d[66]),"+f"(d[67]),"+f"(d[68]),"+f"(d[69]),"+f"(d[70]),"+f"(d[71]),"+f"(d[72]),"+f"(d[73]),"+f"(d[74]),"+f"(d[75]),"+f"(d[76]),"+f"(d[77]),"+f"(d[78]),"+f"(d[79]),"+f"(d[80]),"+f"(d[81]),"+f"(d[82]),"+f"(d[83]),"+f"(d[84]),"+f"(d[85]),"+f"(d[86]),"+f"(d[87]),"+f"(d[88]),"+f"(d[89]),"+f"(d[90]),"+f"(d[91]),"+f"(d[92]),"+f"(d[93]),"+f"(d[94]),"+f"(d[95])
        : "r"(a[0]), "r"(a[1]), "r"(a[2]), "r"(a[3]), "l"(bdesc));
}
__device__ __forceinline__ void wgmma_rs_n48(float* d, const uint32_t* a, uint64_t bdesc) {
    asm volatile("wgmma.mma_async.sync.aligned.m64n48k16.f32.bf16.bf16 {%0,%1,%2,%3,%4,%5,%6,%7,%8,%9,%10,%11,%12,%13,%14,%15,%16,%17,%18,%19,%20,%21,%22,%23}, {%24,%25,%26,%27}, %28, 1, 1, 1, 1;"
        : "+f"(d[0]),"+f"(d[1]),"+f"(d[2]),"+f"(d[3]),"+f"(d[4]),"+f"(d[5]),"+f"(d[6]),"+f"(d[7]),"+f"(d[8]),"+f"(d[9]),"+f"(d[10]),"+f"(d[11]),"+f"(d[12]),"+f"(d[13]),"+f"(d[14]),"+f"(d[15]),"+f"(d[16]),"+f"(d[17]),"+f"(d[18]),"+f"(d[19]),"+f"(d[20]),"+f"(d[21]),"+f"(d[22]),"+f"(d[23])
        : "r"(a[0]), "r"(a[1]), "r"(a[2]), "r"(a[3]), "l"(bdesc));
}
__device__ __forceinline__ void wgmma_rs_n80(float* d, const uint32_t* a, uint64_t bdesc) {
    asm volatile("wgmma.mma_async.sync.aligned.m64n80k16.f32.bf16.bf16 {%0,%1,%2,%3,%4,%5,%6,%7,%8,%9,%10,%11,%12,%13,%14,%15,%16,%17,%18,%19,%20,%21,%22,%23,%24,%25,%26,%27,%28,%29,%30,%31,%32,%33,%34,%35,%36,%37,%38,%39}, {%40,%41,%42,%43}, %44, 1, 1, 1, 1;"
        : "+f"(d[0]),"+f"(d[1]),"+f"(d[2]),"+f"(d[3]),"+f"(d[4]),"+f"(d[5]),"+f"(d[6]),"+f"(d[7]),"+f"(d[8]),"+f"(d[9]),"+f"(d[10]),"+f"(d[11]),"+f"(d[12]),"+f"(d[13]),"+f"(d[14]),"+f"(d[15]),"+f"(d[16]),"+f"(d[17]),"+f"(d[18]),"+f"(d[19]),"+f"(d[20]),"+f"(d[21]),"+f"(d[22]),"+f"(d[23]),"+f"(d[24]),"+f"(d[25]),"+f"(d[26]),"+f"(d[27]),"+f"(d[28]),"+f"(d[29]),"+f"(d[30]),"+f"(d[31]),"+f"(d[32]),"+f"(d[33]),"+f"(d[34]),"+f"(d[35]),"+f"(d[36]),"+f"(d[37]),"+f"(d[38]),"+f"(d[39])
        : "r"(a[0]), "r"(a[1]), "r"(a[2]), "r"(a[3]), "l"(bdesc));
}

__global__ void __launch_bounds__(384, 1)
fused_kernel(const __grid_constant__ CUtensorMap mx, const __grid_constant__ CUtensorMap mw, const __grid_constant__ CUtensorMap mt,
             const __grid_constant__ CUtensorMap mo, const __grid_constant__ CUtensorMap mg, const __grid_constant__ CUtensorMap mu,
             const __grid_constant__ CUtensorMap md, const __grid_constant__ CUtensorMap mm,
             const __nv_bfloat16* __restrict__ wqkv, const __nv_bfloat16* __restrict__ wo,
             const __nv_bfloat16* __restrict__ wr, const __nv_bfloat16* __restrict__ wg, const __nv_bfloat16* __restrict__ wu,
             const __nv_bfloat16* __restrict__ wd, const __nv_bfloat16* __restrict__ cvec, const __nv_bfloat16* __restrict__ wmod,
             __nv_bfloat16* __restrict__ out) {
    extern __shared__ __align__(1024) char sm_raw[];
    const uint32_t sm = smem_u32(sm_raw), bars = sm + OFF_BAR;
    const int gp = blockIdx.x >> 4, ix = blockIdx.x & 15;
    const int ti = (gp & 3) * 4 + (ix >> 2), j = (gp >> 2) * 4 + (ix & 3);
    const int role = ti * 8 + j, odd = j & 1;
    const int tid = threadIdx.x, warp = tid >> 5, lane = tid & 31;
    const int g = lane >> 2, q = lane & 3;
    const uint32_t frag = ((lane & 7) + (lane >> 4) * 8) * 32 + ((((lane >> 3) ^ (lane >> 2)) & 1) << 4);

    if (warp >= 8) {
        asm volatile("setmaxnreg.dec.sync.aligned.u32 104;");
        const int col_main = 80 * j + 16 * odd, col_tail = 80 * j + (odd ? 0 : 64);
        auto load_w = [&](int it) {
            const uint32_t b = bars + B_WF + 8 * (it & 3), dst = sm + OFF_W + (it & 3) * WST;
            mbar_expect_tx(b, WST);
            tma4d(dst, &mw, 0, it * 32, col_main >> 5, 0, b);
            tma3d(dst + 12288, &mt, col_tail, it * 32, 0, b);
        };
        const int at = tid - 256;
        if (warp == 8) {
            {
                const int i0 = lane, i1 = lane + 32;
                mbar_init(bars + 8 * i0, (i0 >= 14 && i0 < 18) ? 8 : 1);
                if (i1 < 42) mbar_init(bars + 8 * i1, (i1 == 37 || i1 == 40) ? 8 : (i1 == 39 ? 3 : 1));
                asm volatile("fence.mbarrier_init.release.cluster;" ::: "memory");
                __syncwarp();
            }
            if (lane == 0) {
                if (role < 80) { mbar_expect_tx(bars + B_WM, 20480); tma3d(sm + OFF_WM, &mm, role * 16, 0, 0, bars + B_WM); }
#pragma unroll 1
                for (int c = 0; c < 10; c++) { mbar_expect_tx(bars + B_XF + 8 * c, 16384); tma3d(sm + c * 16384, &mx, c * 64, ti >> 3, (ti & 7) * 128, bars + B_XF + 8 * c); }
                load_w(0); load_w(1);
                l2_prefetch(wqkv + (size_t)(64 + role * 4 + (role >> 1)) * 1920, 5 * 3840);
            }
        } else {
            if (at < 37) l2_prefetch(wmod + (size_t)(role * 5 + at - 32) * 3840, 2560);
#pragma unroll 1
            for (int v = at - 32; v < 320; v += 96) {
                const uint32_t w = ((const uint32_t*)cvec)[v];
                sts1(sm + OFF_S + (v >> 3) * 32 + (v & 3) * 8 + (v & 4), pack2(blo(w) * sigm(blo(w)), bhi(w) * sigm(bhi(w))));
            }
        }
        const uint32_t epoch = ldg1_rlx(&g_epoch) + 1, tag = epoch & 0xffffu;
        bar_sync(0, 384);
        auto mod_unit = [&](int unit, uint32_t tile, uint32_t red) {
            float d[2][4] = {};
#pragma unroll
            for (int s = 0; s < 10; s++) {
                uint32_t a[4], b[2];
                const int ks = (warp - 8) * 10 + s;
                ldsm4t(a, tile + ks * 512 + frag); lds2(b, sm + OFF_S + ks * 32 + q * 8);
                mma16(d[s & 1], a[0], a[1], a[2], a[3], b[0], b[1]);
            }
            if (q < 2) sts1f(red + ((warp - 8) * 16 + q * 8 + g) * 4, q ? d[0][2] + d[1][2] : d[0][0] + d[1][0]);
            bar_sync(3, 128);
            if (at >= 112) {
                const uint32_t a = red + (at - 112) * 4;
                float t = rbf((lds1f(a) + lds1f(a + 64)) + (lds1f(a + 128) + lds1f(a + 192)));
                if ((unit >= 40 && unit < 80) || (unit >= 160 && unit < 200)) t = rbf(1.f + t);
                stg1_rlx(&g_mod[unit * 16 + at - 112], __float_as_uint(t) | tag);
            }
        };
#pragma unroll 1
        for (int ph = 0; ph < 3; ph++) {
            if (role < 80) {
                mbar_wait(bars + B_WM, ph > 0);
                mod_unit(ph == 0 ? role : 79 + 2 * role + ph, sm + (ph == 0 ? OFF_WM : OFF_WD - 20480 + ph * 20480), sm + OFF_RED2 + (ph & 1) * 256);
            }
            if (ph > 0) continue;
            STAMPT(0, 256);
            if (warp == 8) {
                if (lane == 0) {
#pragma unroll 1
                    for (int it = 2; it < 20; it++) {
                        if (it >= 4) mbar_wait(bars + B_WE + 8 * (it & 3), ((it >> 2) & 1) ^ 1);
                        load_w(it);
                        if (it >= 4 && !(it & 1)) {
                            const int w = (it - 4) >> 1;
                            const int src = w == 0 ? j : (w <= j ? w - 1 : w);
                            const uint32_t b = bars + B_WO + 8 * w, dst = sm + w * WST;
                            mbar_expect_tx(b, WST);
                            tma2d(dst, &mo, col_main, src * 80, b); tma2d(dst + 5120, &mo, col_main + 32, src * 80, b); tma2d(dst + 10240, &mo, col_tail, src * 80, b);
                        }
                    }
                    mbar_wait(bars + B_G1, 0);
                    if (role < 80) { mbar_expect_tx(bars + B_WM, 40960); tma3d(sm + OFF_WD, &mm, 1280 + role * 32, 0, 0, bars + B_WM); tma3d(sm + OFF_WD + 20480, &mm, 1296 + role * 32, 0, 0, bars + B_WM); }
                    if (role < 108) { mbar_expect_tx(bars + B_FG, 40960); tma3d(sm + OFF_WG, &mg, role * 16, 0, 0, bars + B_FG); tma3d(sm + OFF_WU, &mu, role * 16, 0, 0, bars + B_FG); }
                    if (role >= 88) { mbar_expect_tx(bars + B_FD, 55296); tma3d(sm + OFF_WD, &md, (role - 88) * 16, 0, 0, bars + B_FD); }
                }
                __syncwarp();
            } else {
                {
                    uint32_t w[4][4]; int gd = 0; uint32_t bad;
                    do {
                        bad = 0;
#pragma unroll
                        for (int e = 0; e < 4; e++) ldg4_rlx(w[e], &g_mod[min(at - 32 + e * 96, 319) * 4]);
#pragma unroll
                        for (int e = 0; e < 4; e++) bad |= (w[e][0] ^ tag) | (w[e][1] ^ tag) | (w[e][2] ^ tag) | (w[e][3] ^ tag);
                    } while (__any_sync(~0u, bad & 0xffffu) && ++gd < SPIN_LIMIT);
#pragma unroll
                    for (int e = 0; e < 4; e++) {
                        const int v = min(at - 32 + e * 96, 319), isc = v >= 160, k4 = v - isc * 160;
                        const uint32_t a = sm + OFF_TAB + (k4 >> 2) * 64 + (k4 & 1) * 32 + (k4 & 2) * 2 + (isc ? 0 : 8);
                        sts1(a, __byte_perm(w[e][0], w[e][1], 0x7632)); sts1(a + 16, __byte_perm(w[e][2], w[e][3], 0x7632));
                    }
                }
                STAMPT(2, 288);
                bar_sync(1, 352);
                if (warp == 9) {
                    if (lane == 0) { asm volatile("fence.acq_rel.gpu;" ::: "memory"); stg1_rlx(&g_ready[role], epoch); }
                    uint32_t w[4]; int gd = 0;
                    do { __nanosleep(300); ldg4_rlx(w, &g_ready[lane * 4]); } while (__any_sync(~0u, w[0] != epoch || w[1] != epoch || w[2] != epoch || w[3] != epoch) && ++gd < SPIN_LIMIT);
                    asm volatile("fence.acq_rel.gpu;" ::: "memory");
                    __syncwarp();
                    if (lane == 0) { mbar_arrive(bars + B_RDY); if (role == 0) stg1_rlx(&g_epoch, epoch); }
                    uint32_t h[5][4];
                    mbar_wait(bars + B_L16, 0);
                    if ((ti & 7) == 0) {
#pragma unroll
                        for (int s = 0; s < 20; s++) h[s >> 2][s & 3] = 0;
                    } else {
                        do {
#pragma unroll
                            for (int s = 0; s < 5; s++) ldg4_rlx(h[s], &g_halo[(role - 8) * 160 + s * 32 + lane]);
                        } while (__any_sync(~0u, max(max(max(h[0][0], h[1][0]), max(h[2][0], h[3][0])), h[4][0]) == SENT) && ++gd < SPIN_LIMIT);
                    }
                    sts4(sm + OFF_KH + lane * 16, h[0]); sts4(sm + OFF_KH + 512 + lane * 16, h[1]); sts2(sm + OFF_KH + 1024 + lane * 8, h[2][0], h[2][1]);
                    const uint32_t va = sm + OFF_V + (lane & 7) * VP + (lane >> 3) * 16;
                    stsm4(va, h[3]); stsm4(va + 64, h[4]); stsm2(va + 128, h[2][2], h[2][3]);
                    __syncwarp();
                    if (lane == 0) mbar_arrive(bars + B_HL);
                } else if (at < 73) {
                    const int e = at - 64;
                    const __nv_bfloat16* p = e < 5 ? wmod + (size_t)(role * 5 + e) * 3840 + 1280 : (e == 5 ? wo + role * 3200 : (e == 6 ? wg : (e == 7 ? wu : wd)) + role * 8640);
                    l2_prefetch(p, e < 5 ? 5120 : (e == 5 ? 6400 : 17280));
                }
            }
        }
        if (warp > 8) {
            const int t = at - 32;
            uint32_t sb[2][4], cb[2][4], own[4]; uint2 wv[2]; int gd = 0; uint32_t bad;
            const int kg = t < 80 ? 80 * j + t : max(role - 88, 0) * 16 + t - 80;
#pragma unroll
            for (int e = 0; e < 2; e++) wv[e] = *(const uint2*)(wr + min(t + e * 96, 159) * 4);
            const float wo_ = __bfloat162float(wr[kg]);
            do {
#pragma unroll
                for (int e = 0; e < 2; e++) { ldg4_rlx(sb[e], &g_mod[1920 + min(t + e * 96, 159) * 4]); ldg4_rlx(cb[e], &g_mod[2560 + min(t + e * 96, 159) * 4]); }
                bad = 0;
#pragma unroll
                for (int e = 0; e < 4; e++) { own[e] = ldg1_rlx(&g_mod[1280 + e * 640 + kg]); bad |= own[e] ^ tag; }
#pragma unroll
                for (int e = 0; e < 8; e++) bad |= (sb[e >> 2][e & 3] ^ tag) | (cb[e >> 2][e & 3] ^ tag);
            } while (__any_sync(~0u, bad & 0xffffu) && ++gd < SPIN_LIMIT);
            if (t >= 64) wv[1] = make_uint2(0u, 0u);
            float us = 0.f, ss = 0.f;
#pragma unroll
            for (int e = 0; e < 8; e++) {
                const uint32_t w2 = (e & 2) ? wv[e >> 2].y : wv[e >> 2].x;
                const float w = (e & 1) ? bhi(w2) : blo(w2);
                us = fmaf(bhi(cb[e >> 2][e & 3]), w, us); ss = fmaf(bhi(sb[e >> 2][e & 3]), w, ss);
            }
            if (t < 80) {
                const int p = odd ? (t < 16 ? t + 64 : t - 16) : t;
                const uint32_t a = sm + OFF_EP + ((p >> 1) & 3) * 48 + (p >> 3) * 4 + (p & 1) * 2;
                const float u = bhi(own[2]) * wo_, uh = rbf(u);
                sts16(a, own[0] >> 16); sts16(a + 192, own[2] >> 16); sts16(a + 384, own[1] >> 16); sts16(a + 576, own[3] >> 16);
                sts16(a + 768, 0x3f80u); sts16(a + 960, __float_as_uint(uh) >> 16); sts16(a + 1152, pack2(u - uh, 0.f));
            } else sts16(sm + OFF_EP + EP_GD + (t - 80) * 2, own[3] >> 16);
#pragma unroll
            for (int o = 16; o; o >>= 1) { us += __shfl_xor_sync(~0u, us, o); ss += __shfl_xor_sync(~0u, ss, o); }
            if (lane == 0) sts2(sm + OFF_EP + EP_US + (warp - 9) * 8, __float_as_uint(us), __float_as_uint(ss));
            __syncwarp();
            if (lane == 0) mbar_arrive(bars + B_EP);
            STAMPT(20, 288);
        }
    } else {
        asm volatile("setmaxnreg.inc.sync.aligned.u32 200;");
        const int tw = ti * 8 + warp;
        uint4* const my_o = &g_o[tw * 8 * 160 + lane];
#pragma unroll
        for (int s = 0; s < 5; s++) stg4_rlx(my_o + j * 160 + s * 32, SENT, SENT, SENT, SENT);
        if (lane < 24) stg4_rlx(&g_cand[(tw * 8 + j) * 24 + lane], SENT, SENT, SENT, SENT);
        if (lane < 16) stg4_rlx(&g_stats[(tw * 8 + j) * 16 + lane], SENT, SENT, SENT, SENT);
        if (tid < 160) stg4_rlx(&g_halo[role * 160 + tid], SENT, SENT, SENT, SENT);
        if (tid >= 251) stg2_rlx(tid == 251 ? &g_rec[role] : &g_a[min(role, 111) * 4 + tid - 252], SENT, SENT);
        bar_sync(0, 384);
        const uint32_t hi = lane >> 4, xa = sm + (warp * 16 + (lane & 15)) * 128 + ((hi ^ (lane & 7)) << 4);
        uint32_t rr0, rr1, nn0, nn1;
        {
            float gA[2][4] = {}, gB[2][4] = {}, sd[2][4] = {};
#pragma unroll 1
            for (int c = 0; c < 10; c++) {
                mbar_wait(bars + B_XF + 8 * c, 0);
                uint32_t a[4][4];
#pragma unroll
                for (int k = 0; k < 4; k++) ldsm4(a[k], (xa ^ (k * 32)) + c * 16384);
#pragma unroll
                for (int k = 0; k < 4; k++) {
                    mma16(gA[k & 1], a[k][0], a[k][1], a[k][2], a[k][3], a[k][0], a[k][2]);
                    mma16(gB[k & 1], a[k][0], a[k][1], a[k][2], a[k][3], a[k][1], a[k][3]);
                    mma16(sd[k & 1], a[k][0], a[k][1], a[k][2], a[k][3], 0x3f803f80u, 0x3f803f80u);
                }
            }
            const float ss0 = __shfl_sync(~0u, (g & 1) ? gA[0][1] + gA[1][1] : gA[0][0] + gA[1][0], (lane & ~3) | (g >> 1));
            const float ss1 = __shfl_sync(~0u, (g & 1) ? gB[0][3] + gB[1][3] : gB[0][2] + gB[1][2], (lane & ~3) | (g >> 1));
            const float m0 = (sd[0][0] + sd[1][0]) * (1.f / 640), m1 = (sd[0][2] + sd[1][2]) * (1.f / 640);
            const float r0 = rbf(rsqrtf(fmaxf(ss0 * (1.f / 640) - m0 * m0, 0.f) + 1e-5f)), r1 = rbf(rsqrtf(fmaxf(ss1 * (1.f / 640) - m1 * m1, 0.f) + 1e-5f));
            rr0 = pack2(r0, r0); rr1 = pack2(r1, r1); nn0 = pack2(-m0 * r0, -m0 * r0); nn1 = pack2(-m1 * r1, -m1 * r1);
        }
        uint32_t xr[5][4];
#pragma unroll
        for (int s = 0; s < 5; s++) {
            const int ks = 5 * j + (odd ? (s == 4 ? 0 : s + 1) : s);
            ldsm4(xr[s], (xa ^ ((ks & 3) * 32)) + (ks >> 2) * 16384);
        }
        STAMP(1);
        bar_sync(1, 352);
        float acc[120];
#pragma unroll
        for (int i = 0; i < 120; i++) acc[i] = 0.f;
        {
            uint32_t a[2][2][4], raw[2][4], tt[2][4];
            uint32_t tb = sm + OFF_TAB + q * 16, xp = xa;
            auto load = [&](int u) {
                ldsm4(raw[0], xp ^ (u * 64)); ldsm4(raw[1], xp ^ (u * 64 + 32));
                lds4(tt[0], tb + u * 128); lds4(tt[1], tb + u * 128 + 64);
            };
            auto xform = [&](uint32_t (*dst)[4]) {
#pragma unroll
                for (int h = 0; h < 2; h++) {
                    dst[h][0] = hf2(hf2(raw[h][0], rr0, nn0), tt[h][0], tt[h][2]); dst[h][1] = hf2(hf2(raw[h][1], rr1, nn1), tt[h][0], tt[h][2]);
                    dst[h][2] = hf2(hf2(raw[h][2], rr0, nn0), tt[h][1], tt[h][3]); dst[h][3] = hf2(hf2(raw[h][3], rr1, nn1), tt[h][1], tt[h][3]);
                }
            };
            const uint64_t dm0 = mkdesc(sm + OFF_W, 2048, 512, 2), dt0 = mkdesc(sm + OFF_W + 12288, 1024, 256, 3);
            load(0); xform(a[0]);
            STAMP(3);
#pragma unroll 1
            for (int i2 = 0; i2 < 10; i2++) {
#pragma unroll
                for (int u = 0; u < 2; u++) {
                    const int st = (i2 & 1) * 2 + u;
                    mbar_wait(bars + B_WF + 8 * st, (i2 >> 1) & 1);
                    wg_fence();
#pragma unroll
                    for (int h = 0; h < 2; h++) { wgmma_rs_n192(acc, a[u][h], dm0 + st * (WST / 16) + h * 64); wgmma_rs_n48(acc + 96, a[u][h], dt0 + st * (WST / 16) + h * 32); }
                    wg_commit();
                    if (u == 1) { xp += 16384; tb += 256; }
                    load(u ^ 1);
                    wg_wait<1>();
                    if (lane == 0 && (u == 1 || i2 > 0)) mbar_arrive(bars + ((u == 1 && i2 == 8) ? B_L16 : B_WE + 8 * ((st + 3) & 3)));
                    xform(a[u ^ 1]);
                }
            }
            wg_wait<0>();
        }
        STAMP(4);
        uint32_t ab[4][5][4];
        {
            uint32_t Q[10][2], K[2][10], V[2][10];
            if (!odd) {
#pragma unroll
                for (int t = 0; t < 10; t++) {
                    const int iq = t < 8 ? t * 4 : 96 + (t - 8) * 4, ik = t < 8 ? 32 + t * 4 : 104 + (t - 8) * 4, iv = t < 8 ? 64 + t * 4 : 112 + (t - 8) * 4;
                    K[1][t] = pack2(acc[ik + 2], acc[ik + 3]); V[0][t] = pack2(acc[iv], acc[iv + 1]); V[1][t] = pack2(acc[iv + 2], acc[iv + 3]);
                    K[0][t] = pack2(acc[ik], acc[ik + 1]); Q[t][0] = pack2(acc[iq], acc[iq + 1]); Q[t][1] = pack2(acc[iq + 2], acc[iq + 3]);
                }
            } else {
#pragma unroll
                for (int t = 0; t < 10; t++) {
                    const int iq = t >= 2 ? (t - 2) * 4 : 96 + t * 4, ik = t >= 2 ? 32 + (t - 2) * 4 : 104 + t * 4, iv = t >= 2 ? 64 + (t - 2) * 4 : 112 + t * 4;
                    K[1][t] = pack2(acc[ik + 2], acc[ik + 3]); V[0][t] = pack2(acc[iv], acc[iv + 1]); V[1][t] = pack2(acc[iv + 2], acc[iv + 3]);
                    K[0][t] = pack2(acc[ik], acc[ik + 1]); Q[t][0] = pack2(acc[iq], acc[iq + 1]); Q[t][1] = pack2(acc[iq + 2], acc[iq + 3]);
                }
            }
            mbar_wait(bars + B_RDY, 0);
            if (warp == 7) {
                uint4* hp = &g_halo[role * 160 + lane];
                stg4_rlx(hp, K[1][0], K[1][1], K[1][3], K[1][4]); stg4_rlx(hp + 32, K[1][5], K[1][6], K[1][8], K[1][9]); stg4_rlx(hp + 64, K[1][2], K[1][7], V[1][8], V[1][9]);
                stg4_rlx(hp + 96, V[1][0], V[1][1], V[1][2], V[1][3]); stg4_rlx(hp + 128, V[1][4], V[1][5], V[1][6], V[1][7]);
            }
            mbar_wait(bars + B_L16, 0);
            const uint32_t kh = sm + OFF_KH + warp * 1280, vr = sm + OFF_V + (warp * 16 + (lane & 7)) * VP;
            {
                const uint32_t k0[4] = {K[1][0], K[1][1], K[1][3], K[1][4]}, k1[4] = {K[1][5], K[1][6], K[1][8], K[1][9]};
                sts4(kh + 1280 + lane * 16, k0); sts4(kh + 1792 + lane * 16, k1); sts2(kh + 2304 + lane * 8, K[1][2], K[1][7]);
                const uint32_t va = vr + (lane >> 3) * 16, vl[4] = {V[0][8], V[0][9], V[1][8], V[1][9]};
                stsm4(va + 16 * VP, V[1]); stsm4(va + 16 * VP + 64, V[1] + 4); stsm4(vr + (8 + hi * 8) * VP + 128 + ((lane >> 3) & 1) * 16, vl);
                stsm4(va + 8 * VP, V[0]); stsm4(va + 8 * VP + 64, V[0] + 4);
            }
            __syncwarp();
            if (lane == 0) mbar_arrive(bars + B_HL + 8 + 8 * warp);
            uint32_t VT[5][4], VH[10], KH[10];
#pragma unroll
            for (int s = 0; s < 5; s++) ldsm4t(VT[s], vr + (8 + ((lane >> 3) & 1) * 8) * VP + s * 32 + hi * 16);
            float sb[4][4], sc[4][4], sa[4][4];
            uint32_t qs[4][2];
#pragma unroll
            for (int h = 0; h < 4; h++) {
                const int ts = (h >> 1) * 5 + 2, ta = (h >> 1) * 5 + (h & 1) * 3;
                const bool mine = (q >> 1) == (h & 1);
                qs[h][0] = mine ? Q[ts][0] : 0u; qs[h][1] = mine ? Q[ts][1] : 0u;
                mma16c(sb[h], Q[ta][0], Q[ta][1], Q[ta + 1][0], Q[ta + 1][1], K[0][ta], K[0][ta + 1], 0.f, 0.f);
                mma16c(sc[h], Q[ta][0], Q[ta][1], Q[ta + 1][0], Q[ta + 1][1], K[1][ta], K[1][ta + 1], 0.f, 0.f);
                mma8(sb[h], qs[h][0], qs[h][1], K[0][ts]);
                mma8(sc[h], qs[h][0], qs[h][1], K[1][ts]);
            }
            mbar_wait(bars + B_HL + 8 * warp, 0);
            lds4(KH, kh + lane * 16); lds4(KH + 4, kh + 512 + lane * 16); lds2(KH + 8, kh + 1024 + lane * 8);
            ldsm4t(VH, vr + (lane >> 3) * 16); ldsm4t(VH + 4, vr + 64 + (lane >> 3) * 16); ldsm2t(VH + 8, vr + 128 + ((lane >> 3) & 1) * 16);
            STAMP(5);
            const float ninf = (tw & 63) == 0 ? -INFINITY : 0.f;
#pragma unroll
            for (int h = 0; h < 4; h++) {
                const int ta = (h >> 1) * 5 + (h & 1) * 3;
                mma16c(sa[h], Q[ta][0], Q[ta][1], Q[ta + 1][0], Q[ta + 1][1], KH[2 * h], KH[2 * h + 1], ninf, ninf);
                mma8(sa[h], qs[h][0], qs[h][1], KH[8 + (h >> 1)]);
            }
            __syncwarp();
            if (lane == 0) mbar_arrive(bars + B_G1);
            const bool gt0 = 2 * q > g, gt1 = 2 * q + 1 > g;
            const uint32_t mgt = (gt0 ? 0xffffu : 0u) | (gt1 ? 0xffff0000u : 0u);
            const float cs = 0.22360679774997896f * 1.4426950408889634f;
            uint32_t of[12][2];
#pragma unroll
            for (int h = 0; h < 4; h++) {
                const int ts = (h >> 1) * 5 + 2, ta = (h >> 1) * 5 + (h & 1) * 3;
                float t0 = gt0 ? sa[h][0] : sb[h][0], t1 = gt1 ? sa[h][1] : sb[h][1];
                float b0 = gt0 ? sb[h][2] : sc[h][2], b1 = gt1 ? sb[h][3] : sc[h][3];
                float mt_ = fmaxf(t0, t1), mb = fmaxf(b0, b1);
                mt_ = fmaxf(mt_, __shfl_xor_sync(~0u, mt_, 1)); mb = fmaxf(mb, __shfl_xor_sync(~0u, mb, 1));
                mt_ = fmaxf(mt_, __shfl_xor_sync(~0u, mt_, 2)); mb = fmaxf(mb, __shfl_xor_sync(~0u, mb, 2));
                t0 = ex2((t0 - mt_) * cs); t1 = ex2((t1 - mt_) * cs); b0 = ex2((b0 - mb) * cs); b1 = ex2((b1 - mb) * cs);
                float lt = t0 + t1, lb = b0 + b1;
                lt += __shfl_xor_sync(~0u, lt, 1); lb += __shfl_xor_sync(~0u, lb, 1);
                lt += __shfl_xor_sync(~0u, lt, 2); lb += __shfl_xor_sync(~0u, lb, 2);
                lt = rcp(lt); lb = rcp(lb);
                const uint32_t pt = pack2(t0 * lt, t1 * lt), pb = pack2(b0 * lb, b1 * lb);
                const uint32_t pA = pt & mgt, pBt = pt & ~mgt, pBb = pb & mgt, pC = pb & ~mgt;
#pragma unroll
                for (int e = 0; e < 3; e++) {
                    const int t = e == 2 ? ts : ta + e;
                    float d[4];
                    mma16c(d, pBt, pBb, 0u, pC, VT[t >> 1][(t & 1) * 2], VT[t >> 1][(t & 1) * 2 + 1], 0.f, 0.f);
                    mma8(d, pA, 0u, VH[t]);
                    of[h * 3 + e][0] = pack2(d[0], d[1]); of[h * 3 + e][1] = pack2(d[2], d[3]);
                }
            }
#pragma unroll
            for (int t = 0; t < 10; t++) {
                const int p = t / 5, r = t % 5;
#pragma unroll
                for (int e = 0; e < 2; e++) ab[0][t >> 1][(t & 1) * 2 + e] = r == 2 ? ((q & 2) ? of[p * 6 + 5][e] : of[p * 6 + 2][e]) : of[p * 6 + r][e];
            }
#pragma unroll
            for (int s = 0; s < 5; s++) stg4_rlx(my_o + j * 160 + s * 32, ab[0][s][0], ab[0][s][1], ab[0][s][2], ab[0][s][3]);
        }
        STAMP(6);
        float ac2[40];
#pragma unroll
        for (int i = 0; i < 40; i++) ac2[i] = 0.f;
        {
            const uint64_t d0 = mkdesc(sm, 5120, 512, 2);
            auto ldsrc = [&](int w, uint32_t (*dst)[4]) {
                const uint4* p = my_o + (w <= j ? w - 1 : w) * 160;
#pragma unroll
                for (int s = 0; s < 5; s++) ldg4_rlx(dst[s], p + s * 32);
            };
#pragma unroll 1
            for (int w4 = 0; w4 < 8; w4 += 4) {
#pragma unroll
                for (int u = 0; u < 4; u++) {
                    const int w = w4 + u;
                    int gd = 0;
                    while (__any_sync(~0u, max(max(max(ab[u][0][0], ab[u][1][0]), max(ab[u][2][0], ab[u][3][0])), ab[u][4][0]) == SENT) && ++gd < SPIN_LIMIT) ldsrc(w, ab[u]);
                    mbar_wait(bars + B_WO + 8 * w, 0);
                    wg_fence();
#pragma unroll
                    for (int s = 0; s < 5; s++) wgmma_rs_n80(ac2, ab[u][s], d0 + w * (WST / 16) + s * 64);
                    wg_commit();
                    if (u == 0 && w4 == 0) { ldsrc(1, ab[1]); ldsrc(2, ab[2]); }
                    if (w < 5) { wg_wait<1>(); ldsrc(w + 3, ab[(u + 3) & 3]); }
                }
            }
        }
        mbar_wait(bars + B_EP, 0);
        uint32_t tga[12], tst[12];
        const uint32_t ep = sm + OFF_EP + q * 48;
#pragma unroll
        for (int s = 0; s < 3; s++) { lds4(tga + 4 * s, ep + s * 16); lds4(tst + 4 * s, ep + 768 + min(g, 2) * 192 + s * 16); }
        wg_wait<0>();
        STAMP(8);
        {
            float gA[4] = {}, gB[4] = {}, sd[4] = {};
#pragma unroll
            for (int s = 0; s < 5; s++) {
#pragma unroll
                for (int e = 0; e < 4; e++) xr[s][e] = hf2(tga[2 * s + (e >> 1)], pack2(ac2[s * 8 + e * 2], ac2[s * 8 + e * 2 + 1]), xr[s][e]);
                mma16(gA, xr[s][0], xr[s][1], xr[s][2], xr[s][3], xr[s][0], xr[s][2]);
                mma16(gB, xr[s][0], xr[s][1], xr[s][2], xr[s][3], xr[s][1], xr[s][3]);
                mma16(sd, xr[s][0], xr[s][1], xr[s][2], xr[s][3], tst[2 * s], tst[2 * s + 1]);
            }
            const float q0 = __shfl_sync(~0u, (g & 1) ? gA[1] : gA[0], (lane & ~3) | (g >> 1)), q1 = __shfl_sync(~0u, (g & 1) ? gB[3] : gB[2], (lane & ~3) | (g >> 1));
            const float l0 = __shfl_down_sync(~0u, sd[0], 1), l1 = __shfl_down_sync(~0u, sd[2], 1);
            if (q == 0) {
                uint4* sp = &g_stats[(tw * 8 + j) * 16 + g];
                stg4_rlx(sp, __float_as_uint(sd[0]), __float_as_uint(q0), __float_as_uint(sd[1] + l0), 0u);
                stg4_rlx(sp + 8, __float_as_uint(sd[2]), __float_as_uint(q1), __float_as_uint(sd[3] + l1), 0u);
            }
        }
        STAMP(9);
        uint32_t fg[5][4], fu[5][4], tcb[12], tsb[12];
        if (role < 108) {
            mbar_wait(bars + B_FG, 0);
#pragma unroll
            for (int s = 0; s < 5; s++) {
                const uint32_t off = (5 * warp + ((warp & 1) ? (s == 4 ? 0 : s + 1) : s)) * 512 + frag;
                ldsm4t(fg[s], sm + OFF_WG + off); ldsm4t(fu[s], sm + OFF_WU + off);
            }
        }
#pragma unroll
        for (int s = 0; s < 3; s++) { lds4(tcb + 4 * s, ep + 192 + s * 16); lds4(tsb + 4 * s, ep + 384 + s * 16); lds4(tga + 4 * s, ep + 576 + s * 16); }
        float r0, r1;
        {
            const float2 u0 = lds2f(sm + OFF_EP + EP_US), u1 = lds2f(sm + OFF_EP + EP_US + 8), u2 = lds2f(sm + OFF_EP + EP_US + 16);
            const float U = u0.x + u1.x + u2.x, S = u0.y + u1.y + u2.y;
            uint32_t st[4][4]; int gd = 0;
            const uint4* sp = &g_stats[(tw * 8 + 2 * q) * 16 + g];
            do {
                ldg4_rlx(st[0], sp); ldg4_rlx(st[1], sp + 16); ldg4_rlx(st[2], sp + 8); ldg4_rlx(st[3], sp + 24);
            } while (__any_sync(~0u, (st[0][3] | st[1][3] | st[2][3] | st[3][3]) != 0) && ++gd < SPIN_LIMIT);
            STAMP(10);
            float v[6];
#pragma unroll
            for (int e = 0; e < 3; e++) { v[e] = __uint_as_float(st[0][e]) + __uint_as_float(st[1][e]); v[3 + e] = __uint_as_float(st[2][e]) + __uint_as_float(st[3][e]); }
#pragma unroll
            for (int e = 0; e < 6; e++) { v[e] += __shfl_xor_sync(~0u, v[e], 1); v[e] += __shfl_xor_sync(~0u, v[e], 2); }
            const float m0 = v[0] * (1.f / 640), m1 = v[3] * (1.f / 640);
            float s0 = rsqrtf(fmaxf(v[1] * (1.f / 640) - m0 * m0, 0.f) + 1e-5f), s1 = rsqrtf(fmaxf(v[4] * (1.f / 640) - m1 * m1, 0.f) + 1e-5f);
            r0 = fmaf(s0, v[2] - m0 * U, S); r1 = fmaf(s1, v[5] - m1 * U, S);
            s0 = rbf(s0); s1 = rbf(s1);
            rr0 = pack2(s0, s0); rr1 = pack2(s1, s1); nn0 = pack2(-m0 * s0, -m0 * s0); nn1 = pack2(-m1 * s1, -m1 * s1);
        }
        const uint32_t k0 = fkey(r0), k1 = fkey(r1);
        const uint32_t kmax = __reduce_max_sync(~0u, max(k0, k1));
        const int crow = __reduce_min_sync(~0u, k0 == kmax ? g : (k1 == kmax ? g + 8 : 99));
        const int tok_base = ((ti & 7) * 128 + warp * 16) * 2 + (ti >> 3);
        if (warp == j && lane == 0) stg2_rlx(&g_rec[tw], kmax, tok_base + 2 * crow);
        {
            const bool up = crow >= 8;
            const uint32_t rr = up ? rr1 : rr0, nn = up ? nn1 : nn0;
            if (g == (crow & 7)) {
                uint4* cp = &g_cand[(tw * 8 + j) * 24 + q];
#pragma unroll
                for (int s = 0; s < 5; s++) {
                    const uint32_t xa_ = up ? xr[s][1] : xr[s][0], xb_ = up ? xr[s][3] : xr[s][2];
                    stg4_rlx(cp + s * 4, hf2(hf2(xa_, rr, nn), tcb[2 * s], tsb[2 * s]), hf2(hf2(xb_, rr, nn), tcb[2 * s + 1], tsb[2 * s + 1]), xa_, xb_);
                }
            }
        }
        STAMP(11);
#pragma unroll
        for (int s = 0; s < 5; s++) {
#pragma unroll
            for (int e = 0; e < 4; e++) { const int t = 2 * s + (e >> 1); xr[s][e] = hf2(tga[t], hf2(hf2(xr[s][e], (e & 1) ? rr1 : rr0, (e & 1) ? nn1 : nn0), tcb[t], tsb[t]), xr[s][e]); }
        }
        bar_sync(2, 256);
        const uint32_t stg = sm + warp * 2816;
#pragma unroll
        for (int s = 0; s < 5; s++) stsm4(stg + (lane & 15) * VP + (odd ? (s == 4 ? 0 : s + 1) : s) * 32 + hi * 16, xr[s]);
        __syncwarp();
        __nv_bfloat16* const op = out + (size_t)(tok_base + (lane >> 1) * 2) * 640 + 80 * j + (lane & 1) * 8;
#pragma unroll
        for (int s = 0; s < 5; s++) lds4(xr[s], stg + (lane >> 1) * VP + (lane & 1) * 16 + s * 32);
        bool st_row = (lane >> 1) != crow;
        int win = 0, tokwin = 0; uint32_t kwin = 0;
#pragma unroll 1
        for (int pass = 0; pass < 2; pass++) {
            if (st_row) {
#pragma unroll
                for (int s = 0; s < 5; s++) *(uint4*)(op + s * 16) = make_uint4(xr[s][0], xr[s][1], xr[s][2], xr[s][3]);
            }
            if (pass) break;
            STAMP(12);
            uint32_t rc[2][4]; int gd = 0;
            do {
                ldg4_rlx(rc[0], &g_rec[lane * 4]); ldg4_rlx(rc[1], &g_rec[lane * 4 + 2]);
            } while (__any_sync(~0u, (rc[0][1] | rc[0][3] | rc[1][1] | rc[1][3]) == SENT) && ++gd < SPIN_LIMIT);
            kwin = __reduce_max_sync(~0u, max(max(rc[0][0], rc[0][2]), max(rc[1][0], rc[1][2])));
            tokwin = __reduce_min_sync(~0u, min(min(rc[0][0] == kwin ? rc[0][1] : 4096u, rc[0][2] == kwin ? rc[0][3] : 4096u), min(rc[1][0] == kwin ? rc[1][1] : 4096u, rc[1][2] == kwin ? rc[1][3] : 4096u)));
            win = (tokwin & 1) * 64 + (tokwin >> 5);
            st_row = !st_row && win != tw;
            STAMP(13);
            if (role < 108) {
                uint32_t hb[5][2];
                const uint4* cp = &g_cand[(win * 8 + warp) * 24 + q];
                do {
#pragma unroll
                    for (int s = 0; s < 5; s++) ldg2_rlx(hb[s], cp + s * 4);
                } while (__any_sync(~0u, max(max(max(hb[0][0], hb[1][0]), max(hb[2][0], hb[3][0])), hb[4][0]) == SENT) && ++gd < SPIN_LIMIT);
                float dg[2][4] = {}, du[2][4] = {};
#pragma unroll
                for (int s = 0; s < 5; s++) {
                    mma16(dg[s & 1], fg[s][0], fg[s][1], fg[s][2], fg[s][3], hb[s][0], hb[s][1]);
                    mma16(du[s & 1], fu[s][0], fu[s][1], fu[s][2], fu[s][3], hb[s][0], hb[s][1]);
                }
                const float mine = q == 0 ? dg[0][0] + dg[1][0] : q == 1 ? dg[0][2] + dg[1][2] : q == 2 ? du[0][0] + du[1][0] : du[0][2] + du[1][2];
                sts1f(sm + OFF_RED + (warp * 32 + q * 8 + g) * 4, mine);
                bar_sync(2, 256);
                if (warp == 0) {
                    float t = 0.f;
#pragma unroll
                    for (int w = 0; w < 8; w++) t += lds1f(sm + OFF_RED + (w * 32 + lane) * 4);
                    t = rbf(t);
                    const float av = rbf(t * sigm(t)) * __shfl_down_sync(~0u, t, 16);
                    const uint32_t pr = pack2(av, __shfl_down_sync(~0u, av, 1)), p8 = __shfl_down_sync(~0u, pr, 8);
                    if (lane < 8 && !(lane & 1)) stg2_rlx(&g_a[role * 4 + (lane >> 1)], pr, p8);
                }
            }
            STAMP(14);
        }
        if (role >= 88) {
            const int d = role - 88, dj = d / 5, dm = d - dj * 5, sp = (dj & 1) ? (dm == 0 ? 4 : dm - 1) : dm;
            const int ks0 = min(warp * 14, 94);
            uint32_t fd[14][4];
            mbar_wait(bars + B_FD, 0);
#pragma unroll
            for (int s = 0; s < 14; s++) ldsm4t(fd[s], sm + OFF_WD + (ks0 + s) * 512 + frag);
            uint32_t bsv[4], av[14][2], m; int gd = 0;
            do {
                ldg4_rlx(bsv, &g_cand[(win * 8 + dj) * 24 + sp * 4 + q]);
#pragma unroll
                for (int s = 0; s < 14; s++) ldg2_rlx(av[s], &g_a[(ks0 + s) * 4 + q]);
                m = bsv[0];
#pragma unroll
                for (int s = 0; s < 14; s++) m = max(m, av[s][0]);
            } while (__any_sync(~0u, m == SENT) && ++gd < SPIN_LIMIT);
            STAMP(15);
            float dy[4][4] = {};
#pragma unroll
            for (int s = 0; s < 14; s++) {
                if (s < 4 && warp == 7) av[s][0] = av[s][1] = 0u;
                mma16(dy[s & 3], fd[s][0], fd[s][1], fd[s][2], fd[s][3], av[s][0], av[s][1]);
            }
            if (q < 2) sts1f(sm + OFF_RED2 + (warp * 16 + q * 8 + g) * 4, q == 0 ? (dy[0][0] + dy[1][0]) + (dy[2][0] + dy[3][0]) : (dy[0][2] + dy[1][2]) + (dy[2][2] + dy[3][2]));
            bar_sync(2, 256);
            if (tid < 8) {
                float y0 = 0.f, y1 = 0.f;
#pragma unroll
                for (int w = 0; w < 8; w++) { const float2 v = lds2f(sm + OFF_RED2 + w * 64 + tid * 8); y0 += v.x; y1 += v.y; }
                const float sg = rbf(sigm(rbf(__uint_as_float((kwin & 0x80000000u) ? kwin & 0x7fffffffu : ~kwin))));
                const uint32_t hh = tid < 4 ? bsv[0] : bsv[1], xx = tid < 4 ? bsv[2] : bsv[3];
                const uint32_t z = pack2(blo(hh) + rbf(rbf(y0) * sg), bhi(hh) + rbf(rbf(y1) * sg));
                *(uint32_t*)(out + (size_t)tokwin * 640 + d * 16 + tid * 2) = hf2(lds1(sm + OFF_EP + EP_GD + tid * 4), z, xx);
            }
        }
        STAMP(16);
    }
}

typedef CUresult (*EncFn)(CUtensorMap*, CUtensorMapDataType, cuuint32_t, void*, const cuuint64_t*, const cuuint64_t*, const cuuint32_t*, const cuuint32_t*,
                          CUtensorMapInterleave, CUtensorMapSwizzle, CUtensorMapL2promotion, CUtensorMapFloatOOBfill);
static void make_map(EncFn enc, CUtensorMap* m, const void* base, int rank, const cuuint64_t* dims, const cuuint64_t* strides, const cuuint32_t* box, CUtensorMapSwizzle sw) {
    const cuuint32_t es[5] = {1, 1, 1, 1, 1};
    enc(m, CU_TENSOR_MAP_DATA_TYPE_BFLOAT16, rank, (void*)base, dims, strides, box, es, CU_TENSOR_MAP_INTERLEAVE_NONE, sw, CU_TENSOR_MAP_L2_PROMOTION_NONE, CU_TENSOR_MAP_FLOAT_OOB_FILL_NONE);
}

extern "C" void kernel_launch(void* const* d_in, const int* in_sizes, int n_in, void* d_out, int out_size) {
    typedef const __nv_bfloat16* P;
    P x = (P)d_in[0], wqkv = (P)d_in[1], wo = (P)d_in[2], wr = (P)d_in[4], wg = (P)d_in[5], wu = (P)d_in[6], wd = (P)d_in[7], c = (P)d_in[8], wmod = (P)d_in[9];
    void* fn = nullptr; cudaDriverEntryPointQueryResult qr;
    cudaGetDriverEntryPoint("cuTensorMapEncodeTiled", &fn, cudaEnableDefault, &qr);
    EncFn enc = (EncFn)fn;
    CUtensorMap mx, mw, mt, mo, mg, mu, md, mm;
    { cuuint64_t d[] = {640, 2, 1024}, s[] = {1280, 2560}; cuuint32_t b[] = {64, 1, 128}; make_map(enc, &mx, x, 3, d, s, b, CU_TENSOR_MAP_SWIZZLE_128B); }
    { cuuint64_t d[] = {32, 640, 20, 3}, s[] = {3840, 64, 1280}; cuuint32_t b[] = {32, 32, 2, 3}; make_map(enc, &mw, wqkv, 4, d, s, b, CU_TENSOR_MAP_SWIZZLE_64B); }
    { cuuint64_t d[] = {640, 640, 3}, s[] = {3840, 1280}; cuuint32_t b[] = {16, 32, 3}; make_map(enc, &mt, wqkv, 3, d, s, b, CU_TENSOR_MAP_SWIZZLE_32B); }
    { cuuint64_t d[] = {640, 640}, s[] = {1280}; cuuint32_t b[] = {32, 80}; make_map(enc, &mo, wo, 2, d, s, b, CU_TENSOR_MAP_SWIZZLE_64B); }
    { cuuint64_t d[] = {1728, 160, 4}, s[] = {3456, 3456 * 160}; cuuint32_t b[] = {16, 160, 4}; make_map(enc, &mg, wg, 3, d, s, b, CU_TENSOR_MAP_SWIZZLE_32B); make_map(enc, &mu, wu, 3, d, s, b, CU_TENSOR_MAP_SWIZZLE_32B); }
    { cuuint64_t d[] = {640, 216, 8}, s[] = {1280, 1280 * 216}; cuuint32_t b[] = {16, 216, 8}; make_map(enc, &md, wd, 3, d, s, b, CU_TENSOR_MAP_SWIZZLE_32B); }
    { cuuint64_t d[] = {3840, 160, 4}, s[] = {7680, 7680 * 160}; cuuint32_t b[] = {16, 160, 4}; make_map(enc, &mm, wmod, 3, d, s, b, CU_TENSOR_MAP_SWIZZLE_32B); }
    cudaFuncSetAttribute(fused_kernel, cudaFuncAttributeMaxDynamicSharedMemorySize, SMEM_BYTES);
    fused_kernel<<<128, 384, SMEM_BYTES>>>(mx, mw, mt, mo, mg, mu, md, mm, wqkv, wo, wr, wg, wu, wd, c, wmod, (__nv_bfloat16*)d_out);
}
```

```cpp
#include <cuda_runtime.h>
#include <cuda_bf16.h>
#include <cuda.h>
#include <stdint.h>

#define SENT 0xFFFFFFFFu
#define SPIN_LIMIT (1 << 17)

__device__ unsigned g_epoch;
__device__ __align__(128) unsigned g_mod[3840];
__device__ __align__(128) unsigned g_ready[160];
__device__ __align__(128) uint4 g_halo[128 * 160];
__device__ __align__(128) uint4 g_o[128 * 8 * 160];
__device__ __align__(128) uint4 g_stats[2048 * 8];
__device__ __align__(128) uint2 g_rec[8 * 128];
__device__ __align__(128) uint4 g_cand[128 * 8 * 24];
__device__ __align__(128) uint2 g_a[128 * 8];
__device__ __align__(128) uint2 g_us[16];
#define STAMP(n)
#define STAMPT(n, t)

constexpr uint32_t OFF_W = 163840, WST = 15360;
constexpr uint32_t OFF_WM = OFF_W + 2 * WST;
constexpr uint32_t OFF_V = 122880, VP = 176;
constexpr uint32_t OFF_KH = OFF_W;
constexpr uint32_t OFF_WD = 129024, OFF_WG = 184320;
constexpr uint32_t OFF_TAB = 225280;
constexpr uint32_t OFF_S = OFF_TAB + 2560;
constexpr uint32_t OFF_EP = OFF_S + 1280;
constexpr uint32_t EP_GD = 1344, EP_US = 1376;
constexpr uint32_t OFF_RED = OFF_EP + 1408;
constexpr uint32_t OFF_BAR = OFF_RED + 1024;
constexpr uint32_t OFF_PROF = OFF_BAR + 384;
constexpr uint32_t SMEM_BYTES = OFF_PROF + 128;
enum { B_XF = 0, B_WF = 10, B_WO = 14, B_HL = 22, B_FG = 30, B_FD, B_RDY, B_WM, B_EP, B_G0, B_G2, B_L16, B_WE, B_WMF = B_WE + 5, B_N };
constexpr uint32_t SM0 = 1024;
#define BAR0(i) (SM0 + OFF_BAR + 8 * (i))
#define BAR(i) (sm + OFF_BAR + 8 * (i))

__device__ __forceinline__ uint32_t smem_u32(const void* p) { return (uint32_t)__cvta_generic_to_shared(p); }
__device__ __forceinline__ void mbar_init(uint32_t b, int cnt) { asm volatile("mbarrier.init.shared::cta.b64 [%0], %1;" ::"r"(b), "r"(cnt) : "memory"); }
__device__ __forceinline__ void mbar_expect_tx(uint32_t b, uint32_t bytes) { asm volatile("mbarrier.arrive.expect_tx.shared::cta.b64 _, [%0], %1;" ::"r"(b), "r"(bytes) : "memory"); }
__device__ __forceinline__ void mbar_arrive(uint32_t b) { asm volatile("mbarrier.arrive.shared::cta.b64 _, [%0];" ::"r"(b) : "memory"); }
__device__ __forceinline__ bool mbar_try(uint32_t b, uint32_t par) {
    uint32_t ok;
    asm volatile("{.reg .pred p; mbarrier.try_wait.parity.shared::cta.b64 p, [%1], %2; selp.u32 %0, 1, 0, p;}" : "=r"(ok) : "r"(b), "r"(par) : "memory");
    return ok;
}
__device__ __forceinline__ void mbar_wait(uint32_t b, uint32_t par) { int g = 0; while (!mbar_try(b, par)) { if (++g > SPIN_LIMIT) break; } }
__device__ __forceinline__ void bar_sync(int id, int n) { __syncwarp(); asm volatile("bar.sync %0, %1;" ::"r"(id), "r"(n) : "memory"); }
__device__ __forceinline__ void tma2d(uint32_t dst, const CUtensorMap* m, int c0, int c1, uint32_t bar) {
    asm volatile("cp.async.bulk.tensor.2d.shared::cluster.global.mbarrier::complete_tx::bytes [%0], [%1, {%3, %4}], [%2];" ::"r"(dst), "l"(m), "r"(bar), "r"(c0), "r"(c1) : "memory");
}
__device__ __forceinline__ void tma3d(uint32_t dst, const CUtensorMap* m, int c0, int c1, int c2, uint32_t bar) {
    asm volatile("cp.async.bulk.tensor.3d.shared::cluster.global.mbarrier::complete_tx::bytes [%0], [%1, {%3, %4, %5}], [%2];" ::"r"(dst), "l"(m), "r"(bar), "r"(c0), "r"(c1), "r"(c2) : "memory");
}
__device__ __forceinline__ void tma4d(uint32_t dst, const CUtensorMap* m, int c0, int c1, int c2, int c3, uint32_t bar) {
    asm volatile("cp.async.bulk.tensor.4d.shared::cluster.global.mbarrier::complete_tx::bytes [%0], [%1, {%3, %4, %5, %6}], [%2];" ::"r"(dst), "l"(m), "r"(bar), "r"(c0), "r"(c1), "r"(c2), "r"(c3) : "memory");
}
__device__ __forceinline__ void l2_prefetch(const void* p, uint32_t bytes) { asm volatile("cp.async.bulk.prefetch.L2.global [%0], %1;" ::"l"(p), "r"(bytes) : "memory"); }
__device__ __forceinline__ void pf_map(const CUtensorMap* m) { asm volatile("prefetch.tensormap [%0];" ::"l"(m) : "memory"); }
__device__ __forceinline__ void wg_fence() { asm volatile("wgmma.fence.sync.aligned;" ::: "memory"); }
__device__ __forceinline__ void wg_commit() { asm volatile("wgmma.commit_group.sync.aligned;" ::: "memory"); }
template <int N> __device__ __forceinline__ void wg_wait() { asm volatile("wgmma.wait_group.sync.aligned %0;" ::"n"(N) : "memory"); }
__device__ __forceinline__ void ldsm4(uint32_t* r, uint32_t addr) { asm volatile("ldmatrix.sync.aligned.m8n8.x4.shared.b16 {%0,%1,%2,%3}, [%4];" : "=r"(r[0]), "=r"(r[1]), "=r"(r[2]), "=r"(r[3]) : "r"(addr) : "memory"); }
__device__ __forceinline__ void ldsm4t(uint32_t* r, uint32_t addr) { asm volatile("ldmatrix.sync.aligned.m8n8.x4.trans.shared.b16 {%0,%1,%2,%3}, [%4];" : "=r"(r[0]), "=r"(r[1]), "=r"(r[2]), "=r"(r[3]) : "r"(addr) : "memory"); }
__device__ __forceinline__ void stsm4(uint32_t addr, const uint32_t* r) { asm volatile("stmatrix.sync.aligned.m8n8.x4.shared.b16 [%4], {%0,%1,%2,%3};" ::"r"(r[0]), "r"(r[1]), "r"(r[2]), "r"(r[3]), "r"(addr) : "memory"); }
__device__ __forceinline__ void lds4(uint32_t* r, uint32_t addr) { asm volatile("ld.shared.v4.u32 {%0,%1,%2,%3}, [%4];" : "=r"(r[0]), "=r"(r[1]), "=r"(r[2]), "=r"(r[3]) : "r"(addr) : "memory"); }
__device__ __forceinline__ void sts4(uint32_t addr, const uint32_t* r) { asm volatile("st.shared.v4.u32 [%4], {%0,%1,%2,%3};" ::"r"(r[0]), "r"(r[1]), "r"(r[2]), "r"(r[3]), "r"(addr) : "memory"); }
__device__ __forceinline__ float2 lds2f(uint32_t addr) { float2 v; asm volatile("ld.shared.v2.f32 {%0,%1}, [%2];" : "=f"(v.x), "=f"(v.y) : "r"(addr) : "memory"); return v; }
__device__ __forceinline__ float lds1f(uint32_t addr) { float v; asm volatile("ld.shared.f32 %0, [%1];" : "=f"(v) : "r"(addr) : "memory"); return v; }
__device__ __forceinline__ void sts1f(uint32_t addr, float v) { asm volatile("st.shared.f32 [%0], %1;" ::"r"(addr), "f"(v) : "memory"); }
__device__ __forceinline__ void sts1(uint32_t addr, uint32_t v) { asm volatile("st.shared.u32 [%0], %1;" ::"r"(addr), "r"(v) : "memory"); }
__device__ __forceinline__ void ldg4_rlx(uint32_t* r, const void* p) { asm volatile("{.reg .b128 t; ld.relaxed.gpu.global.b128 t, [%4]; mov.b128 {%0,%1,%2,%3}, t;}" : "=r"(r[0]), "=r"(r[1]), "=r"(r[2]), "=r"(r[3]) : "l"(p) : "memory"); }
__device__ __forceinline__ void ldg2_rlx(uint32_t* r, const void* p) { asm volatile("{.reg .b64 t; ld.relaxed.gpu.global.b64 t, [%2]; mov.b64 {%0,%1}, t;}" : "=r"(r[0]), "=r"(r[1]) : "l"(p) : "memory"); }
__device__ __forceinline__ uint32_t ldg1_rlx(const void* p) { uint32_t v; asm volatile("ld.relaxed.gpu.global.u32 %0, [%1];" : "=r"(v) : "l"(p) : "memory"); return v; }
__device__ __forceinline__ void stg4_rlx(void* p, uint32_t a, uint32_t b, uint32_t c, uint32_t d) { asm volatile("{.reg .b128 t; mov.b128 t, {%1,%2,%3,%4}; st.relaxed.gpu.global.b128 [%0], t;}" ::"l"(p), "r"(a), "r"(b), "r"(c), "r"(d) : "memory"); }
__device__ __forceinline__ void stg2_rlx(void* p, uint32_t a, uint32_t b) { asm volatile("{.reg .b64 t; mov.b64 t, {%1,%2}; st.relaxed.gpu.global.b64 [%0], t;}" ::"l"(p), "r"(a), "r"(b) : "memory"); }
__device__ __forceinline__ void stg1_rlx(void* p, uint32_t a) { asm volatile("st.relaxed.gpu.global.u32 [%0], %1;" ::"l"(p), "r"(a) : "memory"); }
__device__ __forceinline__ void ldg4_nc(uint32_t* r, const void* p) { asm volatile("ld.global.nc.L1::no_allocate.v4.u32 {%0,%1,%2,%3}, [%4];" : "=r"(r[0]), "=r"(r[1]), "=r"(r[2]), "=r"(r[3]) : "l"(p)); }
__device__ __forceinline__ uint64_t mkdesc(uint32_t addr, uint32_t lbo, uint32_t sbo, uint32_t sw) { return (uint64_t)((addr & 0x3FFFF) >> 4) | ((uint64_t)(lbo >> 4) << 16) | ((uint64_t)(sbo >> 4) << 32) | ((uint64_t)sw << 62); }
__device__ __forceinline__ uint32_t pack2(float lo, float hi) { uint32_t r; asm("cvt.rn.bf16x2.f32 %0, %1, %2;" : "=r"(r) : "f"(hi), "f"(lo)); return r; }
__device__ __forceinline__ float blo(uint32_t v) { return __uint_as_float(v << 16); }
__device__ __forceinline__ float bhi(uint32_t v) { return __uint_as_float(v & 0xffff0000u); }
__device__ __forceinline__ float rbf(float x) { return blo(pack2(x, 0.f)); }
__device__ __forceinline__ uint32_t hf2(uint32_t a, uint32_t b, uint32_t c) { uint32_t r; asm("fma.rn.bf16x2 %0, %1, %2, %3;" : "=r"(r) : "r"(a), "r"(b), "r"(c)); return r; }
__device__ __forceinline__ uint32_t movm(uint32_t a) { uint32_t r; asm volatile("movmatrix.sync.aligned.m8n8.trans.b16 %0, %1;" : "=r"(r) : "r"(a)); return r; }
__device__ __forceinline__ float ex2(float x) { float r; asm("ex2.approx.ftz.f32 %0, %1;" : "=f"(r) : "f"(x)); return r; }
__device__ __forceinline__ void mma16(float* d, uint32_t a0, uint32_t a1, uint32_t a2, uint32_t a3, uint32_t b0, uint32_t b1) {
    asm volatile("mma.sync.aligned.m16n8k16.row.col.f32.bf16.bf16.f32 {%0,%1,%2,%3}, {%4,%5,%6,%7}, {%8,%9}, {%0,%1,%2,%3};"
                 : "+f"(d[0]), "+f"(d[1]), "+f"(d[2]), "+f"(d[3]) : "r"(a0), "r"(a1), "r"(a2), "r"(a3), "r"(b0), "r"(b1));
}
__device__ __forceinline__ void mma8(float* d, uint32_t a0, uint32_t a1, uint32_t b0) {
    asm volatile("mma.sync.aligned.m16n8k8.row.col.f32.bf16.bf16.f32 {%0,%1,%2,%3}, {%4,%5}, {%6}, {%0,%1,%2,%3};"
                 : "+f"(d[0]), "+f"(d[1]), "+f"(d[2]), "+f"(d[3]) : "r"(a0), "r"(a1), "r"(b0));
}
__device__ __forceinline__ uint32_t umax4(const uint32_t* v, uint32_t m) { return max(max(max(v[0], v[1]), max(v[2], v[3])), m); }
__device__ __forceinline__ uint32_t fkey(float f) { uint32_t u = __float_as_uint(f); return (u & 0x80000000u) ? ~u : (u | 0x80000000u); }
__device__ __forceinline__ float rcp(float x) { float r; asm("rcp.approx.ftz.f32 %0, %1;" : "=f"(r) : "f"(x)); return r; }
__device__ __forceinline__ float sigm(float x) { return rcp(1.f + ex2(x * -1.4426950408889634f)); }
__device__ __forceinline__ void mma16c(float* d, uint32_t a0, uint32_t a1, uint32_t a2, uint32_t a3, uint32_t b0, uint32_t b1, float c0, float c1) {
    asm volatile("mma.sync.aligned.m16n8k16.row.col.f32.bf16.bf16.f32 {%0,%1,%2,%3}, {%4,%5,%6,%7}, {%8,%9}, {%10,%11,%12,%12};"
                 : "=f"(d[0]), "=f"(d[1]), "=f"(d[2]), "=f"(d[3]) : "r"(a0), "r"(a1), "r"(a2), "r"(a3), "r"(b0), "r"(b1), "f"(c0), "f"(c1), "f"(0.f));
}
__device__ __forceinline__ void ldsm2t(uint32_t* r, uint32_t addr) { asm volatile("ldmatrix.sync.aligned.m8n8.x2.trans.shared.b16 {%0,%1}, [%2];" : "=r"(r[0]), "=r"(r[1]) : "r"(addr) : "memory"); }
__device__ __forceinline__ void stsm2(uint32_t addr, uint32_t a, uint32_t b) { asm volatile("stmatrix.sync.aligned.m8n8.x2.shared.b16 [%2], {%0,%1};" ::"r"(a), "r"(b), "r"(addr) : "memory"); }
__device__ __forceinline__ void lds2(uint32_t* r, uint32_t addr) { asm volatile("ld.shared.v2.u32 {%0,%1}, [%2];" : "=r"(r[0]), "=r"(r[1]) : "r"(addr) : "memory"); }
__device__ __forceinline__ void sts2(uint32_t addr, uint32_t a, uint32_t b) { asm volatile("st.shared.v2.u32 [%2], {%0,%1};" ::"r"(a), "r"(b), "r"(addr) : "memory"); }
__device__ __forceinline__ void sts16(uint32_t addr, uint32_t v) { asm volatile("st.shared.u16 [%0], %1;" ::"r"(addr), "h"((unsigned short)v) : "memory"); }
__device__ __forceinline__ uint32_t lds1(uint32_t addr) { uint32_t v; asm volatile("ld.shared.u32 %0, [%1];" : "=r"(v) : "r"(addr) : "memory"); return v; }
__device__ __forceinline__ bool elect1() { uint32_t p; asm volatile("{.reg .pred P; elect.sync _|P, 0xffffffff; selp.u32 %0, 1, 0, P;}" : "=r"(p)); return p; }
__device__ __forceinline__ void tma2d_mc(uint32_t dst, const CUtensorMap* m, int c0, int c1, uint32_t bar) {
    asm volatile("cp.async.bulk.tensor.2d.shared::cluster.global.mbarrier::complete_tx::bytes.multicast::cluster [%0], [%1, {%3, %4}], [%2], %5;" ::"r"(dst), "l"(m), "r"(bar), "r"(c0), "r"(c1), "h"((unsigned short)3) : "memory");
}
__device__ __forceinline__ void tma3d_mc(uint32_t dst, const CUtensorMap* m, int c0, int c1, int c2, uint32_t bar) {
    asm volatile("cp.async.bulk.tensor.3d.shared::cluster.global.mbarrier::complete_tx::bytes.multicast::cluster [%0], [%1, {%3, %4, %5}], [%2], %6;" ::"r"(dst), "l"(m), "r"(bar), "r"(c0), "r"(c1), "r"(c2), "h"((unsigned short)3) : "memory");
}
__device__ __forceinline__ void tma4d_mc(uint32_t dst, const CUtensorMap* m, int c0, int c1, int c2, int c3, uint32_t bar) {
    asm volatile("cp.async.bulk.tensor.4d.shared::cluster.global.mbarrier::complete_tx::bytes.multicast::cluster [%0], [%1, {%3, %4, %5, %6}], [%2], %7;" ::"r"(dst), "l"(m), "r"(bar), "r"(c0), "r"(c1), "r"(c2), "r"(c3), "h"((unsigned short)3) : "memory");
}
__device__ __forceinline__ void mbar_arrive_cl(uint32_t b) { asm volatile("mbarrier.arrive.shared::cluster.b64 _, [%0];" ::"r"(b) : "memory"); }
__device__ __forceinline__ uint32_t hm2(uint32_t a, uint32_t b) { uint32_t r; asm("mul.rn.bf16x2 %0, %1, %2;" : "=r"(r) : "r"(a), "r"(b)); return r; }
__device__ __forceinline__ void wgmma_rs_n192(float* d, const uint32_t* a, uint64_t bdesc) {
    asm volatile("wgmma.mma_async.sync.aligned.m64n192k16.f32.bf16.bf16 {%0,%1,%2,%3,%4,%5,%6,%7,%8,%9,%10,%11,%12,%13,%14,%15,%16,%17,%18,%19,%20,%21,%22,%23,%24,%25,%26,%27,%28,%29,%30,%31,%32,%33,%34,%35,%36,%37,%38,%39,%40,%41,%42,%43,%44,%45,%46,%47,%48,%49,%50,%51,%52,%53,%54,%55,%56,%57,%58,%59,%60,%61,%62,%63,%64,%65,%66,%67,%68,%69,%70,%71,%72,%73,%74,%75,%76,%77,%78,%79,%80,%81,%82,%83,%84,%85,%86,%87,%88,%89,%90,%91,%92,%93,%94,%95}, {%96,%97,%98,%99}, %100, 1, 1, 1, 1;"
        : "+f"(d[0]),"+f"(d[1]),"+f"(d[2]),"+f"(d[3]),"+f"(d[4]),"+f"(d[5]),"+f"(d[6]),"+f"(d[7]),"+f"(d[8]),"+f"(d[9]),"+f"(d[10]),"+f"(d[11]),"+f"(d[12]),"+f"(d[13]),"+f"(d[14]),"+f"(d[15]),"+f"(d[16]),"+f"(d[17]),"+f"(d[18]),"+f"(d[19]),"+f"(d[20]),"+f"(d[21]),"+f"(d[22]),"+f"(d[23]),"+f"(d[24]),"+f"(d[25]),"+f"(d[26]),"+f"(d[27]),"+f"(d[28]),"+f"(d[29]),"+f"(d[30]),"+f"(d[31]),"+f"(d[32]),"+f"(d[33]),"+f"(d[34]),"+f"(d[35]),"+f"(d[36]),"+f"(d[37]),"+f"(d[38]),"+f"(d[39]),"+f"(d[40]),"+f"(d[41]),"+f"(d[42]),"+f"(d[43]),"+f"(d[44]),"+f"(d[45]),"+f"(d[46]),"+f"(d[47]),"+f"(d[48]),"+f"(d[49]),"+f"(d[50]),"+f"(d[51]),"+f"(d[52]),"+f"(d[53]),"+f"(d[54]),"+f"(d[55]),"+f"(d[56]),"+f"(d[57]),"+f"(d[58]),"+f"(d[59]),"+f"(d[60]),"+f"(d[61]),"+f"(d[62]),"+f"(d[63]),"+f"(d[64]),"+f"(d[65]),"+f"(d[66]),"+f"(d[67]),"+f"(d[68]),"+f"(d[69]),"+f"(d[70]),"+f"(d[71]),"+f"(d[72]),"+f"(d[73]),"+f"(d[74]),"+f"(d[75]),"+f"(d[76]),"+f"(d[77]),"+f"(d[78]),"+f"(d[79]),"+f"(d[80]),"+f"(d[81]),"+f"(d[82]),"+f"(d[83]),"+f"(d[84]),"+f"(d[85]),"+f"(d[86]),"+f"(d[87]),"+f"(d[88]),"+f"(d[89]),"+f"(d[90]),"+f"(d[91]),"+f"(d[92]),"+f"(d[93]),"+f"(d[94]),"+f"(d[95])
        : "r"(a[0]), "r"(a[1]), "r"(a[2]), "r"(a[3]), "l"(bdesc));
}
__device__ __forceinline__ void wgmma_rs_n48(float* d, const uint32_t* a, uint64_t bdesc) {
    asm volatile("wgmma.mma_async.sync.aligned.m64n48k16.f32.bf16.bf16 {%0,%1,%2,%3,%4,%5,%6,%7,%8,%9,%10,%11,%12,%13,%14,%15,%16,%17,%18,%19,%20,%21,%22,%23}, {%24,%25,%26,%27}, %28, 1, 1, 1, 1;"
        : "+f"(d[0]),"+f"(d[1]),"+f"(d[2]),"+f"(d[3]),"+f"(d[4]),"+f"(d[5]),"+f"(d[6]),"+f"(d[7]),"+f"(d[8]),"+f"(d[9]),"+f"(d[10]),"+f"(d[11]),"+f"(d[12]),"+f"(d[13]),"+f"(d[14]),"+f"(d[15]),"+f"(d[16]),"+f"(d[17]),"+f"(d[18]),"+f"(d[19]),"+f"(d[20]),"+f"(d[21]),"+f"(d[22]),"+f"(d[23])
        : "r"(a[0]), "r"(a[1]), "r"(a[2]), "r"(a[3]), "l"(bdesc));
}
__device__ __forceinline__ void wgmma_rs_n80(float* d, const uint32_t* a, uint64_t bdesc) {
    asm volatile("wgmma.mma_async.sync.aligned.m64n80k16.f32.bf16.bf16 {%0,%1,%2,%3,%4,%5,%6,%7,%8,%9,%10,%11,%12,%13,%14,%15,%16,%17,%18,%19,%20,%21,%22,%23,%24,%25,%26,%27,%28,%29,%30,%31,%32,%33,%34,%35,%36,%37,%38,%39}, {%40,%41,%42,%43}, %44, 1, 1, 1, 1;"
        : "+f"(d[0]),"+f"(d[1]),"+f"(d[2]),"+f"(d[3]),"+f"(d[4]),"+f"(d[5]),"+f"(d[6]),"+f"(d[7]),"+f"(d[8]),"+f"(d[9]),"+f"(d[10]),"+f"(d[11]),"+f"(d[12]),"+f"(d[13]),"+f"(d[14]),"+f"(d[15]),"+f"(d[16]),"+f"(d[17]),"+f"(d[18]),"+f"(d[19]),"+f"(d[20]),"+f"(d[21]),"+f"(d[22]),"+f"(d[23]),"+f"(d[24]),"+f"(d[25]),"+f"(d[26]),"+f"(d[27]),"+f"(d[28]),"+f"(d[29]),"+f"(d[30]),"+f"(d[31]),"+f"(d[32]),"+f"(d[33]),"+f"(d[34]),"+f"(d[35]),"+f"(d[36]),"+f"(d[37]),"+f"(d[38]),"+f"(d[39])
        : "r"(a[0]), "r"(a[1]), "r"(a[2]), "r"(a[3]), "l"(bdesc));
}

__global__ void __cluster_dims__(2, 1, 1) __launch_bounds__(384, 1)
fused_kernel(const __grid_constant__ CUtensorMap mm, const __grid_constant__ CUtensorMap mx, const __grid_constant__ CUtensorMap mw,
             const __grid_constant__ CUtensorMap mt, const __grid_constant__ CUtensorMap mo, const __grid_constant__ CUtensorMap mg,
             const __grid_constant__ CUtensorMap mu, const __grid_constant__ CUtensorMap md, const __grid_constant__ CUtensorMap mr,
             const __nv_bfloat16* __restrict__ wqkv, const __nv_bfloat16* __restrict__ wo,
             const __nv_bfloat16* __restrict__ wr, const __nv_bfloat16* __restrict__ wg, const __nv_bfloat16* __restrict__ wu,
             const __nv_bfloat16* __restrict__ wd, const __nv_bfloat16* __restrict__ cvec, const __nv_bfloat16* __restrict__ wmod,
             __nv_bfloat16* __restrict__ out) {
    extern __shared__ __align__(1024) char sm_raw[];
    const uint32_t sm = ((blockIdx.x & 1) << 24) + SM0;
    STAMP(30);
    const int tid = threadIdx.x, warp = __shfl_sync(~0u, tid >> 5, 0), lane = tid & 31;
    const int cl = blockIdx.x >> 1, rank = blockIdx.x & 1;
    const int grp = cl < 4 ? 0 : (cl < 36 ? (cl - 4) & 7 : 1 + (cl - 36) % 7), j = cl < 4 ? 4 + cl : (cl < 36 ? (cl - 4) >> 3 : 4 + (cl - 36) / 7);
    const bool spare = cl >= 64;
    const int ti = grp * 2 + rank, role = spare ? blockIdx.x : ti * 8 + j, odd = j & 1;
    uint4 cw = make_uint4(0, 0, 0, 0); uint32_t epoch = 0;
    if (warp == 8) {
        if (elect1()) {
            if (!spare) {
#pragma unroll 1
                for (int r = 0; r < 5; r++) l2_prefetch(wmod + (size_t)(role * 5 + r) * 3840, 2560);
            }
#pragma unroll
            for (int i = 0; i < B_N; i++) mbar_init(BAR(i), i >= B_WE ? (spare ? 8 : 16) : (i > B_EP ? 8 : (i == B_EP ? 3 : 1)));
            asm volatile("fence.mbarrier_init.release.cluster;" ::: "memory");
            if (role < 80) { mbar_expect_tx(BAR(B_WM), 20480); tma3d(sm + OFF_WM, &mm, role * 16, 0, 0, BAR(B_WM)); }
            STAMPT(22, 256);
        }
        __syncwarp();
    } else if (warp > 8 || warp == 0 || spare) {
        if (warp > 8) cw = ((const uint4*)cvec)[min(tid - 288, 79)];
        epoch = ldg1_rlx(&g_epoch) + 1;
    }
    asm volatile("barrier.cluster.arrive.relaxed.aligned;" ::: "memory");
    if (smem_u32(sm_raw) != sm) return;
    const uint32_t tag = epoch & 0xffffu;
    const int g = lane >> 2, q = lane & 3;
    const uint32_t frow = (lane & 7) + (lane >> 4) * 8, fh = (lane >> 3) & 1;
    const uint32_t frag = frow * 32 + ((fh ^ ((lane >> 2) & 1)) << 4);

    if (warp >= 8) {
        asm volatile("setmaxnreg.dec.sync.aligned.u32 104;");
        if (warp == 8) {
            if (!spare && elect1()) {
#pragma unroll 1
                for (int c = 0; c < 10; c++) { mbar_expect_tx(BAR(B_XF + c), 16384); tma3d(sm + c * 16384, &mx, c * 64, ti >> 3, (ti & 7) * 128, BAR(B_XF + c)); }
                STAMPT(23, 256);
            }
            __syncwarp();
            asm volatile("barrier.cluster.wait.aligned;" ::: "memory");
            if (!elect1()) return;
            if (spare) {
                mbar_wait(BAR(B_RDY), 0);
#pragma unroll 1
                for (int it = 0; it < 20; it++) {
                    const int s = it % 5;
                    if (it >= 5) mbar_wait(BAR(B_WE + s), (it / 5 - 1) & 1);
                    mbar_expect_tx(BAR(B_XF + s), 40960);
                    tma3d(sm + s * 40960, &mr, 0, it * 32, 20 + (role - 128) * 10, BAR(B_XF + s));
                }
                return;
            }
            const int col_main = 80 * j + 16 * odd, col_tail = 80 * j + (odd ? 0 : 64);
#pragma unroll 1
            for (int it = 0; it < 20; it++) {
                if (it == 2) { l2_prefetch(wqkv + (size_t)(64 + role * 4 + (role >> 1)) * 1920, 5 * 3840); mbar_wait(BAR(B_WMF), 0); }
                if (it >= 4) mbar_wait(BAR(B_WE + (it & 3)), ((it >> 2) & 1) ^ 1);
                {
                    const uint32_t b = BAR(B_WF + (it & 3)), dst = sm + OFF_W + (it & 3) * WST + rank * 7680;
                    mbar_expect_tx(b, WST);
                    tma4d_mc(dst, &mw, 0, it * 32 + rank * 16, col_main >> 5, 0, b);
                    tma3d_mc(dst + 6144, &mt, col_tail, it * 32 + rank * 16, 0, b);
                }
                if (it == 3) l2_prefetch(wo + role * 3200, 6400);
                if (it >= 4 && !(it & 1)) {
                    const int w = (it - 4) >> 1, row = (w == 0 ? j : (w <= j ? w - 1 : w)) * 80 + rank * 40;
                    const uint32_t b = BAR(B_WO + w), dst = sm + w * WST + rank * 2560;
                    mbar_expect_tx(b, WST);
                    tma2d_mc(dst, &mo, col_main, row, b); tma2d_mc(dst + 5120, &mo, col_main + 32, row, b); tma2d_mc(dst + 10240, &mo, col_tail, row, b);
                }
                if (it >= 5 && it < 17 && (it & 1)) l2_prefetch((it < 9 ? wg : (it < 13 ? wu : wd)) + role * 8640 + (it & 2) * 2160, 8640);
            }
            STAMPT(24, 256);
            if (role < 108) { mbar_wait(BAR(B_G0), 0); mbar_expect_tx(BAR(B_FG), 40960); tma3d(sm + OFF_WG, (role & 1) ? &mu : &mg, (role >> 1) * 32, 0, 0, BAR(B_FG)); }
            if (role >= 88) { mbar_wait(BAR(B_G2), 0); mbar_expect_tx(BAR(B_FD), 55296); tma3d(sm + OFF_WD, &md, (role - 88) * 16, 0, 0, BAR(B_FD)); }
            return;
        }
        const int at = tid - 288;
        if (at < 80) {
            const uint32_t a = sm + OFF_S + (at >> 1) * 32 + (at & 1) * 4, wv[4] = {cw.x, cw.y, cw.z, cw.w};
#pragma unroll
            for (int e = 0; e < 4; e++) sts1(a + e * 8, pack2(blo(wv[e]) * sigm(blo(wv[e])), bhi(wv[e]) * sigm(bhi(wv[e]))));
        }
        STAMPT(26, 288);
        __syncwarp();
        asm volatile("bar.arrive 0, 352;" ::: "memory");
        asm volatile("barrier.cluster.wait.aligned;" ::: "memory");
        int gd = 0;
        {
            uint32_t w[4][4], bad;
            do {
                bad = 0;
#pragma unroll
                for (int e = 0; e < 4; e++) ldg4_rlx(w[e], &g_mod[min(at + e * 96, 319) * 4]);
#pragma unroll
                for (int e = 0; e < 4; e++) bad |= (w[e][0] ^ tag) | (w[e][1] ^ tag) | (w[e][2] ^ tag) | (w[e][3] ^ tag);
            } while (__any_sync(~0u, bad & 0xffffu) && ++gd < SPIN_LIMIT);
            if (spare) { if (at == 0) { mbar_arrive(BAR(B_RDY)); } return; }
#pragma unroll
            for (int e = 0; e < 4; e++) {
                const int v = min(at + e * 96, 319), isc = v >= 160, k4 = v - isc * 160;
                const uint32_t a = sm + OFF_TAB + (k4 >> 2) * 64 + (k4 & 1) * 32 + (k4 & 2) * 2 + (isc ? 0 : 8);
                sts1(a, __byte_perm(w[e][0], w[e][1], 0x7632)); sts1(a + 16, __byte_perm(w[e][2], w[e][3], 0x7632));
            }
        }
        STAMPT(2, 288);
        __syncwarp();
        asm volatile("bar.arrive 1, 352;" ::: "memory");
        {
            uint4* po = &g_o[(ti * 64 + j) * 160 + at];
#pragma unroll 1
            for (int w = 0; w < 8; w++) {
                stg4_rlx(po, SENT, SENT, SENT, SENT);
                stg4_rlx(at < 64 ? po + 96 : (at < 84 ? &g_cand[((ti * 8 + w) * 8 + j) * 24 + at - 64] : &g_halo[role * 160 + w * 12 + at - 84]), SENT, SENT, SENT, SENT);
                po += 1280;
            }
            stg4_rlx(at < 64 ? &g_halo[role * 160 + 96 + at] : &g_stats[((ti * 8 + 6 + ((at >> 4) & 1)) * 8 + j) * 16 + (at & 15)], SENT, SENT, SENT, SENT);
            stg4_rlx(&g_stats[((ti * 8 + (at >> 4)) * 8 + j) * 16 + (at & 15)], SENT, SENT, SENT, SENT);
            if (at < 16) stg2_rlx(at < 8 ? &g_rec[at * 128 + role] : &g_a[role * 8 + at - 8], SENT, SENT);
        }
        bar_sync(3, 96);
        if (warp == 9) {
            if (lane == 0) { asm volatile("fence.acq_rel.gpu;" ::: "memory"); stg1_rlx(&g_ready[role], epoch); }
            uint32_t w[4];
            do { __nanosleep(400); ldg4_rlx(w, &g_ready[lane * 4]); } while (__any_sync(~0u, w[0] != epoch || w[1] != epoch || w[2] != epoch || w[3] != epoch) && ++gd < SPIN_LIMIT);
            asm volatile("fence.acq_rel.gpu;" ::: "memory");
            __syncwarp();
            if (lane == 0) mbar_arrive(BAR(B_RDY));
        }
        mbar_wait(BAR(B_L16), 0);
        if (warp == 9) {
            uint32_t h[5][4];
            if ((ti & 7) == 0) {
#pragma unroll
                for (int s = 0; s < 20; s++) h[s >> 2][s & 3] = 0;
            } else {
                do {
#pragma unroll
                    for (int s = 0; s < 5; s++) ldg4_rlx(h[s], &g_halo[(role - 8) * 160 + s * 32 + lane]);
                } while (__any_sync(~0u, max(max(max(h[0][0], h[1][0]), max(h[2][0], h[3][0])), h[4][0]) == SENT) && ++gd < SPIN_LIMIT);
            }
            sts4(sm + OFF_KH + lane * 16, h[0]); sts4(sm + OFF_KH + 512 + lane * 16, h[1]); sts2(sm + OFF_KH + 1024 + lane * 8, h[2][0], h[2][1]);
            const uint32_t va = sm + OFF_V + (lane & 7) * VP + (lane >> 3) * 16;
            stsm4(va, h[3]); stsm4(va + 64, h[4]); stsm2(va + 128, h[2][2], h[2][3]);
            __syncwarp();
            if (lane == 0) mbar_arrive(BAR(B_HL));
        }
        STAMPT(19, 288);
        {
            uint32_t own[4], us[2], bad;
            const int kg = at < 80 ? 80 * j + at : max(role - 88, 0) * 16 + at - 80;
            const float wo_ = __bfloat162float(wr[kg]);
            while (true) {
                ldg2_rlx(us, &g_us[lane & 15]);
                bad = us[1] ^ tag;
#pragma unroll
                for (int e = 0; e < 4; e++) { own[e] = ldg1_rlx(&g_mod[1280 + e * 640 + kg]); bad |= own[e] ^ tag; }
                if (!__any_sync(~0u, bad & 0xffffu) || ++gd > SPIN_LIMIT) break;
                __nanosleep(200);
            }
            if (role == 0 && at == 0) stg1_rlx(&g_epoch, epoch);
            if (at < 80) {
                const int p = odd ? (at < 16 ? at + 64 : at - 16) : at;
                const uint32_t a = sm + OFF_EP + ((p >> 1) & 3) * 48 + (p >> 3) * 4 + (p & 1) * 2;
                const float u = bhi(own[2]) * wo_, uh = rbf(u);
                sts16(a, own[0] >> 16); sts16(a + 192, own[2] >> 16); sts16(a + 384, own[1] >> 16); sts16(a + 576, own[3] >> 16);
                sts16(a + 768, 0x3f80u); sts16(a + 960, __float_as_uint(uh) >> 16); sts16(a + 1152, pack2(u - uh, 0.f));
            } else sts16(sm + OFF_EP + EP_GD + (at - 80) * 2, own[3] >> 16);
            float t = __uint_as_float(us[0]);
#pragma unroll
            for (int o = 1; o < 8; o <<= 1) t += __shfl_xor_sync(~0u, t, o);
            if (at == 0 || at == 8) sts1f(sm + OFF_EP + EP_US + (at >> 1), t);
            __syncwarp();
            if (lane == 0) mbar_arrive(BAR(B_EP));
            STAMPT(20, 288);
        }
    } else {
        asm volatile("setmaxnreg.inc.sync.aligned.u32 200;");
        asm volatile("barrier.cluster.wait.aligned;" ::: "memory");
        bar_sync(0, 352);
        if (spare) {
            float d[5][4] = {};
            uint32_t off[5];
#pragma unroll
            for (int i = 0; i < 5; i++) { const int c = warp * 5 + i; off[i] = sm + (c >> 2) * 4096 + frow * 128 + ((((c & 3) * 2 + fh) ^ (lane & 7)) << 4); }
#pragma unroll 1
            for (int it = 0; it < 20; it++) {
                const int s = it % 5;
                mbar_wait(BAR(B_XF + s), (it / 5) & 1);
#pragma unroll
                for (int h = 0; h < 2; h++) {
                    uint32_t b[2];
                    lds2(b, sm + OFF_S + (it * 2 + h) * 32 + q * 8);
#pragma unroll
                    for (int i = 0; i < 5; i++) { uint32_t a[4]; ldsm4t(a, off[i] + s * 40960 + h * 2048); mma16(d[i], a[0], a[1], a[2], a[3], b[0], b[1]); }
                }
                __syncwarp();
                if (lane == 0) mbar_arrive(BAR(B_WE + s));
            }
            float dot = 0.f;
#pragma unroll
            for (int i = 0; i < 5; i++) {
                const int c = warp * 80 + i * 16 + (q & 1) * 8 + g;
                float t = rbf((q & 1) ? d[i][2] : d[i][0]);
                if (role == 130) t = rbf(1.f + t);
                if (q < 2) { stg1_rlx(&g_mod[1280 + (role - 128) * 640 + c], __float_as_uint(t) | tag); dot = fmaf(t, __bfloat162float(wr[c]), dot); }
            }
#pragma unroll
            for (int o = 16; o; o >>= 1) dot += __shfl_xor_sync(~0u, dot, o);
            if (lane == 0 && (role == 129 || role == 130)) stg2_rlx(&g_us[(role - 129) * 8 + warp], __float_as_uint(dot), tag);
            STAMP(17);
            return;
        }
        const int tw = ti * 8 + warp;
        uint4* const my_o = &g_o[tw * 8 * 160 + lane];
        const uint32_t pair = (uint32_t)(lane & 1) << 24;
        if (role < 80) {
            uint32_t a[5][4], b[5][2];
#pragma unroll
            for (int s = 0; s < 5; s++) lds2(b[s], sm + OFF_S + (warp * 5 + s) * 32 + q * 8);
            mbar_wait(BAR(B_WM), 0);
            STAMP(27);
#pragma unroll
            for (int s = 0; s < 5; s++) ldsm4t(a[s], sm + OFF_WM + (warp * 5 + s) * 512 + frag);
            float d[2][4] = {};
#pragma unroll
            for (int s = 0; s < 5; s++) mma16(d[s & 1], a[s][0], a[s][1], a[s][2], a[s][3], b[s][0], b[s][1]);
            if (q < 2) sts1f(sm + OFF_RED + (warp * 16 + q * 8 + g) * 4, q ? d[0][2] + d[1][2] : d[0][0] + d[1][0]);
            bar_sync(2, 256);
            if (tid < 16) {
                float t = 0.f;
#pragma unroll
                for (int w = 0; w < 8; w++) t += lds1f(sm + OFF_RED + (w * 16 + tid) * 4);
                t = rbf(t);
                if (role >= 40) t = rbf(1.f + t);
                stg1_rlx(&g_mod[role * 16 + tid], __float_as_uint(t) | tag);
            }
        }
        if (lane < 2) mbar_arrive_cl(pair + BAR0(B_WMF));
        STAMP(0);
        const uint32_t hi = lane >> 4, xa = sm + (warp * 16 + (lane & 15)) * 128 + ((hi ^ (lane & 7)) << 4);
        uint32_t rr0, rr1, nn0, nn1;
        {
            float gA[2][4] = {}, gB[2][4] = {};
            const uint32_t xb = sm + (warp * 16 + frow) * 128 + ((fh ^ (lane & 7)) << 4), one = 0x3f803f80u;
#pragma unroll 1
            for (int c = 0; c < 10; c++) {
                mbar_wait(BAR(B_XF + c), 0);
                uint32_t a[4][4];
#pragma unroll
                for (int k = 0; k < 4; k++) ldsm4(a[k], (xb ^ (k * 32)) + c * 16384);
#pragma unroll
                for (int k = 0; k < 4; k++) {
                    mma16(gA[k & 1], a[k][0], one, a[k][1], one, a[k][0], a[k][1]);
                    mma16(gB[k & 1], a[k][2], one, a[k][3], one, a[k][2], a[k][3]);
                }
            }
            const int src = (lane & ~3) | (g >> 1), e = g & 1;
            const float ss0 = __shfl_sync(~0u, e ? gA[0][1] + gA[1][1] : gA[0][0] + gA[1][0], src), ss1 = __shfl_sync(~0u, e ? gB[0][1] + gB[1][1] : gB[0][0] + gB[1][0], src);
            const float m0 = __shfl_sync(~0u, e ? gA[0][3] + gA[1][3] : gA[0][2] + gA[1][2], src) * (1.f / 640), m1 = __shfl_sync(~0u, e ? gB[0][3] + gB[1][3] : gB[0][2] + gB[1][2], src) * (1.f / 640);
            const float r0 = rbf(rsqrtf(fmaxf(ss0 * (1.f / 640) - m0 * m0, 0.f) + 1e-5f)), r1 = rbf(rsqrtf(fmaxf(ss1 * (1.f / 640) - m1 * m1, 0.f) + 1e-5f));
            rr0 = pack2(r0, r0); rr1 = pack2(r1, r1); nn0 = pack2(-m0 * r0, -m0 * r0); nn1 = pack2(-m1 * r1, -m1 * r1);
        }
        uint32_t xr[5][4];
#pragma unroll
        for (int s = 0; s < 5; s++) {
            const int ks = 5 * j + (odd ? (s == 4 ? 0 : s + 1) : s);
            ldsm4(xr[s], (xa ^ ((ks & 3) * 32)) + (ks >> 2) * 16384);
        }
        STAMP(1);
        bar_sync(1, 352);
        float acc[120];
#pragma unroll
        for (int i = 0; i < 120; i++) acc[i] = 0.f;
        {
            uint32_t a[2][2][4], raw[2][4], tt[2][4];
            uint32_t tb = sm + OFF_TAB + q * 16, xp = xa;
            auto load = [&](int u) {
                ldsm4(raw[0], xp ^ (u * 64)); ldsm4(raw[1], xp ^ (u * 64 + 32));
                lds4(tt[0], tb + u * 128); lds4(tt[1], tb + u * 128 + 64);
            };
            auto xform = [&](uint32_t (*dst)[4]) {
#pragma unroll
                for (int h = 0; h < 2; h++) {
                    dst[h][0] = hf2(hf2(raw[h][0], rr0, nn0), tt[h][0], tt[h][2]); dst[h][1] = hf2(hf2(raw[h][1], rr1, nn1), tt[h][0], tt[h][2]);
                    dst[h][2] = hf2(hf2(raw[h][2], rr0, nn0), tt[h][1], tt[h][3]); dst[h][3] = hf2(hf2(raw[h][3], rr1, nn1), tt[h][1], tt[h][3]);
                }
            };
            const uint64_t dm0 = mkdesc(SM0 + OFF_W, 1024, 512, 2), dt0 = mkdesc(SM0 + OFF_W + 6144, 512, 256, 3);
            load(0); xform(a[0]);
            STAMP(3);
#pragma unroll 1
            for (int i2 = 0; i2 < 10; i2++) {
#pragma unroll
                for (int u = 0; u < 2; u++) {
                    const int st = (i2 & 1) * 2 + u;
                    mbar_wait(BAR(B_WF + st), (i2 >> 1) & 1);
                    wg_fence();
#pragma unroll
                    for (int h = 0; h < 2; h++) { wgmma_rs_n192(acc, a[u][h], dm0 + st * (WST / 16) + h * 480); wgmma_rs_n48(acc + 96, a[u][h], dt0 + st * (WST / 16) + h * 480); }
                    wg_commit();
                    if (u == 1) { xp += 16384; tb += 256; }
                    load(u ^ 1);
                    wg_wait<1>();
                    if (lane < 2 && (u == 1 ? i2 < 8 : (i2 > 0 && i2 < 9))) mbar_arrive_cl(pair + BAR0(B_WE + ((st + 3) & 3)));
                    if (u == 1 && i2 == 8 && lane == 0) mbar_arrive(BAR(B_L16));
                    xform(a[u ^ 1]);
                }
            }
            wg_wait<0>();
            if (lane == 0) mbar_arrive(BAR(B_G0));
        }
        STAMP(4);
        uint32_t ab[4][5][4];
        {
            uint32_t Q[10][2], K[2][10], V[2][10];
            if (!odd) {
#pragma unroll
                for (int t = 0; t < 10; t++) {
                    const int iq = t < 8 ? t * 4 : 96 + (t - 8) * 4, ik = t < 8 ? 32 + t * 4 : 104 + (t - 8) * 4, iv = t < 8 ? 64 + t * 4 : 112 + (t - 8) * 4;
                    K[1][t] = pack2(acc[ik + 2], acc[ik + 3]); V[0][t] = pack2(acc[iv], acc[iv + 1]); V[1][t] = pack2(acc[iv + 2], acc[iv + 3]);
                    K[0][t] = pack2(acc[ik], acc[ik + 1]); Q[t][0] = pack2(acc[iq], acc[iq + 1]); Q[t][1] = pack2(acc[iq + 2], acc[iq + 3]);
                }
            } else {
#pragma unroll
                for (int t = 0; t < 10; t++) {
                    const int iq = t >= 2 ? (t - 2) * 4 : 96 + t * 4, ik = t >= 2 ? 32 + (t - 2) * 4 : 104 + t * 4, iv = t >= 2 ? 64 + (t - 2) * 4 : 112 + t * 4;
                    K[1][t] = pack2(acc[ik + 2], acc[ik + 3]); V[0][t] = pack2(acc[iv], acc[iv + 1]); V[1][t] = pack2(acc[iv + 2], acc[iv + 3]);
                    K[0][t] = pack2(acc[ik], acc[ik + 1]); Q[t][0] = pack2(acc[iq], acc[iq + 1]); Q[t][1] = pack2(acc[iq + 2], acc[iq + 3]);
                }
            }
            mbar_wait(BAR(B_RDY), 0);
            if (warp == 7) {
                uint4* hp = &g_halo[role * 160 + lane];
                stg4_rlx(hp, K[1][0], K[1][1], K[1][3], K[1][4]); stg4_rlx(hp + 32, K[1][5], K[1][6], K[1][8], K[1][9]); stg4_rlx(hp + 64, K[1][2], K[1][7], V[1][8], V[1][9]);
                stg4_rlx(hp + 96, V[1][0], V[1][1], V[1][2], V[1][3]); stg4_rlx(hp + 128, V[1][4], V[1][5], V[1][6], V[1][7]);
            }
            mbar_wait(BAR(B_L16), 0);
            const uint32_t kh = sm + OFF_KH + warp * 1280, vr = sm + OFF_V + (warp * 16 + (lane & 7)) * VP;
            {
                const uint32_t k0[4] = {K[1][0], K[1][1], K[1][3], K[1][4]}, k1[4] = {K[1][5], K[1][6], K[1][8], K[1][9]};
                sts4(kh + 1280 + lane * 16, k0); sts4(kh + 1792 + lane * 16, k1); sts2(kh + 2304 + lane * 8, K[1][2], K[1][7]);
                const uint32_t va = vr + (lane >> 3) * 16, vl[4] = {V[0][8], V[0][9], V[1][8], V[1][9]};
                stsm4(va + 16 * VP, V[1]); stsm4(va + 16 * VP + 64, V[1] + 4); stsm4(vr + (8 + hi * 8) * VP + 128 + ((lane >> 3) & 1) * 16, vl);
                stsm4(va + 8 * VP, V[0]); stsm4(va + 8 * VP + 64, V[0] + 4);
            }
            __syncwarp();
            if (lane == 0 && warp < 7) mbar_arrive(BAR(B_HL + 1 + warp));
            uint32_t VT[5][4], VH[10], KH[10];
#pragma unroll
            for (int s = 0; s < 5; s++) ldsm4t(VT[s], vr + (8 + ((lane >> 3) & 1) * 8) * VP + s * 32 + hi * 16);
            float sb[4][4], sc[4][4], sa[4][4];
            uint32_t qs[4][2];
#pragma unroll
            for (int h = 0; h < 4; h++) {
                const int ts = (h >> 1) * 5 + 2, ta = (h >> 1) * 5 + (h & 1) * 3;
                const bool mine = (q >> 1) == (h & 1);
                qs[h][0] = mine ? Q[ts][0] : 0u; qs[h][1] = mine ? Q[ts][1] : 0u;
                mma16c(sb[h], Q[ta][0], Q[ta][1], Q[ta + 1][0], Q[ta + 1][1], K[0][ta], K[0][ta + 1], 0.f, 0.f);
                mma16c(sc[h], Q[ta][0], Q[ta][1], Q[ta + 1][0], Q[ta + 1][1], K[1][ta], K[1][ta + 1], 0.f, 0.f);
                mma8(sb[h], qs[h][0], qs[h][1], K[0][ts]);
                mma8(sc[h], qs[h][0], qs[h][1], K[1][ts]);
            }
            mbar_wait(BAR(B_HL + warp), 0);
            lds4(KH, kh + lane * 16); lds4(KH + 4, kh + 512 + lane * 16); lds2(KH + 8, kh + 1024 + lane * 8);
            ldsm4t(VH, vr + (lane >> 3) * 16); ldsm4t(VH + 4, vr + 64 + (lane >> 3) * 16); ldsm2t(VH + 8, vr + 128 + ((lane >> 3) & 1) * 16);
            STAMP(5);
            const float ninf = (tw & 63) == 0 ? -INFINITY : 0.f;
#pragma unroll
            for (int h = 0; h < 4; h++) {
                const int ta = (h >> 1) * 5 + (h & 1) * 3;
                mma16c(sa[h], Q[ta][0], Q[ta][1], Q[ta + 1][0], Q[ta + 1][1], KH[2 * h], KH[2 * h + 1], ninf, ninf);
                mma8(sa[h], qs[h][0], qs[h][1], KH[8 + (h >> 1)]);
            }
            const bool gt0 = 2 * q > g, gt1 = 2 * q + 1 > g;
            const uint32_t mgt = (gt0 ? 0xffffu : 0u) | (gt1 ? 0xffff0000u : 0u);
            const float cs = 0.22360679774997896f * 1.4426950408889634f;
            uint32_t of[12][2];
#pragma unroll
            for (int h = 0; h < 4; h++) {
                const int ts = (h >> 1) * 5 + 2, ta = (h >> 1) * 5 + (h & 1) * 3;
                float t0 = gt0 ? sa[h][0] : sb[h][0], t1 = gt1 ? sa[h][1] : sb[h][1];
                float b0 = gt0 ? sb[h][2] : sc[h][2], b1 = gt1 ? sb[h][3] : sc[h][3];
                float mt_ = fmaxf(t0, t1), mb = fmaxf(b0, b1);
                mt_ = fmaxf(mt_, __shfl_xor_sync(~0u, mt_, 1)); mb = fmaxf(mb, __shfl_xor_sync(~0u, mb, 1));
                mt_ = fmaxf(mt_, __shfl_xor_sync(~0u, mt_, 2)); mb = fmaxf(mb, __shfl_xor_sync(~0u, mb, 2));
                t0 = ex2((t0 - mt_) * cs); t1 = ex2((t1 - mt_) * cs); b0 = ex2((b0 - mb) * cs); b1 = ex2((b1 - mb) * cs);
                float lt = t0 + t1, lb = b0 + b1;
                lt += __shfl_xor_sync(~0u, lt, 1); lb += __shfl_xor_sync(~0u, lb, 1);
                lt += __shfl_xor_sync(~0u, lt, 2); lb += __shfl_xor_sync(~0u, lb, 2);
                lt = rcp(lt); lb = rcp(lb);
                const uint32_t pt = pack2(t0 * lt, t1 * lt), pb = pack2(b0 * lb, b1 * lb);
                const uint32_t pA = pt & mgt, pBt = pt & ~mgt, pBb = pb & mgt, pC = pb & ~mgt;
#pragma unroll
                for (int e = 0; e < 3; e++) {
                    const int t = e == 2 ? ts : ta + e;
                    float d[4];
                    mma16c(d, pBt, pBb, 0u, pC, VT[t >> 1][(t & 1) * 2], VT[t >> 1][(t & 1) * 2 + 1], 0.f, 0.f);
                    mma8(d, pA, 0u, VH[t]);
                    of[h * 3 + e][0] = pack2(d[0], d[1]); of[h * 3 + e][1] = pack2(d[2], d[3]);
                }
            }
#pragma unroll
            for (int t = 0; t < 10; t++) {
                const int p = t / 5, r = t % 5;
#pragma unroll
                for (int e = 0; e < 2; e++) ab[0][t >> 1][(t & 1) * 2 + e] = r == 2 ? ((q & 2) ? of[p * 6 + 5][e] : of[p * 6 + 2][e]) : of[p * 6 + r][e];
            }
#pragma unroll
            for (int s = 0; s < 5; s++) stg4_rlx(my_o + j * 160 + s * 32, ab[0][s][0], ab[0][s][1], ab[0][s][2], ab[0][s][3]);
        }
        STAMP(6);
        float ac2[40];
#pragma unroll
        for (int i = 0; i < 40; i++) ac2[i] = 0.f;
        {
            const uint64_t d0 = mkdesc(SM0, 5120, 512, 2);
            auto ldsrc = [&](int w, uint32_t (*dst)[4]) {
                const uint4* p = my_o + (w <= j ? w - 1 : w) * 160;
#pragma unroll
                for (int s = 0; s < 5; s++) ldg4_rlx(dst[s], p + s * 32);
            };
#pragma unroll 1
            for (int w4 = 0; w4 < 8; w4 += 4) {
#pragma unroll
                for (int u = 0; u < 4; u++) {
                    const int w = w4 + u;
                    int gd = 0;
                    while (__any_sync(~0u, max(max(max(ab[u][0][0], ab[u][1][0]), max(ab[u][2][0], ab[u][3][0])), ab[u][4][0]) == SENT) && ++gd < SPIN_LIMIT) ldsrc(w, ab[u]);
                    mbar_wait(BAR(B_WO + w), 0);
                    wg_fence();
#pragma unroll
                    for (int s = 0; s < 5; s++) wgmma_rs_n80(ac2, ab[u][s], d0 + w * (WST / 16) + s * 64);
                    wg_commit();
                    if (u == 0 && w4 == 0) { ldsrc(1, ab[1]); ldsrc(2, ab[2]); }
                    if (w < 5) { wg_wait<1>(); ldsrc(w + 3, ab[(u + 3) & 3]); }
                    if (u == 0 && w4 == 4 && lane == 0) mbar_arrive(BAR(B_G2));
                }
            }
        }
        mbar_wait(BAR(B_EP), 0);
        uint32_t tga[12], tst[12];
        const uint32_t ep = sm + OFF_EP + q * 48;
#pragma unroll
        for (int s = 0; s < 3; s++) { lds4(tga + 4 * s, ep + s * 16); lds4(tst + 4 * s, ep + 768 + min(g, 2) * 192 + s * 16); }
        wg_wait<0>();
        STAMP(8);
        {
            float gA[4] = {}, gB[4] = {}, sd[4] = {};
#pragma unroll
            for (int s = 0; s < 5; s++) {
#pragma unroll
                for (int e = 0; e < 4; e++) xr[s][e] = hf2(tga[2 * s + (e >> 1)], pack2(ac2[s * 8 + e * 2], ac2[s * 8 + e * 2 + 1]), xr[s][e]);
                mma16(gA, xr[s][0], xr[s][1], xr[s][2], xr[s][3], xr[s][0], xr[s][2]);
                mma16(gB, xr[s][0], xr[s][1], xr[s][2], xr[s][3], xr[s][1], xr[s][3]);
                mma16(sd, xr[s][0], xr[s][1], xr[s][2], xr[s][3], tst[2 * s], tst[2 * s + 1]);
            }
            const float q0 = __shfl_sync(~0u, (g & 1) ? gA[1] : gA[0], (lane & ~3) | (g >> 1)), q1 = __shfl_sync(~0u, (g & 1) ? gB[3] : gB[2], (lane & ~3) | (g >> 1));
            const float l0 = __shfl_down_sync(~0u, sd[0], 1), l1 = __shfl_down_sync(~0u, sd[2], 1);
            if (q == 0) {
                uint4* sp = &g_stats[(tw * 8 + j) * 16 + g];
                stg4_rlx(sp, __float_as_uint(sd[0]), __float_as_uint(q0), __float_as_uint(sd[1] + l0), 0u);
                stg4_rlx(sp + 8, __float_as_uint(sd[2]), __float_as_uint(q1), __float_as_uint(sd[3] + l1), 0u);
            }
        }
        STAMP(9);
        uint32_t fg[5][4], fu[5][4], tcb[12], tsb[12];
        if (role < 108) {
            mbar_wait(BAR(B_FG), 0);
#pragma unroll
            for (int s = 0; s < 5; s++) {
                const uint32_t off = sm + OFF_WG + (5 * warp + ((warp & 1) ? (s == 4 ? 0 : s + 1) : s)) * 1024 + frow * 64 + ((fh ^ ((lane >> 1) & 3)) << 4);
                ldsm4t(fg[s], off); ldsm4t(fu[s], off ^ 32);
            }
        }
#pragma unroll
        for (int s = 0; s < 3; s++) { lds4(tcb + 4 * s, ep + 192 + s * 16); lds4(tsb + 4 * s, ep + 384 + s * 16); lds4(tga + 4 * s, ep + 576 + s * 16); }
        float r0, r1;
        {
            const float2 su = lds2f(sm + OFF_EP + EP_US);
            const float S = su.x, U = su.y;
            uint32_t st[4][4]; int gd = 0;
            const uint4* sp = &g_stats[(tw * 8 + 2 * q) * 16 + g];
            do {
                ldg4_rlx(st[0], sp); ldg4_rlx(st[1], sp + 16); ldg4_rlx(st[2], sp + 8); ldg4_rlx(st[3], sp + 24);
            } while (__any_sync(~0u, (st[0][3] | st[1][3] | st[2][3] | st[3][3]) != 0) && ++gd < SPIN_LIMIT);
            STAMP(10);
            float v[6];
#pragma unroll
            for (int e = 0; e < 3; e++) { v[e] = __uint_as_float(st[0][e]) + __uint_as_float(st[1][e]); v[3 + e] = __uint_as_float(st[2][e]) + __uint_as_float(st[3][e]); }
#pragma unroll
            for (int e = 0; e < 6; e++) { v[e] += __shfl_xor_sync(~0u, v[e], 1); v[e] += __shfl_xor_sync(~0u, v[e], 2); }
            const float m0 = v[0] * (1.f / 640), m1 = v[3] * (1.f / 640);
            float s0 = rsqrtf(fmaxf(v[1] * (1.f / 640) - m0 * m0, 0.f) + 1e-5f), s1 = rsqrtf(fmaxf(v[4] * (1.f / 640) - m1 * m1, 0.f) + 1e-5f);
            r0 = fmaf(s0, v[2] - m0 * U, S); r1 = fmaf(s1, v[5] - m1 * U, S);
            s0 = rbf(s0); s1 = rbf(s1);
            rr0 = pack2(s0, s0); rr1 = pack2(s1, s1); nn0 = pack2(-m0 * s0, -m0 * s0); nn1 = pack2(-m1 * s1, -m1 * s1);
        }
        const uint32_t k0 = fkey(r0), k1 = fkey(r1);
        const uint32_t kmax = __reduce_max_sync(~0u, max(k0, k1));
        const int crow = __reduce_min_sync(~0u, k0 == kmax ? g : (k1 == kmax ? g + 8 : 99));
        const int tok_base = ((ti & 7) * 128 + warp * 16) * 2 + (ti >> 3);
        if (warp == j && lane < 8) stg2_rlx(&g_rec[lane * 128 + tw], kmax, tok_base + 2 * crow);
        {
            const bool up = crow >= 8;
            const uint32_t rr = up ? rr1 : rr0, nn = up ? nn1 : nn0;
            if (g == (crow & 7)) {
                uint4* cp = &g_cand[(tw * 8 + j) * 24 + q];
#pragma unroll
                for (int s = 0; s < 5; s++) {
                    const uint32_t xa_ = up ? xr[s][1] : xr[s][0], xb_ = up ? xr[s][3] : xr[s][2];
                    stg4_rlx(cp + s * 4, hf2(hf2(xa_, rr, nn), tcb[2 * s], tsb[2 * s]), hf2(hf2(xb_, rr, nn), tcb[2 * s + 1], tsb[2 * s + 1]), xa_, xb_);
                }
            }
        }
        STAMP(11);
        int win, tokwin, gd = 0; uint32_t kwin;
        {
            uint32_t rc[2][4];
            do {
                ldg4_rlx(rc[0], &g_rec[grp * 128 + lane * 4]); ldg4_rlx(rc[1], &g_rec[grp * 128 + lane * 4 + 2]);
            } while (__any_sync(~0u, (rc[0][1] | rc[0][3] | rc[1][1] | rc[1][3]) == SENT) && ++gd < SPIN_LIMIT);
            kwin = __reduce_max_sync(~0u, max(max(rc[0][0], rc[0][2]), max(rc[1][0], rc[1][2])));
            tokwin = __reduce_min_sync(~0u, min(min(rc[0][0] == kwin ? rc[0][1] : 4096u, rc[0][2] == kwin ? rc[0][3] : 4096u), min(rc[1][0] == kwin ? rc[1][1] : 4096u, rc[1][2] == kwin ? rc[1][3] : 4096u)));
            win = (tokwin & 1) * 64 + (tokwin >> 5);
        }
        STAMP(13);
        if (role < 108) {
            uint32_t hb[5][2];
            const uint4* cp = &g_cand[(win * 8 + warp) * 24 + q];
            do {
#pragma unroll
                for (int s = 0; s < 5; s++) ldg2_rlx(hb[s], cp + s * 4);
            } while (__any_sync(~0u, max(max(max(hb[0][0], hb[1][0]), max(hb[2][0], hb[3][0])), hb[4][0]) == SENT) && ++gd < SPIN_LIMIT);
            float dg[2][4] = {}, du[2][4] = {};
#pragma unroll
            for (int s = 0; s < 5; s++) {
                mma16(dg[s & 1], fg[s][0], fg[s][1], fg[s][2], fg[s][3], hb[s][0], hb[s][1]);
                mma16(du[s & 1], fu[s][0], fu[s][1], fu[s][2], fu[s][3], hb[s][0], hb[s][1]);
            }
            const float mine = q == 0 ? dg[0][0] + dg[1][0] : q == 1 ? dg[0][2] + dg[1][2] : q == 2 ? du[0][0] + du[1][0] : du[0][2] + du[1][2];
            sts1f(sm + OFF_RED + (warp * 32 + q * 8 + g) * 4, mine);
            bar_sync(2, 256);
            if (warp == 0) {
                float t = 0.f;
#pragma unroll
                for (int w = 0; w < 8; w++) t += lds1f(sm + OFF_RED + (w * 32 + lane) * 4);
                t = rbf(t);
                if (!(role & 1)) t *= sigm(t);
                const uint32_t pr = pack2(t, __shfl_down_sync(~0u, t, 1)), p8 = __shfl_down_sync(~0u, pr, 8);
                if (!(lane & 9)) stg2_rlx(&g_a[((role & ~1) + (lane >> 4)) * 8 + (lane & 6) + (role & 1)], pr, p8);
            }
        }
        STAMP(14);
        {
#pragma unroll
            for (int s = 0; s < 5; s++) {
#pragma unroll
                for (int e = 0; e < 4; e++) { const int t = 2 * s + (e >> 1); xr[s][e] = hf2(tga[t], hf2(hf2(xr[s][e], (e & 1) ? rr1 : rr0, (e & 1) ? nn1 : nn0), tcb[t], tsb[t]), xr[s][e]); }
            }
            mbar_wait(BAR(B_G2), 0);
            const uint32_t stg = sm + warp * 2816;
#pragma unroll
            for (int s = 0; s < 5; s++) stsm4(stg + (lane & 15) * VP + (odd ? (s == 4 ? 0 : s + 1) : s) * 32 + hi * 16, xr[s]);
            __syncwarp();
            const int tok = tok_base + (lane >> 1) * 2;
            __nv_bfloat16* const op = out + (size_t)tok * 640 + 80 * j + (lane & 1) * 8;
#pragma unroll
            for (int s = 0; s < 5; s++) lds4(xr[s], stg + (lane >> 1) * VP + (lane & 1) * 16 + s * 32);
            if (tok != tokwin) {
#pragma unroll
                for (int s = 0; s < 5; s++) *(uint4*)(op + s * 16) = make_uint4(xr[s][0], xr[s][1], xr[s][2], xr[s][3]);
            }
        }
        STAMP(12);
        if (role >= 88) {
            const int d = role - 88, dj = d / 5, dm = d - dj * 5, sp = (dj & 1) ? (dm == 0 ? 4 : dm - 1) : dm;
            const int ks0 = min(warp * 14, 94);
            uint32_t fd[14][4];
            mbar_wait(BAR(B_FD), 0);
#pragma unroll
            for (int s = 0; s < 14; s++) ldsm4t(fd[s], sm + OFF_WD + (ks0 + s) * 512 + frag);
            uint32_t bsv[4], av[14][4], m;
            do {
                ldg4_rlx(bsv, &g_cand[(win * 8 + dj) * 24 + sp * 4 + q]);
#pragma unroll
                for (int s = 0; s < 14; s++) ldg4_rlx(av[s], &g_a[(ks0 + s) * 8 + q * 2]);
                m = bsv[0];
#pragma unroll
                for (int s = 0; s < 14; s++) m = max(m, max(av[s][0], av[s][2]));
            } while (__any_sync(~0u, m == SENT) && ++gd < SPIN_LIMIT);
            STAMP(15);
            float dy[4][4] = {};
#pragma unroll
            for (int s = 0; s < 14; s++) {
                if (s < 4 && warp == 7) av[s][0] = av[s][1] = av[s][2] = av[s][3] = 0u;
                mma16(dy[s & 3], fd[s][0], fd[s][1], fd[s][2], fd[s][3], hm2(av[s][0], av[s][2]), hm2(av[s][1], av[s][3]));
            }
            if (q < 2) sts1f(sm + OFF_TAB + (warp * 16 + q * 8 + g) * 4, q == 0 ? (dy[0][0] + dy[1][0]) + (dy[2][0] + dy[3][0]) : (dy[0][2] + dy[1][2]) + (dy[2][2] + dy[3][2]));
            bar_sync(2, 256);
            if (tid < 8) {
                float y0 = 0.f, y1 = 0.f;
#pragma unroll
                for (int w = 0; w < 8; w++) { const float2 v = lds2f(sm + OFF_TAB + w * 64 + tid * 8); y0 += v.x; y1 += v.y; }
                const float sg = rbf(sigm(rbf(__uint_as_float((kwin & 0x80000000u) ? kwin & 0x7fffffffu : ~kwin))));
                const uint32_t hh = tid < 4 ? bsv[0] : bsv[1], xx = tid < 4 ? bsv[2] : bsv[3];
                const uint32_t z = pack2(blo(hh) + rbf(rbf(y0) * sg), bhi(hh) + rbf(rbf(y1) * sg));
                *(uint32_t*)(out + (size_t)tokwin * 640 + d * 16 + tid * 2) = hf2(lds1(sm + OFF_EP + EP_GD + tid * 4), z, xx);
            }
        }
        STAMP(16);
    }
}

typedef CUresult (*EncFn)(CUtensorMap*, CUtensorMapDataType, cuuint32_t, void*, const cuuint64_t*, const cuuint64_t*, const cuuint32_t*, const cuuint32_t*,
                          CUtensorMapInterleave, CUtensorMapSwizzle, CUtensorMapL2promotion, CUtensorMapFloatOOBfill);
static void make_map(EncFn enc, CUtensorMap* m, const void* base, int rank, const cuuint64_t* dims, const cuuint64_t* strides, const cuuint32_t* box, CUtensorMapSwizzle sw) {
    const cuuint32_t es[5] = {1, 1, 1, 1, 1};
    enc(m, CU_TENSOR_MAP_DATA_TYPE_BFLOAT16, rank, (void*)base, dims, strides, box, es, CU_TENSOR_MAP_INTERLEAVE_NONE, sw, CU_TENSOR_MAP_L2_PROMOTION_NONE, CU_TENSOR_MAP_FLOAT_OOB_FILL_NONE);
}

extern "C" void kernel_launch(void* const* d_in, const int* in_sizes, int n_in, void* d_out, int out_size) {
    typedef const __nv_bfloat16* P;
    P x = (P)d_in[0], wqkv = (P)d_in[1], wo = (P)d_in[2], wr = (P)d_in[4], wg = (P)d_in[5], wu = (P)d_in[6], wd = (P)d_in[7], c = (P)d_in[8], wmod = (P)d_in[9];
    void* fn = nullptr; cudaDriverEntryPointQueryResult qr;
    cudaGetDriverEntryPoint("cuTensorMapEncodeTiled", &fn, cudaEnableDefault, &qr);
    EncFn enc = (EncFn)fn;
    CUtensorMap mx, mw, mt, mo, mg, mu, md, mm, mr;
    { cuuint64_t d[] = {640, 2, 1024}, s[] = {1280, 2560}; cuuint32_t b[] = {64, 1, 128}; make_map(enc, &mx, x, 3, d, s, b, CU_TENSOR_MAP_SWIZZLE_128B); }
    { cuuint64_t d[] = {32, 640, 20, 3}, s[] = {3840, 64, 1280}; cuuint32_t b[] = {32, 16, 2, 3}; make_map(enc, &mw, wqkv, 4, d, s, b, CU_TENSOR_MAP_SWIZZLE_64B); }
    { cuuint64_t d[] = {640, 640, 3}, s[] = {3840, 1280}; cuuint32_t b[] = {16, 16, 3}; make_map(enc, &mt, wqkv, 3, d, s, b, CU_TENSOR_MAP_SWIZZLE_32B); }
    { cuuint64_t d[] = {640, 640}, s[] = {1280}; cuuint32_t b[] = {32, 40}; make_map(enc, &mo, wo, 2, d, s, b, CU_TENSOR_MAP_SWIZZLE_64B); }
    { cuuint64_t d[] = {1728, 160, 4}, s[] = {3456, 3456 * 160}; cuuint32_t b[] = {32, 160, 4}; make_map(enc, &mg, wg, 3, d, s, b, CU_TENSOR_MAP_SWIZZLE_64B); make_map(enc, &mu, wu, 3, d, s, b, CU_TENSOR_MAP_SWIZZLE_64B); }
    { cuuint64_t d[] = {640, 216, 8}, s[] = {1280, 1280 * 216}; cuuint32_t b[] = {16, 216, 8}; make_map(enc, &md, wd, 3, d, s, b, CU_TENSOR_MAP_SWIZZLE_32B); }
    { cuuint64_t d[] = {3840, 160, 4}, s[] = {7680, 7680 * 160}; cuuint32_t b[] = {16, 160, 4}; make_map(enc, &mm, wmod, 3, d, s, b, CU_TENSOR_MAP_SWIZZLE_32B); }
    { cuuint64_t d[] = {64, 640, 60}, s[] = {7680, 128}; cuuint32_t b[] = {64, 32, 10}; make_map(enc, &mr, wmod, 3, d, s, b, CU_TENSOR_MAP_SWIZZLE_128B); }
    cudaFuncSetAttribute(fused_kernel, cudaFuncAttributeMaxDynamicSharedMemorySize, SMEM_BYTES);
    fused_kernel<<<132, 384, SMEM_BYTES>>>(mm, mx, mw, mt, mo, mg, mu, md, mr, wqkv, wo, wr, wg, wu, wd, c, wmod, (__nv_bfloat16*)d_out);
}
```

```cpp
#include <cuda_runtime.h>
#include <cuda_bf16.h>
#include <cuda.h>
#include <stdint.h>

#define SENT 0xFFFFFFFFu
#define SPIN_LIMIT (1 << 17)

struct __align__(128) Scratch {
    uint4 o[128 * 8 * 160];
    uint4 halo[128 * 160];
    uint4 stats[2048 * 8];
    uint4 cand[128 * 8 * 24];
    uint2 rec[8 * 128];
    uint2 a[128 * 8];
    uint2 tab[2][8][320];
    unsigned mod[2560];
    uint2 us[16];
    unsigned ready[128];
    unsigned epoch;
};
__device__ Scratch g_s;
#define STAMP(n)
#define STAMPT(n, t)

constexpr uint32_t OFF_W = 163840, WST = 15360;
constexpr uint32_t OFF_WM = OFF_W + 2 * WST;
constexpr uint32_t OFF_V = 122880, VP = 176;
constexpr uint32_t OFF_KH = OFF_W;
constexpr uint32_t OFF_WD = 129024, OFF_WG = 184320;
constexpr uint32_t OFF_TAB = 225280;
constexpr uint32_t OFF_S = OFF_TAB + 2560;
constexpr uint32_t OFF_EP = OFF_S + 1280;
constexpr uint32_t EP_GD = 1344, EP_US = 1376;
constexpr uint32_t OFF_RED = OFF_EP + 1408;
constexpr uint32_t OFF_BAR = OFF_RED + 1024;
constexpr uint32_t OFF_PROF = OFF_BAR + 384;
constexpr uint32_t SMEM_BYTES = OFF_PROF + 128;
enum { B_XF = 0, B_WF = 10, B_WO = 14, B_HL = 22, B_FG = 30, B_FD, B_RDY, B_WM, B_WIN, B_EP, B_G0, B_G2, B_G3, B_L16, B_WE, B_WMF = B_WE + 5, B_N };
#define XDELAY 1200
#define RSLEEP 200
#define HALO_GO B_L16
constexpr uint32_t SM0 = 1024;
#define BAR0(i) (SM0 + OFF_BAR + 8 * (i))
#define BAR(i) (sm + OFF_BAR + 8 * (i))

__device__ __forceinline__ uint32_t smem_u32(const void* p) { return (uint32_t)__cvta_generic_to_shared(p); }
__device__ __forceinline__ void mbar_init(uint32_t b, int cnt) { asm volatile("mbarrier.init.shared::cta.b64 [%0], %1;" ::"r"(b), "r"(cnt) : "memory"); }
__device__ __forceinline__ void mbar_expect_tx(uint32_t b, uint32_t bytes) { asm volatile("mbarrier.arrive.expect_tx.shared::cta.b64 _, [%0], %1;" ::"r"(b), "r"(bytes) : "memory"); }
__device__ __forceinline__ void mbar_arrive(uint32_t b) { asm volatile("mbarrier.arrive.shared::cta.b64 _, [%0];" ::"r"(b) : "memory"); }
__device__ __forceinline__ bool mbar_try(uint32_t b, uint32_t par) {
    uint32_t ok;
    asm volatile("{.reg .pred p; mbarrier.try_wait.parity.shared::cta.b64 p, [%1], %2; selp.u32 %0, 1, 0, p;}" : "=r"(ok) : "r"(b), "r"(par) : "memory");
    return ok;
}
__device__ __forceinline__ void mbar_wait(uint32_t b, uint32_t par) {
    asm volatile("{.reg .pred p;\nW: mbarrier.try_wait.parity.shared::cta.b64 p, [%0], %1;\n@!p bra W;}" ::"r"(b), "r"(par) : "memory");
}
__device__ __forceinline__ void bar_sync(int id, int n) { asm volatile("bar.sync %0, %1;" ::"r"(id), "r"(n) : "memory"); }
__device__ __forceinline__ void tma2d(uint32_t dst, const CUtensorMap* m, int c0, int c1, uint32_t bar) {
    asm volatile("cp.async.bulk.tensor.2d.shared::cluster.global.mbarrier::complete_tx::bytes [%0], [%1, {%3, %4}], [%2];" ::"r"(dst), "l"(m), "r"(bar), "r"(c0), "r"(c1) : "memory");
}
__device__ __forceinline__ void tma3d(uint32_t dst, const CUtensorMap* m, int c0, int c1, int c2, uint32_t bar) {
    asm volatile("cp.async.bulk.tensor.3d.shared::cluster.global.mbarrier::complete_tx::bytes [%0], [%1, {%3, %4, %5}], [%2];" ::"r"(dst), "l"(m), "r"(bar), "r"(c0), "r"(c1), "r"(c2) : "memory");
}
__device__ __forceinline__ void tma4d(uint32_t dst, const CUtensorMap* m, int c0, int c1, int c2, int c3, uint32_t bar) {
    asm volatile("cp.async.bulk.tensor.4d.shared::cluster.global.mbarrier::complete_tx::bytes [%0], [%1, {%3, %4, %5, %6}], [%2];" ::"r"(dst), "l"(m), "r"(bar), "r"(c0), "r"(c1), "r"(c2), "r"(c3) : "memory");
}
__device__ __forceinline__ void l2_prefetch(const void* p, uint32_t bytes) { asm volatile("cp.async.bulk.prefetch.L2.global [%0], %1;" ::"l"(p), "r"(bytes) : "memory"); }
__device__ __forceinline__ void pf_map(const CUtensorMap* m) { asm volatile("prefetch.tensormap [%0];" ::"l"(m) : "memory"); }
__device__ __forceinline__ void wg_fence() { asm volatile("wgmma.fence.sync.aligned;" ::: "memory"); }
__device__ __forceinline__ void wg_commit() { asm volatile("wgmma.commit_group.sync.aligned;" ::: "memory"); }
template <int N> __device__ __forceinline__ void wg_wait() { asm volatile("wgmma.wait_group.sync.aligned %0;" ::"n"(N) : "memory"); }
__device__ __forceinline__ void ldsm4(uint32_t* r, uint32_t addr) { asm volatile("ldmatrix.sync.aligned.m8n8.x4.shared.b16 {%0,%1,%2,%3}, [%4];" : "=r"(r[0]), "=r"(r[1]), "=r"(r[2]), "=r"(r[3]) : "r"(addr) : "memory"); }
__device__ __forceinline__ void ldsm4t(uint32_t* r, uint32_t addr) { asm volatile("ldmatrix.sync.aligned.m8n8.x4.trans.shared.b16 {%0,%1,%2,%3}, [%4];" : "=r"(r[0]), "=r"(r[1]), "=r"(r[2]), "=r"(r[3]) : "r"(addr) : "memory"); }
__device__ __forceinline__ void stsm4(uint32_t addr, const uint32_t* r) { asm volatile("stmatrix.sync.aligned.m8n8.x4.shared.b16 [%4], {%0,%1,%2,%3};" ::"r"(r[0]), "r"(r[1]), "r"(r[2]), "r"(r[3]), "r"(addr) : "memory"); }
__device__ __forceinline__ void lds4(uint32_t* r, uint32_t addr) { asm volatile("ld.shared.v4.u32 {%0,%1,%2,%3}, [%4];" : "=r"(r[0]), "=r"(r[1]), "=r"(r[2]), "=r"(r[3]) : "r"(addr) : "memory"); }
__device__ __forceinline__ void sts4(uint32_t addr, const uint32_t* r) { asm volatile("st.shared.v4.u32 [%4], {%0,%1,%2,%3};" ::"r"(r[0]), "r"(r[1]), "r"(r[2]), "r"(r[3]), "r"(addr) : "memory"); }
__device__ __forceinline__ float2 lds2f(uint32_t addr) { float2 v; asm volatile("ld.shared.v2.f32 {%0,%1}, [%2];" : "=f"(v.x), "=f"(v.y) : "r"(addr) : "memory"); return v; }
__device__ __forceinline__ float lds1f(uint32_t addr) { float v; asm volatile("ld.shared.f32 %0, [%1];" : "=f"(v) : "r"(addr) : "memory"); return v; }
__device__ __forceinline__ void sts1f(uint32_t addr, float v) { asm volatile("st.shared.f32 [%0], %1;" ::"r"(addr), "f"(v) : "memory"); }
__device__ __forceinline__ void sts1(uint32_t addr, uint32_t v) { asm volatile("st.shared.u32 [%0], %1;" ::"r"(addr), "r"(v) : "memory"); }
__device__ __forceinline__ void ldg4_rlx(uint32_t* r, const void* p) { asm volatile("{.reg .b128 t; ld.relaxed.gpu.global.b128 t, [%4]; mov.b128 {%0,%1,%2,%3}, t;}" : "=r"(r[0]), "=r"(r[1]), "=r"(r[2]), "=r"(r[3]) : "l"(p) : "memory"); }
__device__ __forceinline__ void ldg2_rlx(uint32_t* r, const void* p) { asm volatile("{.reg .b64 t; ld.relaxed.gpu.global.b64 t, [%2]; mov.b64 {%0,%1}, t;}" : "=r"(r[0]), "=r"(r[1]) : "l"(p) : "memory"); }
__device__ __forceinline__ uint32_t ldg1_rlx(const void* p) { uint32_t v; asm volatile("ld.relaxed.gpu.global.u32 %0, [%1];" : "=r"(v) : "l"(p) : "memory"); return v; }
__device__ __forceinline__ void stg4_rlx(void* p, uint32_t a, uint32_t b, uint32_t c, uint32_t d) { asm volatile("{.reg .b128 t; mov.b128 t, {%1,%2,%3,%4}; st.relaxed.gpu.global.b128 [%0], t;}" ::"l"(p), "r"(a), "r"(b), "r"(c), "r"(d) : "memory"); }
__device__ __forceinline__ void stg2_rlx(void* p, uint32_t a, uint32_t b) { asm volatile("{.reg .b64 t; mov.b64 t, {%1,%2}; st.relaxed.gpu.global.b64 [%0], t;}" ::"l"(p), "r"(a), "r"(b) : "memory"); }
__device__ __forceinline__ void stg1_rlx(void* p, uint32_t a) { asm volatile("st.relaxed.gpu.global.u32 [%0], %1;" ::"l"(p), "r"(a) : "memory"); }
__device__ __forceinline__ void ldg4_nc(uint32_t* r, const void* p) { asm volatile("ld.global.nc.L1::no_allocate.v4.u32 {%0,%1,%2,%3}, [%4];" : "=r"(r[0]), "=r"(r[1]), "=r"(r[2]), "=r"(r[3]) : "l"(p)); }
__device__ __forceinline__ uint64_t mkdesc(uint32_t addr, uint32_t lbo, uint32_t sbo, uint32_t sw) { return (uint64_t)((addr & 0x3FFFF) >> 4) | ((uint64_t)(lbo >> 4) << 16) | ((uint64_t)(sbo >> 4) << 32) | ((uint64_t)sw << 62); }
__device__ __forceinline__ uint32_t pack2(float lo, float hi) { uint32_t r; asm("cvt.rn.bf16x2.f32 %0, %1, %2;" : "=r"(r) : "f"(hi), "f"(lo)); return r; }
__device__ __forceinline__ float blo(uint32_t v) { return __uint_as_float(v << 16); }
__device__ __forceinline__ float bhi(uint32_t v) { return __uint_as_float(v & 0xffff0000u); }
__device__ __forceinline__ float rbf(float x) { return blo(pack2(x, 0.f)); }
__device__ __forceinline__ uint32_t hf2(uint32_t a, uint32_t b, uint32_t c) { uint32_t r; asm("fma.rn.bf16x2 %0, %1, %2, %3;" : "=r"(r) : "r"(a), "r"(b), "r"(c)); return r; }
__device__ __forceinline__ uint32_t movm(uint32_t a) { uint32_t r; asm volatile("movmatrix.sync.aligned.m8n8.trans.b16 %0, %1;" : "=r"(r) : "r"(a)); return r; }
__device__ __forceinline__ float ex2(float x) { float r; asm("ex2.approx.ftz.f32 %0, %1;" : "=f"(r) : "f"(x)); return r; }
__device__ __forceinline__ void mma16(float* d, uint32_t a0, uint32_t a1, uint32_t a2, uint32_t a3, uint32_t b0, uint32_t b1) {
    asm volatile("mma.sync.aligned.m16n8k16.row.col.f32.bf16.bf16.f32 {%0,%1,%2,%3}, {%4,%5,%6,%7}, {%8,%9}, {%0,%1,%2,%3};"
                 : "+f"(d[0]), "+f"(d[1]), "+f"(d[2]), "+f"(d[3]) : "r"(a0), "r"(a1), "r"(a2), "r"(a3), "r"(b0), "r"(b1));
}
__device__ __forceinline__ void mma8(float* d, uint32_t a0, uint32_t a1, uint32_t b0) {
    asm volatile("mma.sync.aligned.m16n8k8.row.col.f32.bf16.bf16.f32 {%0,%1,%2,%3}, {%4,%5}, {%6}, {%0,%1,%2,%3};"
                 : "+f"(d[0]), "+f"(d[1]), "+f"(d[2]), "+f"(d[3]) : "r"(a0), "r"(a1), "r"(b0));
}
__device__ __forceinline__ uint32_t umax4(const uint32_t* v, uint32_t m) { return max(max(max(v[0], v[1]), max(v[2], v[3])), m); }
__device__ __forceinline__ uint32_t fkey(float f) { uint32_t u = __float_as_uint(f); return (u & 0x80000000u) ? ~u : (u | 0x80000000u); }
__device__ __forceinline__ float rcp(float x) { float r; asm("rcp.approx.ftz.f32 %0, %1;" : "=f"(r) : "f"(x)); return r; }
__device__ __forceinline__ float sigm(float x) { return rcp(1.f + ex2(x * -1.4426950408889634f)); }
__device__ __forceinline__ void mma16c(float* d, uint32_t a0, uint32_t a1, uint32_t a2, uint32_t a3, uint32_t b0, uint32_t b1, float c0, float c1) {
    asm volatile("mma.sync.aligned.m16n8k16.row.col.f32.bf16.bf16.f32 {%0,%1,%2,%3}, {%4,%5,%6,%7}, {%8,%9}, {%10,%11,%12,%12};"
                 : "=f"(d[0]), "=f"(d[1]), "=f"(d[2]), "=f"(d[3]) : "r"(a0), "r"(a1), "r"(a2), "r"(a3), "r"(b0), "r"(b1), "f"(c0), "f"(c1), "f"(0.f));
}
__device__ __forceinline__ void ldsm2t(uint32_t* r, uint32_t addr) { asm volatile("ldmatrix.sync.aligned.m8n8.x2.trans.shared.b16 {%0,%1}, [%2];" : "=r"(r[0]), "=r"(r[1]) : "r"(addr) : "memory"); }
__device__ __forceinline__ void stsm2(uint32_t addr, uint32_t a, uint32_t b) { asm volatile("stmatrix.sync.aligned.m8n8.x2.shared.b16 [%2], {%0,%1};" ::"r"(a), "r"(b), "r"(addr) : "memory"); }
__device__ __forceinline__ void lds2(uint32_t* r, uint32_t addr) { asm volatile("ld.shared.v2.u32 {%0,%1}, [%2];" : "=r"(r[0]), "=r"(r[1]) : "r"(addr) : "memory"); }
__device__ __forceinline__ void sts2(uint32_t addr, uint32_t a, uint32_t b) { asm volatile("st.shared.v2.u32 [%2], {%0,%1};" ::"r"(a), "r"(b), "r"(addr) : "memory"); }
__device__ __forceinline__ void sts16(uint32_t addr, uint32_t v) { asm volatile("st.shared.u16 [%0], %1;" ::"r"(addr), "h"((unsigned short)v) : "memory"); }
__device__ __forceinline__ uint32_t lds1(uint32_t addr) { uint32_t v; asm volatile("ld.shared.u32 %0, [%1];" : "=r"(v) : "r"(addr) : "memory"); return v; }
__device__ __forceinline__ bool elect1() { uint32_t p; asm volatile("{.reg .pred P; elect.sync _|P, 0xffffffff; selp.u32 %0, 1, 0, P;}" : "=r"(p)); return p; }
__device__ __forceinline__ void tma2d_mc(uint32_t dst, const CUtensorMap* m, int c0, int c1, uint32_t bar) {
    asm volatile("cp.async.bulk.tensor.2d.shared::cluster.global.mbarrier::complete_tx::bytes.multicast::cluster [%0], [%1, {%3, %4}], [%2], %5;" ::"r"(dst), "l"(m), "r"(bar), "r"(c0), "r"(c1), "h"((unsigned short)3) : "memory");
}
__device__ __forceinline__ void tma3d_mc(uint32_t dst, const CUtensorMap* m, int c0, int c1, int c2, uint32_t bar) {
    asm volatile("cp.async.bulk.tensor.3d.shared::cluster.global.mbarrier::complete_tx::bytes.multicast::cluster [%0], [%1, {%3, %4, %5}], [%2], %6;" ::"r"(dst), "l"(m), "r"(bar), "r"(c0), "r"(c1), "r"(c2), "h"((unsigned short)3) : "memory");
}
__device__ __forceinline__ void tma4d_mc(uint32_t dst, const CUtensorMap* m, int c0, int c1, int c2, int c3, uint32_t bar) {
    asm volatile("cp.async.bulk.tensor.4d.shared::cluster.global.mbarrier::complete_tx::bytes.multicast::cluster [%0], [%1, {%3, %4, %5, %6}], [%2], %7;" ::"r"(dst), "l"(m), "r"(bar), "r"(c0), "r"(c1), "r"(c2), "r"(c3), "h"((unsigned short)3) : "memory");
}
__device__ __forceinline__ void mbar_arrive_cl(uint32_t b) { asm volatile("mbarrier.arrive.shared::cluster.b64 _, [%0];" ::"r"(b) : "memory"); }
__device__ __forceinline__ uint32_t hm2(uint32_t a, uint32_t b) { uint32_t r; asm("mul.rn.bf16x2 %0, %1, %2;" : "=r"(r) : "r"(a), "r"(b)); return r; }
__device__ __forceinline__ uint32_t clock32() { uint32_t c; asm volatile("mov.u32 %0, %clock;" : "=r"(c)); return c; }
__device__ __forceinline__ void wgmma_rs_n192(float* d, const uint32_t* a, uint64_t bdesc, int accum) {
    asm volatile("{.reg .pred p; setp.ne.b32 p, %101, 0; wgmma.mma_async.sync.aligned.m64n192k16.f32.bf16.bf16 {%0,%1,%2,%3,%4,%5,%6,%7,%8,%9,%10,%11,%12,%13,%14,%15,%16,%17,%18,%19,%20,%21,%22,%23,%24,%25,%26,%27,%28,%29,%30,%31,%32,%33,%34,%35,%36,%37,%38,%39,%40,%41,%42,%43,%44,%45,%46,%47,%48,%49,%50,%51,%52,%53,%54,%55,%56,%57,%58,%59,%60,%61,%62,%63,%64,%65,%66,%67,%68,%69,%70,%71,%72,%73,%74,%75,%76,%77,%78,%79,%80,%81,%82,%83,%84,%85,%86,%87,%88,%89,%90,%91,%92,%93,%94,%95}, {%96,%97,%98,%99}, %100, p, 1, 1, 1;}"
        : "+f"(d[0]),"+f"(d[1]),"+f"(d[2]),"+f"(d[3]),"+f"(d[4]),"+f"(d[5]),"+f"(d[6]),"+f"(d[7]),"+f"(d[8]),"+f"(d[9]),"+f"(d[10]),"+f"(d[11]),"+f"(d[12]),"+f"(d[13]),"+f"(d[14]),"+f"(d[15]),"+f"(d[16]),"+f"(d[17]),"+f"(d[18]),"+f"(d[19]),"+f"(d[20]),"+f"(d[21]),"+f"(d[22]),"+f"(d[23]),"+f"(d[24]),"+f"(d[25]),"+f"(d[26]),"+f"(d[27]),"+f"(d[28]),"+f"(d[29]),"+f"(d[30]),"+f"(d[31]),"+f"(d[32]),"+f"(d[33]),"+f"(d[34]),"+f"(d[35]),"+f"(d[36]),"+f"(d[37]),"+f"(d[38]),"+f"(d[39]),"+f"(d[40]),"+f"(d[41]),"+f"(d[42]),"+f"(d[43]),"+f"(d[44]),"+f"(d[45]),"+f"(d[46]),"+f"(d[47]),"+f"(d[48]),"+f"(d[49]),"+f"(d[50]),"+f"(d[51]),"+f"(d[52]),"+f"(d[53]),"+f"(d[54]),"+f"(d[55]),"+f"(d[56]),"+f"(d[57]),"+f"(d[58]),"+f"(d[59]),"+f"(d[60]),"+f"(d[61]),"+f"(d[62]),"+f"(d[63]),"+f"(d[64]),"+f"(d[65]),"+f"(d[66]),"+f"(d[67]),"+f"(d[68]),"+f"(d[69]),"+f"(d[70]),"+f"(d[71]),"+f"(d[72]),"+f"(d[73]),"+f"(d[74]),"+f"(d[75]),"+f"(d[76]),"+f"(d[77]),"+f"(d[78]),"+f"(d[79]),"+f"(d[80]),"+f"(d[81]),"+f"(d[82]),"+f"(d[83]),"+f"(d[84]),"+f"(d[85]),"+f"(d[86]),"+f"(d[87]),"+f"(d[88]),"+f"(d[89]),"+f"(d[90]),"+f"(d[91]),"+f"(d[92]),"+f"(d[93]),"+f"(d[94]),"+f"(d[95])
        : "r"(a[0]), "r"(a[1]), "r"(a[2]), "r"(a[3]), "l"(bdesc), "r"(accum));
}
__device__ __forceinline__ void wgmma_rs_n48(float* d, const uint32_t* a, uint64_t bdesc, int accum) {
    asm volatile("{.reg .pred p; setp.ne.b32 p, %29, 0; wgmma.mma_async.sync.aligned.m64n48k16.f32.bf16.bf16 {%0,%1,%2,%3,%4,%5,%6,%7,%8,%9,%10,%11,%12,%13,%14,%15,%16,%17,%18,%19,%20,%21,%22,%23}, {%24,%25,%26,%27}, %28, p, 1, 1, 1;}"
        : "+f"(d[0]),"+f"(d[1]),"+f"(d[2]),"+f"(d[3]),"+f"(d[4]),"+f"(d[5]),"+f"(d[6]),"+f"(d[7]),"+f"(d[8]),"+f"(d[9]),"+f"(d[10]),"+f"(d[11]),"+f"(d[12]),"+f"(d[13]),"+f"(d[14]),"+f"(d[15]),"+f"(d[16]),"+f"(d[17]),"+f"(d[18]),"+f"(d[19]),"+f"(d[20]),"+f"(d[21]),"+f"(d[22]),"+f"(d[23])
        : "r"(a[0]), "r"(a[1]), "r"(a[2]), "r"(a[3]), "l"(bdesc), "r"(accum));
}
__device__ __forceinline__ void wgmma_rs_n80(float* d, const uint32_t* a, uint64_t bdesc, int accum) {
    asm volatile("{.reg .pred p; setp.ne.b32 p, %45, 0; wgmma.mma_async.sync.aligned.m64n80k16.f32.bf16.bf16 {%0,%1,%2,%3,%4,%5,%6,%7,%8,%9,%10,%11,%12,%13,%14,%15,%16,%17,%18,%19,%20,%21,%22,%23,%24,%25,%26,%27,%28,%29,%30,%31,%32,%33,%34,%35,%36,%37,%38,%39}, {%40,%41,%42,%43}, %44, p, 1, 1, 1;}"
        : "+f"(d[0]),"+f"(d[1]),"+f"(d[2]),"+f"(d[3]),"+f"(d[4]),"+f"(d[5]),"+f"(d[6]),"+f"(d[7]),"+f"(d[8]),"+f"(d[9]),"+f"(d[10]),"+f"(d[11]),"+f"(d[12]),"+f"(d[13]),"+f"(d[14]),"+f"(d[15]),"+f"(d[16]),"+f"(d[17]),"+f"(d[18]),"+f"(d[19]),"+f"(d[20]),"+f"(d[21]),"+f"(d[22]),"+f"(d[23]),"+f"(d[24]),"+f"(d[25]),"+f"(d[26]),"+f"(d[27]),"+f"(d[28]),"+f"(d[29]),"+f"(d[30]),"+f"(d[31]),"+f"(d[32]),"+f"(d[33]),"+f"(d[34]),"+f"(d[35]),"+f"(d[36]),"+f"(d[37]),"+f"(d[38]),"+f"(d[39])
        : "r"(a[0]), "r"(a[1]), "r"(a[2]), "r"(a[3]), "l"(bdesc), "r"(accum));
}

__global__ void __cluster_dims__(2, 1, 1) __launch_bounds__(384, 1)
fused_kernel(const __nv_bfloat16* __restrict__ wmod, const __nv_bfloat16* __restrict__ cvec, Scratch* __restrict__ S,
             const __nv_bfloat16* __restrict__ wqkv, const __nv_bfloat16* __restrict__ wo, __nv_bfloat16* __restrict__ out,
             const __nv_bfloat16* __restrict__ wr, const __nv_bfloat16* __restrict__ wg, const __nv_bfloat16* __restrict__ wu,
             const __nv_bfloat16* __restrict__ wd,
             const __grid_constant__ CUtensorMap mm, const __grid_constant__ CUtensorMap mx, const __grid_constant__ CUtensorMap mw,
             const __grid_constant__ CUtensorMap mt, const __grid_constant__ CUtensorMap mo, const __grid_constant__ CUtensorMap mg,
             const __grid_constant__ CUtensorMap mu, const __grid_constant__ CUtensorMap md, const __grid_constant__ CUtensorMap mr) {
    extern __shared__ __align__(1024) char sm_raw[];
    const int bid = blockIdx.x;
    const uint32_t sm = ((bid & 1) << 24) + SM0;
    STAMP(30);
    const uint32_t t_start = clock32();
    const int tid = threadIdx.x, warp = __shfl_sync(~0u, tid >> 5, 0), lane = tid & 31;
    const bool spare = bid >= 128;
    if (warp == 8) {
        if (elect1()) {
            mbar_init(BAR(B_WM), 1);
            if (bid < 80) { mbar_expect_tx(BAR(B_WM), 20480); tma3d(sm + OFF_WM, &mm, bid * 16, 0, 0, BAR(B_WM)); }
            STAMPT(22, 256);
#pragma unroll
            for (int i = 0; i < B_N; i++) if (i != B_WM) mbar_init(BAR(i), i >= B_WE ? (spare ? 8 : 16) : (i > B_EP ? 8 : (i == B_EP ? 2 : 1)));
            asm volatile("fence.mbarrier_init.release.cluster;" ::: "memory");
        }
        __syncwarp();
    } else if (warp >= 3 && warp < 8 && !spare) {
        if (elect1()) l2_prefetch(wmod + (size_t)(bid * 5 + warp - 3) * 3840, 2560);
        __syncwarp();
    }
    uint32_t cw[4], ep0;
    if (warp > 8) ldg4_nc(cw, cvec + min(tid - 288, 79) * 8);
    if (warp != 8) ep0 = ldg1_rlx(&S->epoch);
    asm volatile("barrier.cluster.arrive.relaxed.aligned;" ::: "memory");
    if (smem_u32(sm_raw) != sm) return;
    const int cl = bid >> 1, rank = bid & 1, c7 = ((cl - 36) * 37) >> 8;
    const int grp = cl < 4 ? 0 : (cl < 36 ? (cl - 4) & 7 : cl - 35 - 7 * c7), j = cl < 4 ? 4 + cl : (cl < 36 ? (cl - 4) >> 3 : 4 + c7);
    const int ti = grp * 2 + rank, role = spare ? bid : ti * 8 + j, odd = j & 1;
    const int g = lane >> 2, q = lane & 3;
    const uint32_t frow = (lane & 7) + (lane >> 4) * 8, fh = (lane >> 3) & 1;
    const uint32_t frag = frow * 32 + ((fh ^ ((lane >> 2) & 1)) << 4);

    if (warp >= 8) {
        asm volatile("setmaxnreg.dec.sync.aligned.u32 104;");
        if (warp == 8) {
            if (!spare && elect1()) {
                while (clock32() - t_start < XDELAY) {}
#pragma unroll 1
                for (int c = 0; c < 10; c++) { mbar_expect_tx(BAR(B_XF + c), 16384); tma3d(sm + c * 16384, &mx, c * 64, ti >> 3, (ti & 7) * 128, BAR(B_XF + c)); }
                STAMPT(23, 256);
            }
            __syncwarp();
            asm volatile("barrier.cluster.wait.aligned;" ::: "memory");
            if (!elect1()) return;
            if (spare) {
                mbar_wait(BAR(B_RDY), 0);
#pragma unroll 1
                for (int it = 0; it < 20; it++) {
                    const int s = it % 5;
                    if (it >= 5) mbar_wait(BAR(B_WE + s), (it / 5 - 1) & 1);
                    mbar_expect_tx(BAR(B_XF + s), 40960);
                    tma3d(sm + s * 40960, &mr, 0, it * 32, 20 + (role - 128) * 10, BAR(B_XF + s));
                }
                return;
            }
            const int col_main = 80 * j + 16 * odd, col_tail = 80 * j + (odd ? 0 : 64);
#pragma unroll 1
            for (int it = 0; it < 20; it++) {
                if (it == 2) { mbar_wait(BAR(B_WMF), 0); l2_prefetch(wqkv + (size_t)(128 + role * 4) * 1920, 4 * 3840); }
                if (it >= 4) mbar_wait(BAR(B_WE + (it & 3)), ((it >> 2) & 1) ^ 1);
                {
                    const uint32_t b = BAR(B_WF + (it & 3)), dst = sm + OFF_W + (it & 3) * WST + rank * 7680;
                    mbar_expect_tx(b, WST);
                    tma4d_mc(dst, &mw, 0, it * 32 + rank * 16, col_main >> 5, 0, b);
                    tma3d_mc(dst + 6144, &mt, col_tail, it * 32 + rank * 16, 0, b);
                }
                if (it == 3) l2_prefetch(wo + role * 3200, 6400);
                if (it >= 4 && !(it & 1)) {
                    const int w = (it - 4) >> 1, row = (w == 0 ? j : (w <= j ? w - 1 : w)) * 80 + rank * 40;
                    const uint32_t b = BAR(B_WO + w), dst = sm + w * WST + rank * 2560;
                    mbar_expect_tx(b, WST);
                    tma2d_mc(dst, &mo, col_main, row, b); tma2d_mc(dst + 5120, &mo, col_main + 32, row, b); tma2d_mc(dst + 10240, &mo, col_tail, row, b);
                }
                if (it >= 5 && it < 17 && (it & 1)) l2_prefetch((it < 9 ? wg : (it < 13 ? wu : wd)) + role * 8640 + (it & 2) * 2160, 8640);
            }
            STAMPT(24, 256);
            if (role < 108) { mbar_wait(BAR(B_G0), 0); mbar_expect_tx(BAR(B_FG), 40960); tma3d(sm + OFF_WG, (role & 1) ? &mu : &mg, (role >> 1) * 32, 0, 0, BAR(B_FG)); }
            if (role >= 88) { mbar_wait(BAR(B_G2), 0); mbar_expect_tx(BAR(B_FD), 55296); tma3d(sm + OFF_WD, &md, (role - 88) * 16, 0, 0, BAR(B_FD)); }
            return;
        }
        int at = tid - 288;
        if (at < 80) {
            const uint32_t a = sm + OFF_S + (at >> 1) * 32 + (at & 1) * 4;
#pragma unroll
            for (int e = 0; e < 4; e++) sts1(a + e * 8, pack2(blo(cw[e]) * sigm(blo(cw[e])), bhi(cw[e]) * sigm(bhi(cw[e]))));
        }
        STAMPT(26, 288);
        __syncwarp();
        asm volatile("bar.arrive 0, 352;" ::: "memory");
        asm volatile("barrier.cluster.wait.aligned;" ::: "memory");
        const uint32_t epoch = ep0 + 1, tag = epoch & 0xffffu;
        int gd = 0;
        if (warp == 9) {
            {
                uint32_t w[5][4];
                const uint2* tp = &S->tab[epoch & 1][grp & 7][lane * 2];
                do {
#pragma unroll
                    for (int e = 0; e < 5; e++) ldg4_rlx(w[e], tp + e * 64);
                    uint32_t m = w[0][0];
#pragma unroll
                    for (int e = 0; e < 5; e++) m = min(m, min(w[e][0], w[e][2]));
                    if (!__any_sync(~0u, m == 0)) break;
                } while (++gd < SPIN_LIMIT);
                if (spare) { if (lane == 0) mbar_arrive(BAR(B_RDY)); return; }
#pragma unroll
                for (int e = 0; e < 5; e++) { const uint32_t v[4] = {~w[e][0], ~w[e][1], ~w[e][2], ~w[e][3]}; sts4(sm + OFF_TAB + e * 512 + lane * 16, v); }
            }
            STAMPT(2, 288);
            asm volatile("bar.arrive 1, 352;" ::: "memory");
            uint32_t h[5][4];
            do { __nanosleep(1000); ldg4_rlx(h[0], &S->ready[lane * 4]); } while (__any_sync(~0u, h[0][0] != epoch || h[0][1] != epoch || h[0][2] != epoch || h[0][3] != epoch) && ++gd < SPIN_LIMIT);
            asm volatile("fence.acq_rel.gpu;" ::: "memory");
            __syncwarp();
            if (lane == 0) mbar_arrive(BAR(B_RDY));
            mbar_wait(BAR(HALO_GO), 0);
            if ((ti & 7) == 0) {
#pragma unroll
                for (int s = 0; s < 20; s++) h[s >> 2][s & 3] = 0;
            } else {
                do {
#pragma unroll
                    for (int s = 0; s < 5; s++) ldg4_rlx(h[s], &S->halo[(role - 8) * 160 + s * 32 + lane]);
                } while (__any_sync(~0u, max(max(max(h[0][0], h[1][0]), max(h[2][0], h[3][0])), h[4][0]) == SENT) && ++gd < SPIN_LIMIT);
            }
            sts4(sm + OFF_KH + lane * 16, h[0]); sts4(sm + OFF_KH + 512 + lane * 16, h[1]); sts2(sm + OFF_KH + 1024 + lane * 8, h[2][0], h[2][1]);
            const uint32_t va = sm + OFF_V + (lane & 7) * VP + (lane >> 3) * 16;
            stsm4(va, h[3]); stsm4(va + 64, h[4]); stsm2(va + 128, h[2][2], h[2][3]);
            __syncwarp();
            if (lane == 0) mbar_arrive(BAR(B_HL));
            STAMPT(19, 288);
            mbar_wait(BAR(B_G3), 0);
            do {
                ldg4_rlx(h[0], &S->rec[grp * 128 + lane * 4]); ldg4_rlx(h[1], &S->rec[grp * 128 + lane * 4 + 2]);
            } while (__any_sync(~0u, (h[0][1] | h[0][3] | h[1][1] | h[1][3]) == SENT) && ++gd < SPIN_LIMIT);
            const uint32_t kwin = __reduce_max_sync(~0u, max(max(h[0][0], h[0][2]), max(h[1][0], h[1][2])));
            const uint32_t tok = __reduce_min_sync(~0u, min(min(h[0][0] == kwin ? h[0][1] : 2047u, h[0][2] == kwin ? h[0][3] : 2047u), min(h[1][0] == kwin ? h[1][1] : 2047u, h[1][2] == kwin ? h[1][3] : 2047u)));
            if (lane == 0) { sts2(sm + OFF_EP + EP_US + 8, kwin, tok); mbar_arrive(BAR(B_WIN)); if (role == 0) stg1_rlx(&S->epoch, epoch); }
            return;
        }
        if (spare) return;
        at -= 32;
        bar_sync(1, 352);
        {
            uint4* po = &S->o[(ti * 64 + j) * 160 + at];
            uint4* pc = at < 32 ? po + 128 : (at < 52 ? &S->cand[(ti * 64 + j) * 24 + at - 32] : &S->halo[role * 160 + at - 52]);
            const int dc = at < 32 ? 1280 : (at < 52 ? 192 : 12);
#pragma unroll 1
            for (int w = 0; w < 8; w++) {
                stg4_rlx(po, SENT, SENT, SENT, SENT); stg4_rlx(po + 64, SENT, SENT, SENT, SENT); stg4_rlx(pc, SENT, SENT, SENT, SENT);
                po += 1280; pc += dc;
                __nanosleep(RSLEEP);
            }
            stg4_rlx(&S->halo[role * 160 + 96 + at], SENT, SENT, SENT, SENT);
            po = &S->stats[((ti * 8 + (at >> 4)) * 8 + j) * 16 + (at & 15)];
            stg4_rlx(po, SENT, SENT, SENT, SENT); stg4_rlx(po + 512, SENT, SENT, SENT, SENT);
            if (at < 16) stg2_rlx(at < 8 ? &S->rec[at * 128 + role] : &S->a[role * 8 + at - 8], SENT, SENT);
        }
        __syncwarp();
        bar_sync(3, 64);
        if (at == 0) { asm volatile("fence.acq_rel.gpu;" ::: "memory"); stg1_rlx(&S->ready[role], epoch); }
        mbar_wait(BAR(B_G0), 0);
        {
            uint32_t own[4][2], us[2], bad;
            const int kg = at < 40 ? 80 * j + 2 * at : max(role - 88, 0) * 16 + 2 * (at & 7);
            const uint32_t w2 = *(const uint32_t*)(wr + kg);
            while (true) {
                ldg2_rlx(us, &S->us[lane & 15]);
                bad = us[1] ^ tag;
#pragma unroll
                for (int e = 0; e < 4; e++) { ldg2_rlx(own[e], &S->mod[e * 640 + kg]); bad |= (own[e][0] ^ tag) | (own[e][1] ^ tag); }
                if (!__any_sync(~0u, bad & 0xffffu) || ++gd > SPIN_LIMIT) break;
                __nanosleep(300);
            }
            const uint32_t gb = __byte_perm(own[3][0], own[3][1], 0x7632);
            if (at < 40) {
                const int p = odd ? (at < 8 ? at + 32 : at - 8) : at;
                const uint32_t a = sm + OFF_EP + (p & 3) * 48 + (p >> 2) * 4;
                const float u0 = bhi(own[2][0]) * blo(w2), u1 = bhi(own[2][1]) * bhi(w2);
                const uint32_t uh = pack2(u0, u1);
                sts1(a, __byte_perm(own[0][0], own[0][1], 0x7632)); sts1(a + 192, __byte_perm(own[2][0], own[2][1], 0x7632));
                sts1(a + 384, __byte_perm(own[1][0], own[1][1], 0x7632)); sts1(a + 576, gb);
                sts1(a + 768, 0x3f803f80u); sts1(a + 960, uh); sts1(a + 1152, pack2(u0 - blo(uh), u1 - bhi(uh)));
            } else sts1(sm + OFF_EP + EP_GD + (at & 7) * 4, gb);
            float t = __uint_as_float(us[0]);
#pragma unroll
            for (int o = 1; o < 8; o <<= 1) t += __shfl_xor_sync(~0u, t, o);
            if (at == 0 || at == 8) sts1f(sm + OFF_EP + EP_US + (at >> 1), t);
            __syncwarp();
            if (lane == 0) mbar_arrive(BAR(B_EP));
            STAMPT(20, 320);
        }
    } else {
        asm volatile("setmaxnreg.inc.sync.aligned.u32 200;");
        asm volatile("barrier.cluster.wait.aligned;" ::: "memory");
        bar_sync(0, 352);
        const uint32_t epoch = ep0 + 1, tag = epoch & 0xffffu;
        if (spare) {
            float d[5][4] = {};
            uint32_t off[5];
#pragma unroll
            for (int i = 0; i < 5; i++) { const int c = warp * 5 + i; off[i] = sm + (c >> 2) * 4096 + frow * 128 + ((((c & 3) * 2 + fh) ^ (lane & 7)) << 4); }
#pragma unroll 1
            for (int it = 0; it < 20; it++) {
                const int s = it % 5;
                mbar_wait(BAR(B_XF + s), (it / 5) & 1);
#pragma unroll
                for (int h = 0; h < 2; h++) {
                    uint32_t b[2];
                    lds2(b, sm + OFF_S + (it * 2 + h) * 32 + q * 8);
#pragma unroll
                    for (int i = 0; i < 5; i++) { uint32_t a[4]; ldsm4t(a, off[i] + s * 40960 + h * 2048); mma16(d[i], a[0], a[1], a[2], a[3], b[0], b[1]); }
                }
                __syncwarp();
                if (lane == 0) mbar_arrive(BAR(B_WE + s));
            }
            float dot = 0.f;
#pragma unroll
            for (int i = 0; i < 5; i++) {
                const int c = warp * 80 + i * 16 + (q & 1) * 8 + g;
                float t = rbf((q & 1) ? d[i][2] : d[i][0]);
                if (role == 130) t = rbf(1.f + t);
                if (q < 2) { stg1_rlx(&S->mod[(role - 128) * 640 + c], __float_as_uint(t) | tag); dot = fmaf(t, __bfloat162float(wr[c]), dot); }
            }
#pragma unroll
            for (int o = 16; o; o >>= 1) dot += __shfl_xor_sync(~0u, dot, o);
            if (lane == 0 && (role == 129 || role == 130)) stg2_rlx(&S->us[(role - 129) * 8 + warp], __float_as_uint(dot), tag);
            STAMP(17);
            return;
        }
        const int tw = ti * 8 + warp;
        uint4* const my_o = &S->o[tw * 8 * 160 + lane];
        const uint32_t pair = (uint32_t)(lane & 1) << 24;
        if (bid < 80) {
            uint32_t a[5][4], b[5][2];
#pragma unroll
            for (int s = 0; s < 5; s++) lds2(b[s], sm + OFF_S + (warp * 5 + s) * 32 + q * 8);
            mbar_wait(BAR(B_WM), 0);
            STAMP(27);
#pragma unroll
            for (int s = 0; s < 5; s++) ldsm4t(a[s], sm + OFF_WM + (warp * 5 + s) * 512 + frag);
            float d[2][4] = {};
#pragma unroll
            for (int s = 0; s < 5; s++) mma16(d[s & 1], a[s][0], a[s][1], a[s][2], a[s][3], b[s][0], b[s][1]);
            if (q < 2) sts1f(sm + OFF_RED + (warp * 16 + q * 8 + g) * 4, q ? d[0][2] + d[1][2] : d[0][0] + d[1][0]);
            bar_sync(2, 256);
            if (warp == 0) {
                float t = 0.f;
#pragma unroll
                for (int w = 0; w < 4; w++) t += lds1f(sm + OFF_RED + (w * 32 + lane) * 4);
                t = rbf(t + __shfl_xor_sync(~0u, t, 16));
                if (bid >= 40) t += 1.f;
                const uint32_t pr = pack2(t, __shfl_down_sync(~0u, t, 1));
                const int e = (bid >= 40 ? (bid - 40) * 8 : bid * 8 + 1) + q * 2;
                stg2_rlx(&S->tab[epoch & 1][g][e], ~__shfl_sync(~0u, pr, 2 * q), ~__shfl_sync(~0u, pr, 2 * q + 8));
                stg2_rlx(&S->tab[~epoch & 1][g][e], 0u, 0u);
            }
        }
        if (lane < 2) mbar_arrive_cl(pair + BAR0(B_WMF));
        STAMP(0);
        const uint32_t hi = lane >> 4, xa = sm + (warp * 16 + (lane & 15)) * 128 + ((hi ^ (lane & 7)) << 4);
        uint32_t rr0, rr1, nn0, nn1;
        {
            float gA[2][4] = {}, gB[2][4] = {};
            const uint32_t xb = sm + (warp * 16 + frow) * 128 + ((fh ^ (lane & 7)) << 4), one = 0x3f803f80u;
#pragma unroll 1
            for (int c = 0; c < 10; c++) {
                mbar_wait(BAR(B_XF + c), 0);
                uint32_t a[4][4];
#pragma unroll
                for (int k = 0; k < 4; k++) ldsm4(a[k], (xb ^ (k * 32)) + c * 16384);
#pragma unroll
                for (int k = 0; k < 4; k++) {
                    mma16(gA[k & 1], a[k][0], one, a[k][1], one, a[k][0], a[k][1]);
                    mma16(gB[k & 1], a[k][2], one, a[k][3], one, a[k][2], a[k][3]);
                }
            }
            const int src = (lane & ~3) | (g >> 1), e = g & 1;
            const float ss0 = __shfl_sync(~0u, e ? gA[0][1] + gA[1][1] : gA[0][0] + gA[1][0], src), ss1 = __shfl_sync(~0u, e ? gB[0][1] + gB[1][1] : gB[0][0] + gB[1][0], src);
            const float m0 = __shfl_sync(~0u, e ? gA[0][3] + gA[1][3] : gA[0][2] + gA[1][2], src) * (1.f / 640), m1 = __shfl_sync(~0u, e ? gB[0][3] + gB[1][3] : gB[0][2] + gB[1][2], src) * (1.f / 640);
            const float r0 = rbf(rsqrtf(fmaxf(ss0 * (1.f / 640) - m0 * m0, 0.f) + 1e-5f)), r1 = rbf(rsqrtf(fmaxf(ss1 * (1.f / 640) - m1 * m1, 0.f) + 1e-5f));
            rr0 = pack2(r0, r0); rr1 = pack2(r1, r1); nn0 = pack2(-m0 * r0, -m0 * r0); nn1 = pack2(-m1 * r1, -m1 * r1);
        }
        uint32_t xr[5][4];
#pragma unroll
        for (int s = 0; s < 5; s++) {
            const int ks = 5 * j + (odd ? (s == 4 ? 0 : s + 1) : s);
            ldsm4(xr[s], (xa ^ ((ks & 3) * 32)) + (ks >> 2) * 16384);
        }
        STAMP(1);
        bar_sync(1, 352);
        float acc[120];
#pragma unroll
        for (int i = 0; i < 120; i++) asm volatile("" : "=f"(acc[i]));
        {
            uint32_t a[2][2][4], raw[2][4], tt[2][4];
            uint32_t tb = sm + OFF_TAB + q * 16, xp = xa;
            auto load = [&](int u) {
                ldsm4(raw[0], xp ^ (u * 64)); ldsm4(raw[1], xp ^ (u * 64 + 32));
                lds4(tt[0], tb + u * 128); lds4(tt[1], tb + u * 128 + 64);
            };
            auto xform = [&](uint32_t (*dst)[4]) {
#pragma unroll
                for (int h = 0; h < 2; h++) {
                    dst[h][0] = hf2(hf2(raw[h][0], rr0, nn0), tt[h][0], tt[h][2]); dst[h][1] = hf2(hf2(raw[h][1], rr1, nn1), tt[h][0], tt[h][2]);
                    dst[h][2] = hf2(hf2(raw[h][2], rr0, nn0), tt[h][1], tt[h][3]); dst[h][3] = hf2(hf2(raw[h][3], rr1, nn1), tt[h][1], tt[h][3]);
                }
            };
            const uint64_t dm0 = mkdesc(SM0 + OFF_W, 1024, 512, 2), dt0 = mkdesc(SM0 + OFF_W + 6144, 512, 256, 3);
            load(0); xform(a[0]);
            STAMP(3);
#pragma unroll 1
            for (int i2 = 0; i2 < 10; i2++) {
#pragma unroll
                for (int u = 0; u < 2; u++) {
                    const int st = (i2 & 1) * 2 + u;
                    mbar_wait(BAR(B_WF + st), (i2 >> 1) & 1);
                    wg_fence();
#pragma unroll
                    for (int h = 0; h < 2; h++) { wgmma_rs_n192(acc, a[u][h], dm0 + st * (WST / 16) + h * 480, u + h + i2); wgmma_rs_n48(acc + 96, a[u][h], dt0 + st * (WST / 16) + h * 480, u + h + i2); }
                    wg_commit();
                    if (u == 1) { xp += 16384; tb += 256; }
                    load(u ^ 1);
                    wg_wait<1>();
                    if (lane < 2 && (u == 1 ? i2 < 8 : (i2 > 0 && i2 < 9))) mbar_arrive_cl(pair + BAR0(B_WE + ((st + 3) & 3)));
                    if (u == 1 && i2 == 8 && lane == 0) mbar_arrive(BAR(B_L16));
                    xform(a[u ^ 1]);
                }
            }
            wg_wait<0>();
            if (lane == 0) mbar_arrive(BAR(B_G0));
        }
        STAMP(4);
        uint32_t ab[4][5][4];
        {
            uint32_t Q[10][2], K[2][10], V[2][10];
            if (!odd) {
#pragma unroll
                for (int t = 0; t < 10; t++) {
                    const int iq = t < 8 ? t * 4 : 96 + (t - 8) * 4, ik = t < 8 ? 32 + t * 4 : 104 + (t - 8) * 4, iv = t < 8 ? 64 + t * 4 : 112 + (t - 8) * 4;
                    K[1][t] = pack2(acc[ik + 2], acc[ik + 3]); V[0][t] = pack2(acc[iv], acc[iv + 1]); V[1][t] = pack2(acc[iv + 2], acc[iv + 3]);
                    K[0][t] = pack2(acc[ik], acc[ik + 1]); Q[t][0] = pack2(acc[iq], acc[iq + 1]); Q[t][1] = pack2(acc[iq + 2], acc[iq + 3]);
                }
            } else {
#pragma unroll
                for (int t = 0; t < 10; t++) {
                    const int iq = t >= 2 ? (t - 2) * 4 : 96 + t * 4, ik = t >= 2 ? 32 + (t - 2) * 4 : 104 + t * 4, iv = t >= 2 ? 64 + (t - 2) * 4 : 112 + t * 4;
                    K[1][t] = pack2(acc[ik + 2], acc[ik + 3]); V[0][t] = pack2(acc[iv], acc[iv + 1]); V[1][t] = pack2(acc[iv + 2], acc[iv + 3]);
                    K[0][t] = pack2(acc[ik], acc[ik + 1]); Q[t][0] = pack2(acc[iq], acc[iq + 1]); Q[t][1] = pack2(acc[iq + 2], acc[iq + 3]);
                }
            }
            mbar_wait(BAR(B_RDY), 0);
            if (warp == 7) {
                uint4* hp = &S->halo[role * 160 + lane];
                stg4_rlx(hp, K[1][0], K[1][1], K[1][3], K[1][4]); stg4_rlx(hp + 32, K[1][5], K[1][6], K[1][8], K[1][9]); stg4_rlx(hp + 64, K[1][2], K[1][7], V[1][8], V[1][9]);
                stg4_rlx(hp + 96, V[1][0], V[1][1], V[1][2], V[1][3]); stg4_rlx(hp + 128, V[1][4], V[1][5], V[1][6], V[1][7]);
            }
            mbar_wait(BAR(B_L16), 0);
            const uint32_t kh = sm + OFF_KH + warp * 1280, vr = sm + OFF_V + (warp * 16 + (lane & 7)) * VP;
            {
                const uint32_t k0[4] = {K[1][0], K[1][1], K[1][3], K[1][4]}, k1[4] = {K[1][5], K[1][6], K[1][8], K[1][9]};
                sts4(kh + 1280 + lane * 16, k0); sts4(kh + 1792 + lane * 16, k1); sts2(kh + 2304 + lane * 8, K[1][2], K[1][7]);
                const uint32_t va = vr + (lane >> 3) * 16, vl[4] = {V[0][8], V[0][9], V[1][8], V[1][9]};
                stsm4(va + 16 * VP, V[1]); stsm4(va + 16 * VP + 64, V[1] + 4); stsm4(vr + (8 + hi * 8) * VP + 128 + ((lane >> 3) & 1) * 16, vl);
                stsm4(va + 8 * VP, V[0]); stsm4(va + 8 * VP + 64, V[0] + 4);
            }
            __syncwarp();
            if (lane == 0 && warp < 7) mbar_arrive(BAR(B_HL + 1 + warp));
            uint32_t VT[5][4], VH[10], KH[10];
#pragma unroll
            for (int s = 0; s < 5; s++) ldsm4t(VT[s], vr + (8 + ((lane >> 3) & 1) * 8) * VP + s * 32 + hi * 16);
            float sb[4][4], sc[4][4], sa[4][4];
            uint32_t qs[4][2];
#pragma unroll
            for (int h = 0; h < 4; h++) {
                const int ts = (h >> 1) * 5 + 2, ta = (h >> 1) * 5 + (h & 1) * 3;
                const bool mine = (q >> 1) == (h & 1);
                qs[h][0] = mine ? Q[ts][0] : 0u; qs[h][1] = mine ? Q[ts][1] : 0u;
                mma16c(sb[h], Q[ta][0], Q[ta][1], Q[ta + 1][0], Q[ta + 1][1], K[0][ta], K[0][ta + 1], 0.f, 0.f);
                mma16c(sc[h], Q[ta][0], Q[ta][1], Q[ta + 1][0], Q[ta + 1][1], K[1][ta], K[1][ta + 1], 0.f, 0.f);
                mma8(sb[h], qs[h][0], qs[h][1], K[0][ts]);
                mma8(sc[h], qs[h][0], qs[h][1], K[1][ts]);
            }
            mbar_wait(BAR(B_HL + warp), 0);
            lds4(KH, kh + lane * 16); lds4(KH + 4, kh + 512 + lane * 16); lds2(KH + 8, kh + 1024 + lane * 8);
            ldsm4t(VH, vr + (lane >> 3) * 16); ldsm4t(VH + 4, vr + 64 + (lane >> 3) * 16); ldsm2t(VH + 8, vr + 128 + ((lane >> 3) & 1) * 16);
            STAMP(5);
            const float ninf = (tw & 63) == 0 ? -INFINITY : 0.f;
#pragma unroll
            for (int h = 0; h < 4; h++) {
                const int ta = (h >> 1) * 5 + (h & 1) * 3;
                mma16c(sa[h], Q[ta][0], Q[ta][1], Q[ta + 1][0], Q[ta + 1][1], KH[2 * h], KH[2 * h + 1], ninf, ninf);
                mma8(sa[h], qs[h][0], qs[h][1], KH[8 + (h >> 1)]);
            }
            const bool gt0 = 2 * q > g, gt1 = 2 * q + 1 > g;
            const uint32_t mgt = (gt0 ? 0xffffu : 0u) | (gt1 ? 0xffff0000u : 0u);
            const float cs = 0.22360679774997896f * 1.4426950408889634f;
            uint32_t of[12][2];
#pragma unroll
            for (int h = 0; h < 4; h++) {
                const int ts = (h >> 1) * 5 + 2, ta = (h >> 1) * 5 + (h & 1) * 3;
                float t0 = gt0 ? sa[h][0] : sb[h][0], t1 = gt1 ? sa[h][1] : sb[h][1];
                float b0 = gt0 ? sb[h][2] : sc[h][2], b1 = gt1 ? sb[h][3] : sc[h][3];
                float mt_ = fmaxf(t0, t1), mb = fmaxf(b0, b1);
                mt_ = fmaxf(mt_, __shfl_xor_sync(~0u, mt_, 1)); mb = fmaxf(mb, __shfl_xor_sync(~0u, mb, 1));
                mt_ = fmaxf(mt_, __shfl_xor_sync(~0u, mt_, 2)); mb = fmaxf(mb, __shfl_xor_sync(~0u, mb, 2));
                mt_ *= -cs; mb *= -cs;
                t0 = ex2(fmaf(t0, cs, mt_)); t1 = ex2(fmaf(t1, cs, mt_)); b0 = ex2(fmaf(b0, cs, mb)); b1 = ex2(fmaf(b1, cs, mb));
                float lt = t0 + t1, lb = b0 + b1;
                lt += __shfl_xor_sync(~0u, lt, 1); lb += __shfl_xor_sync(~0u, lb, 1);
                lt += __shfl_xor_sync(~0u, lt, 2); lb += __shfl_xor_sync(~0u, lb, 2);
                lt = rcp(lt); lb = rcp(lb);
                const uint32_t pt = pack2(t0 * lt, t1 * lt), pb = pack2(b0 * lb, b1 * lb);
                const uint32_t pA = pt & mgt, pBt = pt & ~mgt, pBb = pb & mgt, pC = pb & ~mgt;
#pragma unroll
                for (int e = 0; e < 3; e++) {
                    const int t = e == 2 ? ts : ta + e;
                    float d[4];
                    mma16c(d, pBt, pBb, 0u, pC, VT[t >> 1][(t & 1) * 2], VT[t >> 1][(t & 1) * 2 + 1], 0.f, 0.f);
                    mma8(d, pA, 0u, VH[t]);
                    of[h * 3 + e][0] = pack2(d[0], d[1]); of[h * 3 + e][1] = pack2(d[2], d[3]);
                }
            }
#pragma unroll
            for (int t = 0; t < 10; t++) {
                const int p = t / 5, r = t % 5;
#pragma unroll
                for (int e = 0; e < 2; e++) ab[0][t >> 1][(t & 1) * 2 + e] = r == 2 ? ((q & 2) ? of[p * 6 + 5][e] : of[p * 6 + 2][e]) : of[p * 6 + r][e];
            }
#pragma unroll
            for (int s = 0; s < 5; s++) stg4_rlx(my_o + j * 160 + s * 32, ab[0][s][0], ab[0][s][1], ab[0][s][2], ab[0][s][3]);
        }
        STAMP(6);
        float ac2[40];
#pragma unroll
        for (int i = 0; i < 40; i++) asm volatile("" : "=f"(ac2[i]));
#pragma unroll
        for (int i = 0; i < 60; i++) asm volatile("" : "=r"(ab[1 + i / 20][(i / 4) % 5][i % 4]));
        {
            const uint64_t d0 = mkdesc(SM0, 5120, 512, 2);
            auto ldsrc = [&](int w, uint32_t (*dst)[4]) {
                const uint4* p = my_o + (w <= j ? w - 1 : w) * 160;
#pragma unroll
                for (int s = 0; s < 5; s++) ldg4_rlx(dst[s], p + s * 32);
            };
#pragma unroll 1
            for (int w4 = 0; w4 < 8; w4 += 4) {
#pragma unroll
                for (int u = 0; u < 4; u++) {
                    const int w = w4 + u;
                    int gd = 0;
                    while (__any_sync(~0u, max(max(max(ab[u][0][0], ab[u][1][0]), max(ab[u][2][0], ab[u][3][0])), ab[u][4][0]) == SENT) && ++gd < SPIN_LIMIT) ldsrc(w, ab[u]);
                    mbar_wait(BAR(B_WO + w), 0);
                    wg_fence();
#pragma unroll
                    for (int s = 0; s < 5; s++) wgmma_rs_n80(ac2, ab[u][s], d0 + w * (WST / 16) + s * 64, w + s);
                    wg_commit();
                    if (u == 0 && w4 == 0) { ldsrc(1, ab[1]); ldsrc(2, ab[2]); }
                    if (w < 5) { wg_wait<1>(); ldsrc(w + 3, ab[(u + 3) & 3]); }
                    if (u == 0 && w4 == 4 && lane == 0) mbar_arrive(BAR(B_G2));
                }
            }
        }
        mbar_wait(BAR(B_EP), 0);
        uint32_t tga[12], tst[12];
        const uint32_t ep = sm + OFF_EP + q * 48;
#pragma unroll
        for (int s = 0; s < 3; s++) { lds4(tga + 4 * s, ep + s * 16); lds4(tst + 4 * s, ep + 768 + min(g, 2) * 192 + s * 16); }
        wg_wait<0>();
        STAMP(8);
        {
            float gA[4] = {}, gB[4] = {}, sd[4] = {};
#pragma unroll
            for (int s = 0; s < 5; s++) {
#pragma unroll
                for (int e = 0; e < 4; e++) xr[s][e] = hf2(tga[2 * s + (e >> 1)], pack2(ac2[s * 8 + e * 2], ac2[s * 8 + e * 2 + 1]), xr[s][e]);
                mma16(gA, xr[s][0], xr[s][1], xr[s][2], xr[s][3], xr[s][0], xr[s][2]);
                mma16(gB, xr[s][0], xr[s][1], xr[s][2], xr[s][3], xr[s][1], xr[s][3]);
                mma16(sd, xr[s][0], xr[s][1], xr[s][2], xr[s][3], tst[2 * s], tst[2 * s + 1]);
            }
            const float q0 = __shfl_sync(~0u, (g & 1) ? gA[1] : gA[0], (lane & ~3) | (g >> 1)), q1 = __shfl_sync(~0u, (g & 1) ? gB[3] : gB[2], (lane & ~3) | (g >> 1));
            const float l0 = __shfl_down_sync(~0u, sd[0], 1), l1 = __shfl_down_sync(~0u, sd[2], 1);
            if (q == 0) {
                uint4* sp = &S->stats[(tw * 8 + j) * 16 + g];
                stg4_rlx(sp, __float_as_uint(sd[0]), __float_as_uint(q0), __float_as_uint(sd[1] + l0), 0u);
                stg4_rlx(sp + 8, __float_as_uint(sd[2]), __float_as_uint(q1), __float_as_uint(sd[3] + l1), 0u);
            }
        }
        if (lane == 0) mbar_arrive(BAR(B_G3));
        STAMP(9);
        uint32_t fg[5][4], fu[5][4], tcb[12], tsb[12];
        if (role < 108) {
            mbar_wait(BAR(B_FG), 0);
#pragma unroll
            for (int s = 0; s < 5; s++) {
                const uint32_t off = sm + OFF_WG + (5 * warp + ((warp & 1) ? (s == 4 ? 0 : s + 1) : s)) * 1024 + frow * 64 + ((fh ^ ((lane >> 1) & 3)) << 4);
                ldsm4t(fg[s], off); ldsm4t(fu[s], off ^ 32);
            }
        }
#pragma unroll
        for (int s = 0; s < 3; s++) { lds4(tcb + 4 * s, ep + 192 + s * 16); lds4(tsb + 4 * s, ep + 384 + s * 16); lds4(tga + 4 * s, ep + 576 + s * 16); }
        float r0, r1;
        {
            const float2 su = lds2f(sm + OFF_EP + EP_US);
            const float Sc = su.x, U = su.y;
            uint32_t st[4][4]; int gd = 0;
            const uint4* sp = &S->stats[(tw * 8 + 2 * q) * 16 + g];
            do {
                ldg4_rlx(st[0], sp); ldg4_rlx(st[1], sp + 16); ldg4_rlx(st[2], sp + 8); ldg4_rlx(st[3], sp + 24);
            } while (__any_sync(~0u, (st[0][3] | st[1][3] | st[2][3] | st[3][3]) != 0) && ++gd < SPIN_LIMIT);
            STAMP(10);
            float v[6];
#pragma unroll
            for (int e = 0; e < 3; e++) { v[e] = __uint_as_float(st[0][e]) + __uint_as_float(st[1][e]); v[3 + e] = __uint_as_float(st[2][e]) + __uint_as_float(st[3][e]); }
#pragma unroll
            for (int e = 0; e < 6; e++) { v[e] += __shfl_xor_sync(~0u, v[e], 1); v[e] += __shfl_xor_sync(~0u, v[e], 2); }
            const float m0 = v[0] * (1.f / 640), m1 = v[3] * (1.f / 640);
            float s0 = rsqrtf(fmaxf(v[1] * (1.f / 640) - m0 * m0, 0.f) + 1e-5f), s1 = rsqrtf(fmaxf(v[4] * (1.f / 640) - m1 * m1, 0.f) + 1e-5f);
            r0 = fmaf(s0, v[2] - m0 * U, Sc); r1 = fmaf(s1, v[5] - m1 * U, Sc);
            s0 = rbf(s0); s1 = rbf(s1);
            rr0 = pack2(s0, s0); rr1 = pack2(s1, s1); nn0 = pack2(-m0 * s0, -m0 * s0); nn1 = pack2(-m1 * s1, -m1 * s1);
        }
        const uint32_t k0 = fkey(r0), k1 = fkey(r1);
        const uint32_t kmax = __reduce_max_sync(~0u, max(k0, k1));
        const int crow = __reduce_min_sync(~0u, k0 == kmax ? g : (k1 == kmax ? g + 8 : 99));
        const int tok_base = ((ti & 7) * 128 + warp * 16) * 2 + (ti >> 3);
        if (warp == j && lane < 8) stg2_rlx(&S->rec[lane * 128 + tw], kmax, tok_base + 2 * crow);
        {
            const bool up = crow >= 8;
            const uint32_t rr = up ? rr1 : rr0, nn = up ? nn1 : nn0;
            if (g == (crow & 7)) {
                uint4* cp = &S->cand[(tw * 8 + j) * 24 + q];
#pragma unroll
                for (int s = 0; s < 5; s++) {
                    const uint32_t xa_ = up ? xr[s][1] : xr[s][0], xb_ = up ? xr[s][3] : xr[s][2];
                    stg4_rlx(cp + s * 4, hf2(hf2(xa_, rr, nn), tcb[2 * s], tsb[2 * s]), hf2(hf2(xb_, rr, nn), tcb[2 * s + 1], tsb[2 * s + 1]), xa_, xb_);
                }
            }
        }
        STAMP(11);
        const int tok = tok_base + (lane >> 1) * 2;
        __nv_bfloat16* const op = out + (size_t)tok * 640 + 80 * j + (lane & 1) * 8;
        {
#pragma unroll
            for (int s = 0; s < 5; s++) {
#pragma unroll
                for (int e = 0; e < 4; e++) { const int t = 2 * s + (e >> 1); xr[s][e] = hf2(tga[t], hf2(hf2(xr[s][e], (e & 1) ? rr1 : rr0, (e & 1) ? nn1 : nn0), tcb[t], tsb[t]), xr[s][e]); }
            }
            mbar_wait(BAR(B_G2), 0);
            const uint32_t stg = sm + warp * 2816;
#pragma unroll
            for (int s = 0; s < 5; s++) stsm4(stg + (lane & 15) * VP + (odd ? (s == 4 ? 0 : s + 1) : s) * 32 + hi * 16, xr[s]);
            __syncwarp();
#pragma unroll
            for (int s = 0; s < 5; s++) lds4(xr[s], stg + (lane >> 1) * VP + (lane & 1) * 16 + s * 32);
            if ((lane >> 1) != crow) {
#pragma unroll
                for (int s = 0; s < 5; s++) *(uint4*)(op + s * 16) = make_uint4(xr[s][0], xr[s][1], xr[s][2], xr[s][3]);
            }
        }
        STAMP(12);
        mbar_wait(BAR(B_WIN), 0);
        uint32_t wv[2]; int gd = 0;
        lds2(wv, sm + OFF_EP + EP_US + 8);
        const uint32_t kwin = wv[0];
        const int tokwin = wv[1], win = (tokwin & 1) * 64 + (tokwin >> 5);
        STAMP(13);
        if (role < 108) {
            uint32_t hb[5][2];
            const uint4* cp = &S->cand[(win * 8 + warp) * 24 + q];
            do {
#pragma unroll
                for (int s = 0; s < 5; s++) ldg2_rlx(hb[s], cp + s * 4);
            } while (__any_sync(~0u, max(max(max(hb[0][0], hb[1][0]), max(hb[2][0], hb[3][0])), hb[4][0]) == SENT) && ++gd < SPIN_LIMIT);
            float dg[2][4] = {}, du[2][4] = {};
#pragma unroll
            for (int s = 0; s < 5; s++) {
                mma16(dg[s & 1], fg[s][0], fg[s][1], fg[s][2], fg[s][3], hb[s][0], hb[s][1]);
                mma16(du[s & 1], fu[s][0], fu[s][1], fu[s][2], fu[s][3], hb[s][0], hb[s][1]);
            }
            const float mine = q == 0 ? dg[0][0] + dg[1][0] : q == 1 ? dg[0][2] + dg[1][2] : q == 2 ? du[0][0] + du[1][0] : du[0][2] + du[1][2];
            sts1f(sm + OFF_RED + (warp * 32 + q * 8 + g) * 4, mine);
            bar_sync(2, 256);
            if (warp == 0) {
                float t = 0.f;
#pragma unroll
                for (int w = 0; w < 8; w++) t += lds1f(sm + OFF_RED + (w * 32 + lane) * 4);
                t = rbf(t);
                if (!(role & 1)) t *= sigm(t);
                const uint32_t pr = pack2(t, __shfl_down_sync(~0u, t, 1)), p8 = __shfl_down_sync(~0u, pr, 8);
                if (!(lane & 9)) stg2_rlx(&S->a[((role & ~1) + (lane >> 4)) * 8 + (lane & 6) + (role & 1)], pr, p8);
            }
        }
        STAMP(14);
        if (tok == tok_base + 2 * crow && tok != tokwin) {
#pragma unroll
            for (int s = 0; s < 5; s++) *(uint4*)(op + s * 16) = make_uint4(xr[s][0], xr[s][1], xr[s][2], xr[s][3]);
        }
        if (role >= 88) {
            const int d = role - 88, dj = d / 5, dm = d - dj * 5, sp = (dj & 1) ? (dm == 0 ? 4 : dm - 1) : dm;
            const int ks0 = min(warp * 14, 94);
            uint32_t fd[14][4];
            mbar_wait(BAR(B_FD), 0);
#pragma unroll
            for (int s = 0; s < 14; s++) ldsm4t(fd[s], sm + OFF_WD + (ks0 + s) * 512 + frag);
            uint32_t bsv[4], av[14][4], m;
            do {
                ldg4_rlx(bsv, &S->cand[(win * 8 + dj) * 24 + sp * 4 + q]);
#pragma unroll
                for (int s = 0; s < 14; s++) ldg4_rlx(av[s], &S->a[(ks0 + s) * 8 + q * 2]);
                m = bsv[0];
#pragma unroll
                for (int s = 0; s < 14; s++) m = max(m, max(av[s][0], av[s][2]));
            } while (__any_sync(~0u, m == SENT) && ++gd < SPIN_LIMIT);
            STAMP(15);
            float dy[4][4] = {};
#pragma unroll
            for (int s = 0; s < 14; s++) {
                if (s < 4 && warp == 7) av[s][0] = av[s][1] = av[s][2] = av[s][3] = 0u;
                mma16(dy[s & 3], fd[s][0], fd[s][1], fd[s][2], fd[s][3], hm2(av[s][0], av[s][2]), hm2(av[s][1], av[s][3]));
            }
            if (q < 2) sts1f(sm + OFF_TAB + (warp * 16 + q * 8 + g) * 4, q == 0 ? (dy[0][0] + dy[1][0]) + (dy[2][0] + dy[3][0]) : (dy[0][2] + dy[1][2]) + (dy[2][2] + dy[3][2]));
            bar_sync(2, 256);
            if (tid < 8) {
                float y0 = 0.f, y1 = 0.f;
#pragma unroll
                for (int w = 0; w < 8; w++) { const float2 v = lds2f(sm + OFF_TAB + w * 64 + tid * 8); y0 += v.x; y1 += v.y; }
                const float sg = rbf(sigm(rbf(__uint_as_float((kwin & 0x80000000u) ? kwin & 0x7fffffffu : ~kwin))));
                const uint32_t hh = tid < 4 ? bsv[0] : bsv[1], xx = tid < 4 ? bsv[2] : bsv[3];
                const uint32_t z = pack2(blo(hh) + rbf(rbf(y0) * sg), bhi(hh) + rbf(rbf(y1) * sg));
                *(uint32_t*)(out + (size_t)tokwin * 640 + d * 16 + tid * 2) = hf2(lds1(sm + OFF_EP + EP_GD + tid * 4), z, xx);
            }
        }
        STAMP(16);
    }
}

typedef CUresult (*EncFn)(CUtensorMap*, CUtensorMapDataType, cuuint32_t, void*, const cuuint64_t*, const cuuint64_t*, const cuuint32_t*, const cuuint32_t*,
                          CUtensorMapInterleave, CUtensorMapSwizzle, CUtensorMapL2promotion, CUtensorMapFloatOOBfill);
static void make_map(EncFn enc, CUtensorMap* m, const void* base, int rank, const cuuint64_t* dims, const cuuint64_t* strides, const cuuint32_t* box, CUtensorMapSwizzle sw) {
    const cuuint32_t es[5] = {1, 1, 1, 1, 1};
    enc(m, CU_TENSOR_MAP_DATA_TYPE_BFLOAT16, rank, (void*)base, dims, strides, box, es, CU_TENSOR_MAP_INTERLEAVE_NONE, sw, CU_TENSOR_MAP_L2_PROMOTION_NONE, CU_TENSOR_MAP_FLOAT_OOB_FILL_NONE);
}

extern "C" void kernel_launch(void* const* d_in, const int* in_sizes, int n_in, void* d_out, int out_size) {
    typedef const __nv_bfloat16* P;
    P x = (P)d_in[0], wqkv = (P)d_in[1], wo = (P)d_in[2], wr = (P)d_in[4], wg = (P)d_in[5], wu = (P)d_in[6], wd = (P)d_in[7], c = (P)d_in[8], wmod = (P)d_in[9];
    void* fn = nullptr; cudaDriverEntryPointQueryResult qr;
    cudaGetDriverEntryPoint("cuTensorMapEncodeTiled", &fn, cudaEnableDefault, &qr);
    EncFn enc = (EncFn)fn;
    CUtensorMap mx, mw, mt, mo, mg, mu, md, mm, mr;
    { cuuint64_t d[] = {640, 2, 1024}, s[] = {1280, 2560}; cuuint32_t b[] = {64, 1, 128}; make_map(enc, &mx, x, 3, d, s, b, CU_TENSOR_MAP_SWIZZLE_128B); }
    { cuuint64_t d[] = {32, 640, 20, 3}, s[] = {3840, 64, 1280}; cuuint32_t b[] = {32, 16, 2, 3}; make_map(enc, &mw, wqkv, 4, d, s, b, CU_TENSOR_MAP_SWIZZLE_64B); }
    { cuuint64_t d[] = {640, 640, 3}, s[] = {3840, 1280}; cuuint32_t b[] = {16, 16, 3}; make_map(enc, &mt, wqkv, 3, d, s, b, CU_TENSOR_MAP_SWIZZLE_32B); }
    { cuuint64_t d[] = {640, 640}, s[] = {1280}; cuuint32_t b[] = {32, 40}; make_map(enc, &mo, wo, 2, d, s, b, CU_TENSOR_MAP_SWIZZLE_64B); }
    { cuuint64_t d[] = {1728, 160, 4}, s[] = {3456, 3456 * 160}; cuuint32_t b[] = {32, 160, 4}; make_map(enc, &mg, wg, 3, d, s, b, CU_TENSOR_MAP_SWIZZLE_64B); make_map(enc, &mu, wu, 3, d, s, b, CU_TENSOR_MAP_SWIZZLE_64B); }
    { cuuint64_t d[] = {640, 216, 8}, s[] = {1280, 1280 * 216}; cuuint32_t b[] = {16, 216, 8}; make_map(enc, &md, wd, 3, d, s, b, CU_TENSOR_MAP_SWIZZLE_32B); }
    { cuuint64_t d[] = {3840, 160, 4}, s[] = {7680, 7680 * 160}; cuuint32_t b[] = {16, 160, 4}; make_map(enc, &mm, wmod, 3, d, s, b, CU_TENSOR_MAP_SWIZZLE_32B); }
    { cuuint64_t d[] = {64, 640, 60}, s[] = {7680, 128}; cuuint32_t b[] = {64, 32, 10}; make_map(enc, &mr, wmod, 3, d, s, b, CU_TENSOR_MAP_SWIZZLE_128B); }
    void* sp = nullptr;
    cudaGetSymbolAddress(&sp, g_s);
    cudaFuncSetAttribute(fused_kernel, cudaFuncAttributeMaxDynamicSharedMemorySize, SMEM_BYTES);
    fused_kernel<<<132, 384, SMEM_BYTES>>>(wmod, c, (Scratch*)sp, wqkv, wo, (__nv_bfloat16*)d_out, wr, wg, wu, wd, mm, mx, mw, mt, mo, mg, mu, md, mr);
}
```

```cpp
#include <cuda_runtime.h>
#include <cuda_bf16.h>
#include <cuda.h>
#include <stdint.h>

#define SPIN_LIMIT (1 << 17)

#define NCR 8
#define NCT 1
#define RPOS 0
#define RWAIT 0
#define CPF 32
#define RTB 1
#define STATV 0
#define OFFS 0
#define SWAPM 0xff
#define HPAUSE 0
#define HJOB 2
#define WGBAR 0
#define TSPLIT 0
#define XPF 0
constexpr int RV = 704;
struct __align__(4096) Exch {
    uint4 o[5 * 128 * 256];
    uint4 halo[112 * 160];
    uint4 stats[8][2056];
    uint4 cand[8][128 * 20 + 8];
    uint4 ra[64][24];
    uint4 pad[128 * RV - (128 * 256 + 112 * 160 + 8 * 2056 + 8 * (128 * 20 + 8) + 64 * 24)];
};
struct __align__(4096) Scratch {
    Exch x;
    uint4 tab[60][72];
    unsigned cnt;
};
__device__ Scratch g_s;
#define STAMP(n)
#define GSTAMP(n)
#define STAMPT(n, t)

constexpr uint32_t OFF_W = 163840, WST = 15360;
constexpr uint32_t OFF_WM = OFF_W + 2 * WST;
constexpr uint32_t OFF_FF = OFF_WM + 20480;
constexpr uint32_t OFF_P8 = 131072, VP = 176;
constexpr uint32_t OFF_WD = 129024, OFF_WG = 184320;
constexpr uint32_t OFF_TAB = 225280;
constexpr uint32_t OFF_RED = OFF_TAB + 2560;
constexpr uint32_t OFF_EP = OFF_TAB + 4096;
constexpr uint32_t EP_GD = 1344, EP_US = 1376;
constexpr uint32_t OFF_BAR = OFF_EP + 1424;
constexpr uint32_t OFF_PROF = OFF_BAR + 640;
constexpr uint32_t SMEM_BYTES = OFF_PROF + 128;
enum { B_XF = 0, B_WF = 10, B_WO0 = 30, B_WO, B_FG, B_FD, B_TB, B_HL = B_TB + 4, B_G0 = B_HL + 8, B_RDY, B_WIN, B_EP, B_EP2, B_EP3, B_G2, B_G3, B_G4, B_WE = 55, B_T0 = B_WE + 19 };
#define ALIGNED 1
#define WO_MASK 0x1f5000
#define P_TAB 100
#define P_REC 0
#define P_ST 0
#define P_A 0
#define RDELAY 600
#define OUTPOS2 1
#define EARLY_RST 0
#define OUTPOS 0
#define LAG 2
#define NOPF 0
#define SDELAY 1200
#define XWAIT 2
#define PFMAP 0
#define WLATE 0
#define SPLIT 1
#define P_O 0
#define P_H 0
#define LATE1 1
#define EARLY_LD 5
#define FD_AT 2
#define GU_MASK 0xaa00
#define TB_GO (B_WE + 16)
#define TB_GO2 B_G2
#define TDELAY 3900
#define PFN 5
#define PF0 1
#define RDY_AT 8
#define YSLEEP 300
#define MDELAY 2000
#define MPF 2
#define MPF0 6
#define XDELAY 600
#define RSLEEP 40
#define HALO_GO B_G0
constexpr uint32_t SM0 = 1024;
#define BAR0(i) (SM0 + OFF_BAR + 8 * (i))
#define BAR(i) (sm + OFF_BAR + 8 * (i))

__device__ __forceinline__ uint32_t smem_u32(const void* p) { return (uint32_t)__cvta_generic_to_shared(p); }
__device__ __forceinline__ void mbar_init(uint32_t b, int cnt) { asm volatile("mbarrier.init.shared::cta.b64 [%0], %1;" ::"r"(b), "r"(cnt) : "memory"); }
__device__ __forceinline__ void mbar_expect_tx(uint32_t b, uint32_t bytes) { asm volatile("mbarrier.arrive.expect_tx.shared::cta.b64 _, [%0], %1;" ::"r"(b), "r"(bytes) : "memory"); }
__device__ __forceinline__ void mbar_arrive(uint32_t b) { asm volatile("mbarrier.arrive.shared::cta.b64 _, [%0];" ::"r"(b) : "memory"); }
__device__ __forceinline__ bool mbar_try(uint32_t b, uint32_t par) {
    uint32_t ok;
    asm volatile("{.reg .pred p; mbarrier.try_wait.parity.shared::cta.b64 p, [%1], %2; selp.u32 %0, 1, 0, p;}" : "=r"(ok) : "r"(b), "r"(par) : "memory");
    return ok;
}
__device__ __forceinline__ void mbar_wait(uint32_t b, uint32_t par) {
    asm volatile("{.reg .pred p;\nW: mbarrier.try_wait.parity.shared::cta.b64 p, [%0], %1;\n@!p bra W;}" ::"r"(b), "r"(par) : "memory");
}
__device__ __forceinline__ void bar_sync(int id, int n) { asm volatile("bar.sync %0, %1;" ::"r"(id), "r"(n) : "memory"); }
__device__ __forceinline__ void tma2d(uint32_t dst, const CUtensorMap* m, int c0, int c1, uint32_t bar) {
    asm volatile("cp.async.bulk.tensor.2d.shared::cluster.global.mbarrier::complete_tx::bytes [%0], [%1, {%3, %4}], [%2];" ::"r"(dst), "l"(m), "r"(bar), "r"(c0), "r"(c1) : "memory");
}
__device__ __forceinline__ void tma3d(uint32_t dst, const CUtensorMap* m, int c0, int c1, int c2, uint32_t bar) {
    asm volatile("cp.async.bulk.tensor.3d.shared::cluster.global.mbarrier::complete_tx::bytes [%0], [%1, {%3, %4, %5}], [%2];" ::"r"(dst), "l"(m), "r"(bar), "r"(c0), "r"(c1), "r"(c2) : "memory");
}
__device__ __forceinline__ void tma4d(uint32_t dst, const CUtensorMap* m, int c0, int c1, int c2, int c3, uint32_t bar) {
    asm volatile("cp.async.bulk.tensor.4d.shared::cluster.global.mbarrier::complete_tx::bytes [%0], [%1, {%3, %4, %5, %6}], [%2];" ::"r"(dst), "l"(m), "r"(bar), "r"(c0), "r"(c1), "r"(c2), "r"(c3) : "memory");
}
__device__ __forceinline__ void l2_prefetch(const void* p, uint32_t bytes) { asm volatile("cp.async.bulk.prefetch.L2.global [%0], %1;" ::"l"(p), "r"(bytes) : "memory"); }
__device__ __forceinline__ void pf_map(const CUtensorMap* m) { asm volatile("prefetch.tensormap [%0];" ::"l"(m) : "memory"); }
__device__ __forceinline__ void wg_fence() { asm volatile("wgmma.fence.sync.aligned;" ::: "memory"); }
__device__ __forceinline__ void wg_commit() { asm volatile("wgmma.commit_group.sync.aligned;" ::: "memory"); }
template <int N> __device__ __forceinline__ void wg_wait() { asm volatile("wgmma.wait_group.sync.aligned %0;" ::"n"(N) : "memory"); }
__device__ __forceinline__ void ldsm4(uint32_t* r, uint32_t addr) { asm volatile("ldmatrix.sync.aligned.m8n8.x4.shared.b16 {%0,%1,%2,%3}, [%4];" : "=r"(r[0]), "=r"(r[1]), "=r"(r[2]), "=r"(r[3]) : "r"(addr) : "memory"); }
__device__ __forceinline__ void ldsm4t(uint32_t* r, uint32_t addr) { asm volatile("ldmatrix.sync.aligned.m8n8.x4.trans.shared.b16 {%0,%1,%2,%3}, [%4];" : "=r"(r[0]), "=r"(r[1]), "=r"(r[2]), "=r"(r[3]) : "r"(addr) : "memory"); }
__device__ __forceinline__ void stsm4(uint32_t addr, const uint32_t* r) { asm volatile("stmatrix.sync.aligned.m8n8.x4.shared.b16 [%4], {%0,%1,%2,%3};" ::"r"(r[0]), "r"(r[1]), "r"(r[2]), "r"(r[3]), "r"(addr) : "memory"); }
__device__ __forceinline__ void lds4(uint32_t* r, uint32_t addr) { asm volatile("ld.shared.v4.u32 {%0,%1,%2,%3}, [%4];" : "=r"(r[0]), "=r"(r[1]), "=r"(r[2]), "=r"(r[3]) : "r"(addr) : "memory"); }
__device__ __forceinline__ void sts4(uint32_t addr, const uint32_t* r) { asm volatile("st.shared.v4.u32 [%4], {%0,%1,%2,%3};" ::"r"(r[0]), "r"(r[1]), "r"(r[2]), "r"(r[3]), "r"(addr) : "memory"); }
__device__ __forceinline__ float2 lds2f(uint32_t addr) { float2 v; asm volatile("ld.shared.v2.f32 {%0,%1}, [%2];" : "=f"(v.x), "=f"(v.y) : "r"(addr) : "memory"); return v; }
__device__ __forceinline__ float lds1f(uint32_t addr) { float v; asm volatile("ld.shared.f32 %0, [%1];" : "=f"(v) : "r"(addr) : "memory"); return v; }
__device__ __forceinline__ void sts1f(uint32_t addr, float v) { asm volatile("st.shared.f32 [%0], %1;" ::"r"(addr), "f"(v) : "memory"); }
__device__ __forceinline__ void sts1(uint32_t addr, uint32_t v) { asm volatile("st.shared.u32 [%0], %1;" ::"r"(addr), "r"(v) : "memory"); }
__device__ __forceinline__ void ldg4_rlx(uint32_t* r, const void* p) { asm volatile("{.reg .b128 t; ld.relaxed.gpu.global.b128 t, [%4]; mov.b128 {%0,%1,%2,%3}, t;}" : "=r"(r[0]), "=r"(r[1]), "=r"(r[2]), "=r"(r[3]) : "l"(p) : "memory"); }
__device__ __forceinline__ void ldg2_rlx(uint32_t* r, const void* p) { asm volatile("{.reg .b64 t; ld.relaxed.gpu.global.b64 t, [%2]; mov.b64 {%0,%1}, t;}" : "=r"(r[0]), "=r"(r[1]) : "l"(p) : "memory"); }
__device__ __forceinline__ uint32_t ldg1_rlx(const void* p) { uint32_t v; asm volatile("ld.relaxed.gpu.global.u32 %0, [%1];" : "=r"(v) : "l"(p) : "memory"); return v; }
__device__ __forceinline__ void stg4_rlx(void* p, uint32_t a, uint32_t b, uint32_t c, uint32_t d) { asm volatile("{.reg .b128 t; mov.b128 t, {%1,%2,%3,%4}; st.relaxed.gpu.global.b128 [%0], t;}" ::"l"(p), "r"(a), "r"(b), "r"(c), "r"(d) : "memory"); }
__device__ __forceinline__ void stg2_rlx(void* p, uint32_t a, uint32_t b) { asm volatile("{.reg .b64 t; mov.b64 t, {%1,%2}; st.relaxed.gpu.global.b64 [%0], t;}" ::"l"(p), "r"(a), "r"(b) : "memory"); }
__device__ __forceinline__ void stg1_rlx(void* p, uint32_t a) { asm volatile("st.relaxed.gpu.global.u32 [%0], %1;" ::"l"(p), "r"(a) : "memory"); }
__device__ __forceinline__ void ldg4_nc(uint32_t* r, const void* p) { asm volatile("ld.global.nc.L1::no_allocate.v4.u32 {%0,%1,%2,%3}, [%4];" : "=r"(r[0]), "=r"(r[1]), "=r"(r[2]), "=r"(r[3]) : "l"(p)); }
__device__ __forceinline__ uint64_t mkdesc(uint32_t addr, uint32_t lbo, uint32_t sbo, uint32_t sw) { return (uint64_t)((addr & 0x3FFFF) >> 4) | ((uint64_t)(lbo >> 4) << 16) | ((uint64_t)(sbo >> 4) << 32) | ((uint64_t)sw << 62); }
__device__ __forceinline__ uint32_t pack2(float lo, float hi) { uint32_t r; asm("cvt.rn.bf16x2.f32 %0, %1, %2;" : "=r"(r) : "f"(hi), "f"(lo)); return r; }
__device__ __forceinline__ float blo(uint32_t v) { return __uint_as_float(v << 16); }
__device__ __forceinline__ float bhi(uint32_t v) { return __uint_as_float(v & 0xffff0000u); }
__device__ __forceinline__ float rbf(float x) { return blo(pack2(x, 0.f)); }
__device__ __forceinline__ uint32_t hf2(uint32_t a, uint32_t b, uint32_t c) { uint32_t r; asm("fma.rn.bf16x2 %0, %1, %2, %3;" : "=r"(r) : "r"(a), "r"(b), "r"(c)); return r; }
__device__ __forceinline__ uint32_t movm(uint32_t a) { uint32_t r; asm volatile("movmatrix.sync.aligned.m8n8.trans.b16 %0, %1;" : "=r"(r) : "r"(a)); return r; }
__device__ __forceinline__ float ex2(float x) { float r; asm("ex2.approx.ftz.f32 %0, %1;" : "=f"(r) : "f"(x)); return r; }
__device__ __forceinline__ void mma16(float* d, uint32_t a0, uint32_t a1, uint32_t a2, uint32_t a3, uint32_t b0, uint32_t b1) {
    asm("mma.sync.aligned.m16n8k16.row.col.f32.bf16.bf16.f32 {%0,%1,%2,%3}, {%4,%5,%6,%7}, {%8,%9}, {%0,%1,%2,%3};"
                 : "+f"(d[0]), "+f"(d[1]), "+f"(d[2]), "+f"(d[3]) : "r"(a0), "r"(a1), "r"(a2), "r"(a3), "r"(b0), "r"(b1));
}
__device__ __forceinline__ void mma8(float* d, uint32_t a0, uint32_t a1, uint32_t b0) {
    asm("mma.sync.aligned.m16n8k8.row.col.f32.bf16.bf16.f32 {%0,%1,%2,%3}, {%4,%5}, {%6}, {%0,%1,%2,%3};"
                 : "+f"(d[0]), "+f"(d[1]), "+f"(d[2]), "+f"(d[3]) : "r"(a0), "r"(a1), "r"(b0));
}
__device__ __forceinline__ uint32_t umax4(const uint32_t* v, uint32_t m) { return max(max(max(v[0], v[1]), max(v[2], v[3])), m); }
__device__ __forceinline__ uint32_t fkey(float f) { const uint32_t u = __float_as_uint(f); return u ^ (((int)u >> 31) | 0x80000000u); }
__device__ __forceinline__ float rcp(float x) { float r; asm("rcp.approx.ftz.f32 %0, %1;" : "=f"(r) : "f"(x)); return r; }
__device__ __forceinline__ float sigm(float x) { return rcp(1.f + ex2(x * -1.4426950408889634f)); }
__device__ __forceinline__ void mma16c(float* d, uint32_t a0, uint32_t a1, uint32_t a2, uint32_t a3, uint32_t b0, uint32_t b1, float c0, float c1) {
    asm("mma.sync.aligned.m16n8k16.row.col.f32.bf16.bf16.f32 {%0,%1,%2,%3}, {%4,%5,%6,%7}, {%8,%9}, {%10,%11,%12,%12};"
                 : "=f"(d[0]), "=f"(d[1]), "=f"(d[2]), "=f"(d[3]) : "r"(a0), "r"(a1), "r"(a2), "r"(a3), "r"(b0), "r"(b1), "f"(c0), "f"(c1), "f"(0.f));
}
__device__ __forceinline__ void ldsm2t(uint32_t* r, uint32_t addr) { asm volatile("ldmatrix.sync.aligned.m8n8.x2.trans.shared.b16 {%0,%1}, [%2];" : "=r"(r[0]), "=r"(r[1]) : "r"(addr) : "memory"); }
__device__ __forceinline__ void stsm2(uint32_t addr, uint32_t a, uint32_t b) { asm volatile("stmatrix.sync.aligned.m8n8.x2.shared.b16 [%2], {%0,%1};" ::"r"(a), "r"(b), "r"(addr) : "memory"); }
__device__ __forceinline__ void lds2(uint32_t* r, uint32_t addr) { asm volatile("ld.shared.v2.u32 {%0,%1}, [%2];" : "=r"(r[0]), "=r"(r[1]) : "r"(addr) : "memory"); }
__device__ __forceinline__ void sts2(uint32_t addr, uint32_t a, uint32_t b) { asm volatile("st.shared.v2.u32 [%2], {%0,%1};" ::"r"(a), "r"(b), "r"(addr) : "memory"); }
__device__ __forceinline__ void sts16(uint32_t addr, uint32_t v) { asm volatile("st.shared.u16 [%0], %1;" ::"r"(addr), "h"((unsigned short)v) : "memory"); }
__device__ __forceinline__ uint32_t lds1(uint32_t addr) { uint32_t v; asm volatile("ld.shared.u32 %0, [%1];" : "=r"(v) : "r"(addr) : "memory"); return v; }
__device__ __forceinline__ bool elect1() { uint32_t p; asm volatile("{.reg .pred P; elect.sync _|P, 0xffffffff; selp.u32 %0, 1, 0, P;}" : "=r"(p)); return p; }
__device__ __forceinline__ void tma2d_mc(uint32_t dst, const CUtensorMap* m, int c0, int c1, uint32_t bar) {
    asm volatile("cp.async.bulk.tensor.2d.shared::cluster.global.mbarrier::complete_tx::bytes.multicast::cluster [%0], [%1, {%3, %4}], [%2], %5;" ::"r"(dst), "l"(m), "r"(bar), "r"(c0), "r"(c1), "h"((unsigned short)3) : "memory");
}
__device__ __forceinline__ void tma3d_mc(uint32_t dst, const CUtensorMap* m, int c0, int c1, int c2, uint32_t bar) {
    asm volatile("cp.async.bulk.tensor.3d.shared::cluster.global.mbarrier::complete_tx::bytes.multicast::cluster [%0], [%1, {%3, %4, %5}], [%2], %6;" ::"r"(dst), "l"(m), "r"(bar), "r"(c0), "r"(c1), "r"(c2), "h"((unsigned short)3) : "memory");
}
__device__ __forceinline__ void tma4d_mc(uint32_t dst, const CUtensorMap* m, int c0, int c1, int c2, int c3, uint32_t bar) {
    asm volatile("cp.async.bulk.tensor.4d.shared::cluster.global.mbarrier::complete_tx::bytes.multicast::cluster [%0], [%1, {%3, %4, %5, %6}], [%2], %7;" ::"r"(dst), "l"(m), "r"(bar), "r"(c0), "r"(c1), "r"(c2), "r"(c3), "h"((unsigned short)3) : "memory");
}
__device__ __forceinline__ void mbar_arrive_cl(uint32_t b) { asm volatile("mbarrier.arrive.shared::cluster.b64 _, [%0];" ::"r"(b) : "memory"); }
__device__ __forceinline__ uint32_t hm2(uint32_t a, uint32_t b) { uint32_t r; asm("mul.rn.bf16x2 %0, %1, %2;" : "=r"(r) : "r"(a), "r"(b)); return r; }
__device__ __forceinline__ uint32_t clock32() { uint32_t c; asm volatile("mov.u32 %0, %clock;" : "=r"(c)); return c; }
__device__ __forceinline__ uint32_t ldsm1(uint32_t addr) { uint32_t r; asm volatile("ldmatrix.sync.aligned.m8n8.x1.shared.b16 {%0}, [%1];" : "=r"(r) : "r"(addr) : "memory"); return r; }
__device__ __forceinline__ float rsq(float x) { float r; asm("rsqrt.approx.ftz.f32 %0, %1;" : "=f"(r) : "f"(x)); return r; }
__device__ __forceinline__ void pause_until(uint32_t t0, uint32_t n) {
    asm volatile("{.reg .pred p; .reg .u32 t;\nP: mov.u32 t, %clock; sub.u32 t, t, %0; setp.lt.u32 p, t, %1;\n@p bra.uni P;}" ::"r"(t0), "r"(n) : "memory");
}
__device__ __forceinline__ void pause(uint32_t n) { if (n) { const uint32_t t = clock32(); while (clock32() - t < n) {} } }
__device__ __forceinline__ uint32_t wbuf(int it) {
    const uint32_t v = it < 4 ? it + 8 : (uint32_t)(0x8302418302b1a908ull >> (4 * it - 16)) & 15;
    return v * WST + (v >> 3) * (OFF_W - 8 * WST);
}
__device__ __forceinline__ uint32_t wobuf(int w) { return ((0x30241765u >> (4 * w)) & 7) * WST; }
__device__ __forceinline__ uint32_t inc(uint32_t v) { uint32_t r; asm volatile("{.reg .u32 t; or.b32 t, %1, 255; add.u32 %0, t, 1;}" : "=r"(r) : "r"(v)); return r; }
__device__ __forceinline__ uint32_t ldg1_acq(const void* p) { uint32_t v; asm volatile("ld.acquire.gpu.global.u32 %0, [%1];" : "=r"(v) : "l"(p) : "memory"); return v; }
__device__ __forceinline__ void tma3d_st(const CUtensorMap* m, int c0, int c1, int c2, uint32_t src) {
    asm volatile("cp.async.bulk.tensor.3d.global.shared::cta.bulk_group [%0, {%2, %3, %4}], [%1];" ::"l"(m), "r"(src), "r"(c0), "r"(c1), "r"(c2) : "memory");
}
__device__ __forceinline__ uint32_t nz(uint32_t v) { uint32_t r; asm("max.u32 %0, %1, 1;" : "=r"(r) : "r"(v)); return r; }
__device__ __forceinline__ uint32_t tagw(uint32_t w, uint32_t tc) { return ((w & 0x8000ffffu) | min(max(w & 0x7fff0000u, 0x20000000u), 0x5fff0000u)) + tc; }
template <int S_> __device__ __forceinline__ void await7(uint32_t (*r)[4], const char* const* p, uint32_t fz, uint32_t stale) {
    if (S_ == 0) asm volatile("{.reg .b128 t; .reg .pred p; .reg .u32 m, k, n;\nmov.u32 n, %clock; or.b32 n, n, %37; shr.u32 n, n, 31;\nL:\n"
        "min.u32 m, %0, %4; min.u32 m, m, %8; min.u32 m, m, %12; min.u32 m, m, %16; min.u32 m, m, %20; min.u32 m, m, %24;\n"
        "setp.eq.u32 p, m, 0; vote.sync.any.pred p, p, 0xffffffff; add.u32 n, n, 1; setp.lt.and.u32 p, n, %36, p;\n@!p bra.uni D;\n"
        "setp.eq.u32 p, %0, 0; mov.b128 t, {%0,%1,%2,%3}; @p ld.relaxed.gpu.global.b128 t, [%28+%35]; mov.b128 {%0,%1,%2,%3}, t;\n"
        "setp.eq.u32 p, %4, 0; mov.b128 t, {%4,%5,%6,%7}; @p ld.relaxed.gpu.global.b128 t, [%29+%35]; mov.b128 {%4,%5,%6,%7}, t;\n"
        "setp.eq.u32 p, %8, 0; mov.b128 t, {%8,%9,%10,%11}; @p ld.relaxed.gpu.global.b128 t, [%30+%35]; mov.b128 {%8,%9,%10,%11}, t;\n"
        "setp.eq.u32 p, %12, 0; mov.b128 t, {%12,%13,%14,%15}; @p ld.relaxed.gpu.global.b128 t, [%31+%35]; mov.b128 {%12,%13,%14,%15}, t;\n"
        "setp.eq.u32 p, %16, 0; mov.b128 t, {%16,%17,%18,%19}; @p ld.relaxed.gpu.global.b128 t, [%32+%35]; mov.b128 {%16,%17,%18,%19}, t;\n"
        "setp.eq.u32 p, %20, 0; mov.b128 t, {%20,%21,%22,%23}; @p ld.relaxed.gpu.global.b128 t, [%33+%35]; mov.b128 {%20,%21,%22,%23}, t;\n"
        "setp.eq.u32 p, %24, 0; mov.b128 t, {%24,%25,%26,%27}; @p ld.relaxed.gpu.global.b128 t, [%34+%35]; mov.b128 {%24,%25,%26,%27}, t;\n"
        "bra.uni L;\nD:}"
        : "+r"(r[0][0]), "+r"(r[0][1]), "+r"(r[0][2]), "+r"(r[0][3]), "+r"(r[1][0]), "+r"(r[1][1]), "+r"(r[1][2]), "+r"(r[1][3]), "+r"(r[2][0]), "+r"(r[2][1]), "+r"(r[2][2]), "+r"(r[2][3]), "+r"(r[3][0]), "+r"(r[3][1]), "+r"(r[3][2]), "+r"(r[3][3]), "+r"(r[4][0]), "+r"(r[4][1]), "+r"(r[4][2]), "+r"(r[4][3]), "+r"(r[5][0]), "+r"(r[5][1]), "+r"(r[5][2]), "+r"(r[5][3]), "+r"(r[6][0]), "+r"(r[6][1]), "+r"(r[6][2]), "+r"(r[6][3])
        : "l"(p[0]), "l"(p[1]), "l"(p[2]), "l"(p[3]), "l"(p[4]), "l"(p[5]), "l"(p[6]), "n"((4 - S_) * 524288), "n"(SPIN_LIMIT), "r"(fz), "r"(stale) : "memory");
    else asm volatile("{.reg .b128 t; .reg .pred p; .reg .u32 m, k, n;\nmov.u32 n, %clock; or.b32 n, n, %37; shr.u32 n, n, 31;\nL:\n"
        "xor.b32 m, %0, %38; xor.b32 k, %4, %38; and.b32 m, m, k; xor.b32 k, %8, %38; and.b32 m, m, k; xor.b32 k, %12, %38; and.b32 m, m, k; xor.b32 k, %16, %38; and.b32 m, m, k;\n"
        "xor.b32 k, %20, %38; and.b32 m, m, k; xor.b32 k, %24, %38; and.b32 m, m, k; and.b32 m, m, 0x40000000;\n"
        "setp.eq.u32 p, m, 0; vote.sync.any.pred p, p, 0xffffffff; add.u32 n, n, 1; setp.lt.and.u32 p, n, %36, p;\n@!p bra.uni D;\n"
        "xor.b32 k, %0, %38; and.b32 k, k, 0x40000000; setp.eq.u32 p, k, 0; mov.b128 t, {%0,%1,%2,%3}; @p ld.relaxed.gpu.global.b128 t, [%28+%35]; mov.b128 {%0,%1,%2,%3}, t;\n"
        "xor.b32 k, %4, %38; and.b32 k, k, 0x40000000; setp.eq.u32 p, k, 0; mov.b128 t, {%4,%5,%6,%7}; @p ld.relaxed.gpu.global.b128 t, [%29+%35]; mov.b128 {%4,%5,%6,%7}, t;\n"
        "xor.b32 k, %8, %38; and.b32 k, k, 0x40000000; setp.eq.u32 p, k, 0; mov.b128 t, {%8,%9,%10,%11}; @p ld.relaxed.gpu.global.b128 t, [%30+%35]; mov.b128 {%8,%9,%10,%11}, t;\n"
        "xor.b32 k, %12, %38; and.b32 k, k, 0x40000000; setp.eq.u32 p, k, 0; mov.b128 t, {%12,%13,%14,%15}; @p ld.relaxed.gpu.global.b128 t, [%31+%35]; mov.b128 {%12,%13,%14,%15}, t;\n"
        "xor.b32 k, %16, %38; and.b32 k, k, 0x40000000; setp.eq.u32 p, k, 0; mov.b128 t, {%16,%17,%18,%19}; @p ld.relaxed.gpu.global.b128 t, [%32+%35]; mov.b128 {%16,%17,%18,%19}, t;\n"
        "xor.b32 k, %20, %38; and.b32 k, k, 0x40000000; setp.eq.u32 p, k, 0; mov.b128 t, {%20,%21,%22,%23}; @p ld.relaxed.gpu.global.b128 t, [%33+%35]; mov.b128 {%20,%21,%22,%23}, t;\n"
        "xor.b32 k, %24, %38; and.b32 k, k, 0x40000000; setp.eq.u32 p, k, 0; mov.b128 t, {%24,%25,%26,%27}; @p ld.relaxed.gpu.global.b128 t, [%34+%35]; mov.b128 {%24,%25,%26,%27}, t;\n"
        "bra.uni L;\nD:}"
        : "+r"(r[0][0]), "+r"(r[0][1]), "+r"(r[0][2]), "+r"(r[0][3]), "+r"(r[1][0]), "+r"(r[1][1]), "+r"(r[1][2]), "+r"(r[1][3]), "+r"(r[2][0]), "+r"(r[2][1]), "+r"(r[2][2]), "+r"(r[2][3]), "+r"(r[3][0]), "+r"(r[3][1]), "+r"(r[3][2]), "+r"(r[3][3]), "+r"(r[4][0]), "+r"(r[4][1]), "+r"(r[4][2]), "+r"(r[4][3]), "+r"(r[5][0]), "+r"(r[5][1]), "+r"(r[5][2]), "+r"(r[5][3]), "+r"(r[6][0]), "+r"(r[6][1]), "+r"(r[6][2]), "+r"(r[6][3])
        : "l"(p[0]), "l"(p[1]), "l"(p[2]), "l"(p[3]), "l"(p[4]), "l"(p[5]), "l"(p[6]), "n"((4 - S_) * 524288), "n"(SPIN_LIMIT), "r"(fz), "r"(stale) : "memory");
}
template <class T> __device__ __forceinline__ T* pinp(T* p) { return (T*)__shfl_xor_sync(~0u, (unsigned long long)p, 0); }
__device__ __forceinline__ float fsel(bool c, float a, float b) { float r; asm("{.reg .pred p; setp.ne.u32 p, %3, 0; selp.f32 %0, %1, %2, p;}" : "=f"(r) : "f"(a), "f"(b), "r"((int)c)); return r; }
__device__ __forceinline__ void stg4_if(bool c, void* p, uint32_t a, uint32_t b, uint32_t d, uint32_t e) {
    asm volatile("{.reg .b128 t; .reg .pred p; setp.ne.u32 p, %5, 0; mov.b128 t, {%1,%2,%3,%4}; @p st.relaxed.gpu.global.b128 [%0], t;}" ::"l"(p), "r"(a), "r"(b), "r"(d), "r"(e), "r"((int)c) : "memory");
}
__device__ __forceinline__ void stg2_if(bool c, void* p, uint32_t a, uint32_t b) {
    asm volatile("{.reg .b64 t; .reg .pred p; setp.ne.u32 p, %3, 0; mov.b64 t, {%1,%2}; @p st.relaxed.gpu.global.b64 [%0], t;}" ::"l"(p), "r"(a), "r"(b), "r"((int)c) : "memory");
}
__device__ __forceinline__ void stg1_if(bool c, void* p, uint32_t a) {
    asm volatile("{.reg .pred p; setp.ne.u32 p, %2, 0; @p st.relaxed.gpu.global.u32 [%0], %1;}" ::"l"(p), "r"(a), "r"((int)c) : "memory");
}
__device__ __forceinline__ void wgmma_rs_n192(float* d, const uint32_t* a, uint64_t bdesc, int accum) {
    asm volatile("{.reg .pred p; setp.ne.b32 p, %101, 0; wgmma.mma_async.sync.aligned.m64n192k16.f32.bf16.bf16 {%0,%1,%2,%3,%4,%5,%6,%7,%8,%9,%10,%11,%12,%13,%14,%15,%16,%17,%18,%19,%20,%21,%22,%23,%24,%25,%26,%27,%28,%29,%30,%31,%32,%33,%34,%35,%36,%37,%38,%39,%40,%41,%42,%43,%44,%45,%46,%47,%48,%49,%50,%51,%52,%53,%54,%55,%56,%57,%58,%59,%60,%61,%62,%63,%64,%65,%66,%67,%68,%69,%70,%71,%72,%73,%74,%75,%76,%77,%78,%79,%80,%81,%82,%83,%84,%85,%86,%87,%88,%89,%90,%91,%92,%93,%94,%95}, {%96,%97,%98,%99}, %100, p, 1, 1, 1;}"
        : "+f"(d[0]),"+f"(d[1]),"+f"(d[2]),"+f"(d[3]),"+f"(d[4]),"+f"(d[5]),"+f"(d[6]),"+f"(d[7]),"+f"(d[8]),"+f"(d[9]),"+f"(d[10]),"+f"(d[11]),"+f"(d[12]),"+f"(d[13]),"+f"(d[14]),"+f"(d[15]),"+f"(d[16]),"+f"(d[17]),"+f"(d[18]),"+f"(d[19]),"+f"(d[20]),"+f"(d[21]),"+f"(d[22]),"+f"(d[23]),"+f"(d[24]),"+f"(d[25]),"+f"(d[26]),"+f"(d[27]),"+f"(d[28]),"+f"(d[29]),"+f"(d[30]),"+f"(d[31]),"+f"(d[32]),"+f"(d[33]),"+f"(d[34]),"+f"(d[35]),"+f"(d[36]),"+f"(d[37]),"+f"(d[38]),"+f"(d[39]),"+f"(d[40]),"+f"(d[41]),"+f"(d[42]),"+f"(d[43]),"+f"(d[44]),"+f"(d[45]),"+f"(d[46]),"+f"(d[47]),"+f"(d[48]),"+f"(d[49]),"+f"(d[50]),"+f"(d[51]),"+f"(d[52]),"+f"(d[53]),"+f"(d[54]),"+f"(d[55]),"+f"(d[56]),"+f"(d[57]),"+f"(d[58]),"+f"(d[59]),"+f"(d[60]),"+f"(d[61]),"+f"(d[62]),"+f"(d[63]),"+f"(d[64]),"+f"(d[65]),"+f"(d[66]),"+f"(d[67]),"+f"(d[68]),"+f"(d[69]),"+f"(d[70]),"+f"(d[71]),"+f"(d[72]),"+f"(d[73]),"+f"(d[74]),"+f"(d[75]),"+f"(d[76]),"+f"(d[77]),"+f"(d[78]),"+f"(d[79]),"+f"(d[80]),"+f"(d[81]),"+f"(d[82]),"+f"(d[83]),"+f"(d[84]),"+f"(d[85]),"+f"(d[86]),"+f"(d[87]),"+f"(d[88]),"+f"(d[89]),"+f"(d[90]),"+f"(d[91]),"+f"(d[92]),"+f"(d[93]),"+f"(d[94]),"+f"(d[95])
        : "r"(a[0]), "r"(a[1]), "r"(a[2]), "r"(a[3]), "l"(bdesc), "r"(accum));
}
__device__ __forceinline__ void wgmma_rs_n48(float* d, const uint32_t* a, uint64_t bdesc, int accum) {
    asm volatile("{.reg .pred p; setp.ne.b32 p, %29, 0; wgmma.mma_async.sync.aligned.m64n48k16.f32.bf16.bf16 {%0,%1,%2,%3,%4,%5,%6,%7,%8,%9,%10,%11,%12,%13,%14,%15,%16,%17,%18,%19,%20,%21,%22,%23}, {%24,%25,%26,%27}, %28, p, 1, 1, 1;}"
        : "+f"(d[0]),"+f"(d[1]),"+f"(d[2]),"+f"(d[3]),"+f"(d[4]),"+f"(d[5]),"+f"(d[6]),"+f"(d[7]),"+f"(d[8]),"+f"(d[9]),"+f"(d[10]),"+f"(d[11]),"+f"(d[12]),"+f"(d[13]),"+f"(d[14]),"+f"(d[15]),"+f"(d[16]),"+f"(d[17]),"+f"(d[18]),"+f"(d[19]),"+f"(d[20]),"+f"(d[21]),"+f"(d[22]),"+f"(d[23])
        : "r"(a[0]), "r"(a[1]), "r"(a[2]), "r"(a[3]), "l"(bdesc), "r"(accum));
}
__device__ __forceinline__ void wgmma_rs_n80(float* d, const uint32_t* a, uint64_t bdesc, int accum) {
    asm volatile("{.reg .pred p; setp.ne.b32 p, %45, 0; wgmma.mma_async.sync.aligned.m64n80k16.f32.bf16.bf16 {%0,%1,%2,%3,%4,%5,%6,%7,%8,%9,%10,%11,%12,%13,%14,%15,%16,%17,%18,%19,%20,%21,%22,%23,%24,%25,%26,%27,%28,%29,%30,%31,%32,%33,%34,%35,%36,%37,%38,%39}, {%40,%41,%42,%43}, %44, p, 1, 1, 1;}"
        : "+f"(d[0]),"+f"(d[1]),"+f"(d[2]),"+f"(d[3]),"+f"(d[4]),"+f"(d[5]),"+f"(d[6]),"+f"(d[7]),"+f"(d[8]),"+f"(d[9]),"+f"(d[10]),"+f"(d[11]),"+f"(d[12]),"+f"(d[13]),"+f"(d[14]),"+f"(d[15]),"+f"(d[16]),"+f"(d[17]),"+f"(d[18]),"+f"(d[19]),"+f"(d[20]),"+f"(d[21]),"+f"(d[22]),"+f"(d[23]),"+f"(d[24]),"+f"(d[25]),"+f"(d[26]),"+f"(d[27]),"+f"(d[28]),"+f"(d[29]),"+f"(d[30]),"+f"(d[31]),"+f"(d[32]),"+f"(d[33]),"+f"(d[34]),"+f"(d[35]),"+f"(d[36]),"+f"(d[37]),"+f"(d[38]),"+f"(d[39])
        : "r"(a[0]), "r"(a[1]), "r"(a[2]), "r"(a[3]), "l"(bdesc), "r"(accum));
}

__global__ void __cluster_dims__(2, 1, 1) __launch_bounds__(384, 1)
fused_kernel(const __nv_bfloat16* __restrict__ xin, const __nv_bfloat16* __restrict__ wmod, const __nv_bfloat16* __restrict__ cvec, Scratch* __restrict__ S,
             const __nv_bfloat16* __restrict__ wqkv, const __nv_bfloat16* __restrict__ wo, __nv_bfloat16* __restrict__ out,
             const __nv_bfloat16* __restrict__ wr, const __nv_bfloat16* __restrict__ wg, const __nv_bfloat16* __restrict__ wu,
             const __nv_bfloat16* __restrict__ wd,
             const __grid_constant__ CUtensorMap mm, const __grid_constant__ CUtensorMap mx, const __grid_constant__ CUtensorMap mw,
             const __grid_constant__ CUtensorMap mt, const __grid_constant__ CUtensorMap mo, const __grid_constant__ CUtensorMap mg,
             const __grid_constant__ CUtensorMap mu, const __grid_constant__ CUtensorMap md,
             const __grid_constant__ CUtensorMap mw2, const __grid_constant__ CUtensorMap mout) {
    extern __shared__ __align__(1024) char sm_raw[];
    const int bid = blockIdx.x;
    const uint32_t sm = ((bid & 1) << 24) + SM0;
    STAMP(30);
    const uint32_t t_start = clock32();
    if (bid < CPF && threadIdx.x == 0)
        asm volatile("cp.async.bulk.prefetch.tensor.2d.L2.global [%0, {%1, %2}];" ::"l"(&mm), "r"((bid & 1) * 640 + (bid >> 4) * 64), "r"(((bid >> 1) & 7) * 80) : "memory");
    const int cl = bid >> 1, rank = bid & 1, c7 = ((cl - 36) * 37) >> 8;
    const int grp = cl < 4 ? 0 : (cl < 36 ? (cl - 4) & 7 : cl - 35 - 7 * c7);
    const int ti = grp * 2 + rank;
    auto ldx = [&](int c) { mbar_expect_tx(BAR(B_XF + c), 16384); tma3d(sm + c * 16384, &mx, c * 64, ti >> 3, (ti & 7) * 128, BAR(B_XF + c)); };
    if (threadIdx.x == 256 && bid < 128) {
        mbar_init(BAR(B_XF), 1); mbar_init(BAR(B_XF + 1), 1);
        if (XDELAY > 1) pause_until(t_start, XDELAY);
        ldx(0); ldx(1);
        STAMPT(22, 256);
#pragma unroll
        for (int i = 2; i < 10; i++) mbar_init(BAR(B_XF + i), 1);
        mbar_init(BAR(B_T0), 1);
        asm volatile("fence.mbarrier_init.release.cluster;" ::: "memory");
        ldx(2); ldx(3); ldx(4);
    }
    const int warp = __shfl_sync(~0u, threadIdx.x >> 5, 0);

#define PIN(v) __shfl_xor_sync(~0u, (v), 0)
#define LANE_VARS const int tid = PIN(threadIdx.x), lane = tid & 31, g = lane >> 2, q = lane & 3; \
    const uint32_t frow = (lane & 7) + (lane >> 4) * 8, fh = (lane >> 3) & 1;
    if (bid >= 128) {
        LANE_VARS
        const int h = bid - 128;
        if (warp >= 8) {
            if (warp == 8) return;
            const int t = tid - 288;
            if (t < 90) stg4_rlx(&S->tab[(5 + t / 9) * 4 + h][t % 9], 0u, 0u, 0u, 0u);
            __syncwarp();
            asm volatile("bar.arrive 1, 352;" ::: "memory");
            bar_sync(2, 96);
            if (t == 0) asm volatile("red.release.gpu.global.add.u32 [%0], 32;" ::"l"(&S->cnt) : "memory");
            return;
        }
        const uint32_t slot = sm + warp * 20480, bar = BAR(warp * 2);
        auto column = [&](int job) {
            const int n = job * 4 + h;
            return job < 10 ? ((h & 1) ? (job < 5 ? 10 : 30) : (job < 5 ? 0 : 10)) + (n >> 1) : (n < 50 ? n - 10 : n);
        };
        auto load = [&](int job) {
            mbar_expect_tx(bar + (job & 1) * 8, 10240);
            tma2d(slot + (job & 1) * 10240, &mm, column(job) * 64, warp * 80, bar + (job & 1) * 8);
        };
        if (elect1()) { mbar_init(bar, 1); mbar_init(bar + 8, 1); load(0); }
        __syncwarp();
        uint32_t b[10];
#pragma unroll
        for (int s = 0; s < 10; s++) b[s] = ldg1_rlx((const uint32_t*)cvec + warp * 40 + s * 4 + q);
        if (lane < 8 && warp < 5) stg4_rlx(&S->tab[warp * 4 + h][lane], 0u, 0u, 0u, 0u);
#pragma unroll
        for (int s = 0; s < 10; s++) b[s] = pack2(blo(b[s]) * sigm(blo(b[s])), bhi(b[s]) * sigm(bhi(b[s])));
        const uint32_t fa = slot + frow * 128 + ((fh ^ (lane & 7)) << 4);
        const int c0 = (lane >> 3) * 16 + (lane & 1) * 8 + (lane & 6);
#pragma unroll 1
        for (int job = 0; job < 15; job++) {
            uint32_t w2 = 0;
            if (job >= 5) w2 = ldg1_rlx(wr + (column(job) % 10) * 64 + c0);

            mbar_wait(bar + (job & 1) * 8, (job >> 1) & 1);
            if (job == 0) { if (elect1()) load(1); __syncwarp(); }
            float d[4][4] = {};
#pragma unroll
            for (int s = 0; s < 5; s++) {
#pragma unroll
                for (int m = 0; m < 4; m++) { uint32_t a[4]; ldsm4t(a, (fa ^ (m * 32)) + (job & 1) * 10240 + s * 2048); mma16(d[m], a[0], a[1], a[2], a[3], b[2 * s], b[2 * s + 1]); }
            }
            const uint32_t red = sm + OFF_W + (job & 1) * 2048;
            sts1f(red + (warp * 64 + q * 8 + g) * 4, q == 0 ? d[0][0] : (q == 1 ? d[0][2] : (q == 2 ? d[1][0] : d[1][2])));
            sts1f(red + (warp * 64 + 32 + q * 8 + g) * 4, q == 0 ? d[2][0] : (q == 1 ? d[2][2] : (q == 2 ? d[3][0] : d[3][2])));
            __syncwarp();
            if (HPAUSE && job == HJOB) pause_until(t_start, HPAUSE);
            if (job < 13 && elect1()) load(job + 2);
            __syncwarp();
            bar_sync(0, 256);
            if (job == 5) bar_sync(1, 352);
            if (warp == (job & 7)) {
                float y0 = 0.f, y1 = 0.f;
#pragma unroll
                for (int w = 0; w < 8; w++) { const float2 v = lds2f(red + (w * 64 + c0) * 4); y0 += v.x; y1 += v.y; }
                const uint32_t t = hf2(pack2(y0, y1), 0x3f803f80u, ((h & 1) && job < 10) ? 0x3f803f80u : 0x80008000u);
                uint32_t* const p = (uint32_t*)&S->tab[job * 4 + h][0];
                stg1_rlx(p + lane, nz(t));
                float dot = fmaf(blo(t), blo(w2), bhi(t) * bhi(w2));
#pragma unroll
                for (int o = 16; o; o >>= 1) dot += __shfl_xor_sync(~0u, dot, o);
                if (lane == 0) stg1_rlx(p + 32, dot == 0.f ? 0x80000000u : __float_as_uint(dot));
            }
            if (job == 0) STAMP(27);
            if (job == 8) STAMP(28);
        }
        STAMP(17);
        return;
    }
    uint32_t ep0;
    if (__builtin_expect(warp == 8, 1)) {
        asm volatile("barrier.cluster.arrive.relaxed.aligned;" ::: "memory");
        if (elect1()) {
#pragma unroll 1
            for (int c = 5; c < 10; c++) ldx(c);
        }
        __syncwarp();
    } else {
        if (warp < 8) {
            if (elect1()) {
#pragma unroll
                for (int i = 0; i < 8; i++) { const int b = B_WF + warp * 8 + i; mbar_init(BAR(b), b >= B_WE ? 16 : (b >= B_G2 ? 8 : (b >= B_EP ? 2 : (b == B_WO ? 7 : 1)))); }
                asm volatile("fence.mbarrier_init.release.cluster;" ::: "memory");
            }
            __syncwarp();
        }
        if (warp == 9) ep0 = ldg1_rlx(&S->cnt);
        asm volatile("barrier.cluster.arrive.relaxed.aligned;" ::: "memory");
    }
    const int sl = cl < 4 ? 4 + cl : (cl < 36 ? (cl - 4) >> 3 : 4 + c7);
    const int j = sl ^ (((sl + 2) >> 2) & (SWAPM >> grp) & 1), role = ti * 8 + j, odd = j & 1;
    const int fi = j * 16 + ti;
    const int al = ((j + 1) & 2) == 0;
    Exch* const X = &S->x;
    if (warp >= 8) {
        asm volatile("setmaxnreg.dec.sync.aligned.u32 72;");
        if (warp == 8) {
            asm volatile("barrier.cluster.wait.aligned;" ::: "memory");
            if (!elect1()) return;
            const int col_main = 80 * j + 16 * odd, col_tail = 80 * j + (odd ? 0 : 64);
            auto load_w = [&](int it) {
                const uint32_t b = BAR(B_WF + it), dst = sm + wbuf(it) + rank * 6144;
                mbar_expect_tx(b, WST);
                tma4d_mc(dst, al ? &mw2 : &mw, 0, it * 32 + rank * 16, col_main >> (5 + al), 0, b);
                tma3d_mc(dst + 12288 - rank * 4608, &mt, col_tail, it * 32 + rank * 16, 0, b);
            };
            int it = 0, wn = 0, gn = 0;
#pragma unroll 1
            for (int r = -2; r < 19; r++) {
                if (r == -2 && WLATE) mbar_wait(BAR(B_XF + WLATE), 0);
                if (r == -1) mbar_wait(BAR(B_XF + XWAIT), 0);
                if (r >= 0) mbar_wait(BAR(B_WE + r), 0);
                const int lim = min(r < 2 ? (r == 1 ? 7 : 2 * r + 6) : r + 7, 20);
#pragma unroll 1
                for (; it < lim; it++) load_w(it);
                if (r == -1 || r == 0) l2_prefetch(wqkv + (size_t)(384 + r * 256 + role * 2) * 1920, 2 * 3840);
                if (r == 0) l2_prefetch(wo + role * 3200, 6400);
                if (MPF == 1 && r >= MPF0 && r < MPF0 + 5) l2_prefetch(wmod + (size_t)(role * 5 + r - MPF0) * 3840 + 1280, 5120);
                if (MPF == 2 && r >= MPF0 && r < MPF0 + 10) l2_prefetch(wmod + (size_t)(role * 5 + ((r - MPF0) >> 1)) * 3840 + 1920 + (r & 1) * 1280, 1280);
                if (((GU_MASK >> (r + 2)) & 1) && fi < 108) { if (gn == 0) mbar_expect_tx(BAR(B_FG), 40960); tma2d(sm + OFF_WG + gn * 10240, (fi & 1) ? &mu : &mg, (fi >> 1) * 32, gn * 160, BAR(B_FG)); gn++; }
#pragma unroll 1
                for (int n = ((WO_MASK >> (r + 2)) & 1) + (r == 14); n > 0; n--) {
                    const int row = (j ^ wn) * 80 + rank * 40;
                    const uint32_t b = BAR(wn ? B_WO : B_WO0), dst = sm + wobuf(wn) + rank * 2560;
                    mbar_expect_tx(b, WST);
                    tma2d_mc(dst, &mo, col_main, row, b); tma2d_mc(dst + 5120, &mo, col_main + 32, row, b); tma2d_mc(dst + 10240, &mo, col_tail, row, b);
                    wn++;
                }
                if (!NOPF && r >= PF0 && r < PF0 + 3 * PFN) { const int m = (r - PF0) / PFN; l2_prefetch((m == 0 ? wg : (m == 1 ? wu : wd)) + role * 8640 + (r - PF0 - m * PFN) * (8640 / PFN), 17280 / PFN); }
            }
            STAMPT(24, 256);
            if (fi >= 88) { mbar_wait(BAR(B_G2), 0); mbar_expect_tx(BAR(B_FD), 55296); tma3d(sm + OFF_WD, &md, (fi - 88) * 16, 0, 0, BAR(B_FD)); }
            return;
        }
        asm volatile("barrier.cluster.wait.aligned;" ::: "memory");
        const int tid = threadIdx.x, lane = tid & 31, fh = (lane >> 3) & 1;
        int gd = 0;
        if (warp == 9) {
            {
                uint32_t ta = sm + OFF_TAB + fh * 1280 + (lane >> 4) * 128 + (lane & 4) * 16 + (lane & 1) * 32 + (lane & 2) * 4;
                const uint4* tp = &S->tab[lane >> 3][lane & 7];
                pause_until(t_start, TDELAY);
#pragma unroll 1
                for (int e = 0; e < 5; e++) {
                    uint32_t w[4];
                    if (e > 1) mbar_wait(BAR(B_WE + 4 * e - 8), 0);
                    while (true) {
                        ldg4_rlx(w, tp);
                        if (!__any_sync(~0u, min(min(w[0], w[1]), min(w[2], w[3])) == 0) || ++gd > SPIN_LIMIT) break;
                        pause(P_TAB);
                    }
                    sts2(ta, w[0], w[1]); sts2(ta + 16, w[2], w[3]);
                    __syncwarp();
                    if (e == 0) { STAMPT(2, 288); if (lane == 0) sts1(sm + OFF_EP + EP_US + 8, ep0 << 22 & 0x40000000u); }
                    if (lane == 0) mbar_arrive(BAR(e ? B_TB - 1 + e : B_T0));
                    ta += 256; tp += 288;
                }
            }
            uint32_t h[5][4];
            while (ldg1_acq(&S->cnt) != inc(ep0) && ++gd < SPIN_LIMIT) __nanosleep(YSLEEP);
            __syncwarp();
            if (lane == 0) mbar_arrive(BAR(B_RDY));
            mbar_wait(BAR(HALO_GO), 0);
            if ((ti & 7) == 0) {
#pragma unroll
                for (int s = 0; s < 20; s++) h[s >> 2][s & 3] = 0;
            } else {
                do {
                    pause(P_H);
#pragma unroll
                    for (int s = 0; s < 5; s++) ldg4_rlx(h[s], &X->halo[(role - 8 - (ti & 8)) * 160 + s * 32 + lane]);
                } while (__any_sync(~0u, min(min(min(h[0][0], h[1][0]), min(h[2][0], h[3][0])), h[4][0]) == 0) && ++gd < SPIN_LIMIT);
            }
            const uint32_t p8 = sm + OFF_P8 - 4096, va = p8 + 2048 + (lane & 7) * VP + (lane >> 3) * 16;
            sts4(p8 + 2048 + 1408 + lane * 16, h[0]); sts4(p8 + 1408 + lane * 16, h[1]); sts2(p8 + (lane >> 4) * 2048 + 1920 + (lane & 15) * 8, h[2][0], h[2][1]);
            stsm4(va, h[3]); stsm4(va + 64, h[4]); stsm2(va + 128, h[2][2], h[2][3]);
            __syncwarp();
            if (lane == 0) mbar_arrive(BAR(B_HL));
            STAMPT(19, 288);
            mbar_wait(BAR(B_G3), 0);
            do {
                pause(P_REC);
                ldg4_rlx(h[0], &X->ra[(lane >> 3) * 8 + grp][lane & 7]); ldg4_rlx(h[1], &X->ra[(lane >> 3) * 8 + 32 + grp][lane & 7]);
            } while (__any_sync(~0u, min(min(h[0][1], h[0][3]), min(h[1][1], h[1][3])) == 0) && ++gd < SPIN_LIMIT);
            const uint32_t kwin = __reduce_max_sync(~0u, max(max(h[0][0], h[0][2]), max(h[1][0], h[1][2])));
            const uint32_t tok = __reduce_min_sync(~0u, min(min(h[0][0] == kwin ? h[0][1] : 2048u, h[0][2] == kwin ? h[0][3] : 2048u), min(h[1][0] == kwin ? h[1][1] : 2048u, h[1][2] == kwin ? h[1][3] : 2048u)));
            if (lane == 0) {
                const uint32_t t = (tok - 1) & 2047, wi = (t & 1) * 64 + (t >> 5), wv[4] = {kwin, t, wi, wi * 320};
                sts4(sm + OFF_EP + EP_US + 32, wv); mbar_arrive(BAR(B_WIN));
            }
            if (lane < 8 && role < 20) stg4_rlx(&S->tab[role][lane], 0u, 0u, 0u, 0u);
            return;
        }
        const int at = tid - 320;
        const int kg = at < 40 ? 80 * j + 2 * at : max(fi - 88, 0) * 16 + 2 * (at & 7);
        const uint32_t w2 = *(const uint32_t*)(wr + kg);
        mbar_wait(BAR(B_WF + RWAIT), 0);
        if (RTB) mbar_wait(BAR(B_T0), 0);
        {
            uint4* p = &X->o[4 * 128 * 256] + role * RV + at;
#pragma unroll 1
            for (int r = 0; r < RV / 64; r++) {
                stg4_rlx(p, 0u, 0u, 0u, 0u);
                p += 64;
                __nanosleep(RSLEEP);
            }
        }
        bar_sync(5, 64);
        if (at == 0) { mbar_wait(BAR(B_TB), 0); }
        if (at == 0) asm volatile("red.release.gpu.global.add.u32 [%0], 1;" ::"l"(&S->cnt) : "memory");
        mbar_wait(BAR(B_RDY), 0);
        const uint32_t* const mp = (const uint32_t*)&S->tab[0][0] + ((kg >> 4) & 3) * 8 + (kg & 6) + ((kg >> 3) & 1);
        const int p = odd ? (at < 8 ? at + 32 : at - 8) : at, lm = min(lane, 9);
        const uint32_t a = sm + OFF_EP + (p & 3) * 48 + (p >> 2) * 4;
#pragma unroll 1
        for (int ph = 0; ph < 4; ph++) {
            uint32_t v, us;
            mbar_wait(BAR(ph < 2 ? TB_GO : TB_GO2), 0);
            while (true) {
                v = ldg1_rlx(mp + (ph < 2 ? 20 + ph + (kg >> 6) * 2 : 20 + ph * 10 + (kg >> 6)) * 288);
                us = ldg1_rlx(&S->tab[ph < 2 ? 20 + ph + lm * 2 : 20 + ph * 10 + lm][8]);
                if (!__any_sync(~0u, min(v, us) == 0) || ++gd > SPIN_LIMIT) break;
                __nanosleep(200);
            }
            if (at < 40) {
                sts1(a + ph * 192, v);
                if (ph == 1) {
                    const float u0 = blo(v) * blo(w2), u1 = bhi(v) * bhi(w2);
                    const uint32_t uh = pack2(u0, u1);
                    sts1(a + 768, 0x3f803f80u); sts1(a + 960, uh); sts1(a + 1152, pack2(u0 - blo(uh), u1 - bhi(uh)));
                }
            } else sts1(sm + OFF_EP + EP_GD + (at & 7) * 4, v);
            float t = lane < 10 ? __uint_as_float(us) : 0.f;
#pragma unroll
            for (int o = 1; o < 16; o <<= 1) t += __shfl_xor_sync(~0u, t, o);
            if (at == 0) sts1f(sm + OFF_EP + EP_US + 12 + ph * 4, t);
            __syncwarp();
            if (lane == 0 && ph) mbar_arrive(BAR(B_EP - 1 + ph));
        }
        STAMPT(20, 320);
    } else {
        asm volatile("setmaxnreg.inc.sync.aligned.u32 216;");
        asm volatile("barrier.cluster.wait.aligned;" ::: "memory");
        LANE_VARS
        const int tw = ti * 8 + warp;
        const uint32_t oo = tw * 4096 + j * 512 + lane * 16;
        const uint32_t pair = (uint32_t)(lane & 1) << 24;
        const uint32_t hi = lane >> 4, xa = sm + (warp * 16 + (lane & 15)) * 128 + ((hi ^ (lane & 7)) << 4);
        const uint32_t p8 = sm + OFF_P8 + warp * 2048, q8 = p8 - (warp ? 2048 : 4096), q9 = p8 - 2048 + (warp ? 16384 : 0);
        const uint32_t l16 = PIN(lane * 16), kt = PIN(hi * 16384 + (lane & 15) * 8), va = PIN(p8 + (lane & 7) * VP + (lane >> 3) * 16);
        const uint32_t vb = PIN(p8 + (lane & 7) * VP + hi * 16384 + fh * 16), vc = PIN(p8 + (lane & 7) * VP + fh * 16384 + hi * 16);
        const uint32_t vh = PIN((fh ? p8 : q9) + (lane & 7) * VP + hi * 16), kh = PIN((hi ? q9 : q8) + (lane & 15) * 8);
        const uint32_t mgt = PIN((2 * q > g ? 0xffffu : 0u) | (2 * q + 1 > g ? 0xffff0000u : 0u));
        uint32_t rr0, rr1, nn0, nn1;
        {
            float gA[2][4] = {}, gB[2][4] = {};
            uint32_t xb = sm + (warp * 16 + frow) * 128 + ((fh ^ (lane & 7)) << 4), one[16];
#pragma unroll
            for (int k = 0; k < 16; k++) one[k] = 0x3f803f80u + ((uint32_t)tid >> (12 + k));
#pragma unroll 1
            for (int c = 0; c < 10; c += 2) {
                mbar_wait(BAR(B_XF + c), 0); mbar_wait(BAR(B_XF + c + 1), 0);
                uint32_t a[8][4];
#pragma unroll
                for (int k = 0; k < 8; k++) ldsm4(a[k], (xb ^ ((k & 3) * 32)) + (k >> 2) * 16384);
                xb += 32768;
#pragma unroll
                for (int k = 0; k < 8; k++) {
                    uint32_t t[4];
#pragma unroll
                    for (int e = 0; e < 4; e++) asm volatile("mov.b32 %0, %1;" : "=r"(t[e]) : "r"(a[k][e]));
                    mma16(gA[k & 1], t[0], one[(k & 3) * 4], t[1], one[(k & 3) * 4 + 1], a[k][0], a[k][1]);
                    mma16(gB[k & 1], t[2], one[(k & 3) * 4 + 2], t[3], one[(k & 3) * 4 + 3], a[k][2], a[k][3]);
                }
            }
            const int src = (lane & ~3) | (g >> 1), e = g & 1;
            const float ss0 = __shfl_sync(~0u, e ? gA[0][1] + gA[1][1] : gA[0][0] + gA[1][0], src), ss1 = __shfl_sync(~0u, e ? gB[0][1] + gB[1][1] : gB[0][0] + gB[1][0], src);
            const float m0 = __shfl_sync(~0u, e ? gA[0][3] + gA[1][3] : gA[0][2] + gA[1][2], src) * (1.f / 640), m1 = __shfl_sync(~0u, e ? gB[0][3] + gB[1][3] : gB[0][2] + gB[1][2], src) * (1.f / 640);
            const float r0 = rbf(rsq(fmaxf(ss0 * (1.f / 640) - m0 * m0, 0.f) + 1e-5f)), r1 = rbf(rsq(fmaxf(ss1 * (1.f / 640) - m1 * m1, 0.f) + 1e-5f));
            rr0 = pack2(r0, r0); rr1 = pack2(r1, r1); nn0 = pack2(-m0 * r0, -m0 * r0); nn1 = pack2(-m1 * r1, -m1 * r1);
        }
        uint32_t xr[5][4];
#pragma unroll
        for (int s = 0; s < 5; s++) {
            const int ks = 5 * j + (odd ? (s == 4 ? 0 : s + 1) : s);
            ldsm4(xr[s], (xa ^ ((ks & 3) * 32)) + (ks >> 2) * 16384);
        }
        STAMP(0);
        mbar_wait(BAR(B_T0), 0);
        if (WGBAR) bar_sync(1, 256);
        float acc[120];
#pragma unroll
        for (int i = 0; i < 120; i++) asm volatile("" : "=f"(acc[i]));
        {
            uint32_t a[2][2][4], raw[2][4], tt[2][4];
            uint32_t tb = sm + OFF_TAB + q * 16, xp = xa;
            auto load = [&](int u) {
                ldsm4(raw[0], xp ^ (u * 64)); ldsm4(raw[1], xp ^ (u * 64 + 32));
                lds4(tt[0], tb + u * 64 + 1280); lds4(tt[1], tb + u * 64);
            };
            auto xform = [&](uint32_t (*dst)[4]) {
#pragma unroll
                for (int h = 0; h < 2; h++) {
                    dst[h][0] = hf2(hf2(raw[h][0], rr0, nn0), tt[0][2 * h], tt[1][2 * h]); dst[h][1] = hf2(hf2(raw[h][1], rr1, nn1), tt[0][2 * h], tt[1][2 * h]);
                    dst[h][2] = hf2(hf2(raw[h][2], rr0, nn0), tt[0][2 * h + 1], tt[1][2 * h + 1]); dst[h][3] = hf2(hf2(raw[h][3], rr1, nn1), tt[0][2 * h + 1], tt[1][2 * h + 1]);
                }
            };
            const uint64_t dm0 = al ? mkdesc(SM0, 2048, 1024, 1) : mkdesc(SM0, 1024, 512, 2), dt0 = mkdesc(SM0 + 12288, 512, 256, 3);
            load(0); xform(a[0]);
            STAMP(3);
#pragma unroll 1
            for (int i2 = 0; i2 < 10; i2++) {
#pragma unroll
                for (int u = 0; u < 2; u++) {
                    const int it = i2 * 2 + u;
                    const uint32_t bo = wbuf(it) >> 4;
                    mbar_wait(BAR(B_WF + it), 0);
                    if (LAG && warp < 4 && i2 * 2 + u == 20 - LAG) bar_sync(4, 256);
                    wg_fence();
#pragma unroll
                    for (int h = 0; h < 2; h++) { wgmma_rs_n192(acc, a[u][h], dm0 + bo + h * 384, (u | h) ? 1 : i2); wgmma_rs_n48(acc + 96, a[u][h], dt0 + bo + h * 96, (u | h) ? 1 : i2); }
                    wg_commit();
                    if (LAG && u == 1 && warp >= 4 && i2 == 9) asm volatile("bar.arrive 4, 256;" ::: "memory");
                    if (u == 1) { xp += 16384; tb += 128; }
                    if (u == 1 && (i2 & 1) && i2 < 9) mbar_wait(BAR(B_TB + (i2 >> 1)), 0);
                    load(u ^ 1);
                    wg_wait<1>();
                    if (lane < 2 && (u == 1 || i2 > 0)) mbar_arrive_cl(pair + BAR0(B_WE - 1 + it));
                    xform(a[u ^ 1]);
                }
            }
        }
        uint32_t own[5][4], ab[3][7][4], sv, tc;
        const char* op[7];
        auto ldo = [&](int s, uint32_t (*dst)[4]) {
#pragma unroll
            for (int w = 0; w < 7; w++) ldg4_rlx(dst[w], op[w] + (4 - s) * 524288);
        };
        {
            uint32_t Q[10][2], K[2][10], V[2][10];
            mbar_wait(BAR(B_RDY), 0);
            sv = lds1(sm + OFF_EP + EP_US + 8); tc = (sv ^ 0x40000000u) - 0x20000000u;
            wg_wait<0>();
            STAMP(4); STAMPT(18, 128);
#define ACC_IDX(t, m) (odd_ ? (t >= 2 ? m * 32 + (t - 2) * 4 : 96 + m * 8 + t * 4) : (t < 8 ? m * 32 + t * 4 : 96 + m * 8 + (t - 8) * 4))
#define PACK1(odd_v) { constexpr bool odd_ = odd_v; _Pragma("unroll") for (int t = 0; t < 10; t++) { \
                K[1][t] = pack2(acc[ACC_IDX(t, 1) + 2], acc[ACC_IDX(t, 1) + 3]); V[1][t] = pack2(acc[ACC_IDX(t, 2) + 2], acc[ACC_IDX(t, 2) + 3]); \
                V[0][t] = pack2(acc[ACC_IDX(t, 2)], acc[ACC_IDX(t, 2) + 1]); } }
#define PACK2(odd_v) { constexpr bool odd_ = odd_v; _Pragma("unroll") for (int t = 0; t < 10; t++) { \
                K[0][t] = pack2(acc[ACC_IDX(t, 1)], acc[ACC_IDX(t, 1) + 1]); \
                Q[t][0] = pack2(acc[ACC_IDX(t, 0)], acc[ACC_IDX(t, 0) + 1]); Q[t][1] = pack2(acc[ACC_IDX(t, 0) + 2], acc[ACC_IDX(t, 0) + 3]); } }
            if (odd) PACK1(true) else PACK1(false)
            if (warp == 7 && (~ti & 7)) {
                uint4* hp = &X->halo[(role - (ti & 8)) * 160 + lane];
                K[1][0] = nz(K[1][0]); K[1][5] = nz(K[1][5]); K[1][2] = nz(K[1][2]); V[1][0] = nz(V[1][0]); V[1][4] = nz(V[1][4]);
                stg4_rlx(hp, K[1][0], K[1][1], K[1][3], K[1][4]); stg4_rlx(hp + 32, K[1][5], K[1][6], K[1][8], K[1][9]); stg4_rlx(hp + 64, K[1][2], K[1][7], V[1][8], V[1][9]);
                stg4_rlx(hp + 96, V[1][0], V[1][1], V[1][2], V[1][3]); stg4_rlx(hp + 128, V[1][4], V[1][5], V[1][6], V[1][7]);
            }
            {
                const uint32_t k0[4] = {K[1][0], K[1][1], K[1][3], K[1][4]}, k1[4] = {K[1][5], K[1][6], K[1][8], K[1][9]}, vl[4] = {V[0][8], V[0][9], V[1][8], V[1][9]};
                sts4(p8 + 16384 + 1408 + l16, k0); sts4(p8 + 1408 + l16, k1); sts2(p8 + 1920 + kt, K[1][2], K[1][7]);
                stsm4(va + 16384, V[1]); stsm4(va + 16384 + 64, V[1] + 4); stsm4(vb + 128, vl);
                stsm4(va, V[0]); stsm4(va + 64, V[0] + 4);
            }
            __syncwarp();
            if (lane == 0) mbar_arrive(BAR(B_HL + 1 + warp));
            uint32_t VT[5][4], KH[10];
#pragma unroll
            for (int s = 0; s < 5; s++) ldsm4t(VT[s], vc + s * 32);
            if (odd) PACK2(true) else PACK2(false)
            float sb[4][4], sc[4][4];
            uint32_t qs[4][2];
#pragma unroll
            for (int h = 0; h < 4; h++) {
                const int ts = (h >> 1) * 5 + 2, ta = (h >> 1) * 5 + (h & 1) * 3;
                const bool mine = (q >> 1) == (h & 1);
                qs[h][0] = mine ? Q[ts][0] : 0u; qs[h][1] = mine ? Q[ts][1] : 0u;
                mma16c(sb[h], Q[ta][0], Q[ta][1], Q[ta + 1][0], Q[ta + 1][1], K[0][ta], K[0][ta + 1], 0.f, 0.f);
                mma16c(sc[h], Q[ta][0], Q[ta][1], Q[ta + 1][0], Q[ta + 1][1], K[1][ta], K[1][ta + 1], 0.f, 0.f);
                mma8(sb[h], qs[h][0], qs[h][1], K[0][ts]);
                mma8(sc[h], qs[h][0], qs[h][1], K[1][ts]);
            }
            const bool gt0 = mgt & 1, gt1 = (int)mgt < 0;
            auto half = [&](int e, float (*pv)[4], float (*cu)[4]) {
                const float cs = 0.22360679774997896f * 1.4426950408889634f;
                uint32_t p[4];
                float t0[4], t1[4], m[4];
#pragma unroll
                for (int h = 0; h < 4; h++) { t0[h] = gt0 ? pv[h][2 * e] : cu[h][2 * e]; t1[h] = gt1 ? pv[h][2 * e + 1] : cu[h][2 * e + 1]; m[h] = fmaxf(t0[h], t1[h]); }
#pragma unroll
                for (int h = 0; h < 4; h++) m[h] = fmaxf(m[h], __shfl_xor_sync(~0u, m[h], 1));
#pragma unroll
                for (int h = 0; h < 4; h++) m[h] = fmaxf(m[h], __shfl_xor_sync(~0u, m[h], 2)) * -cs;
#pragma unroll
                for (int h = 0; h < 4; h++) p[h] = pack2(ex2(fmaf(t0[h], cs, m[h])), ex2(fmaf(t1[h], cs, m[h])));
#pragma unroll
                for (int pr = 0; pr < 2; pr++) {
                    const uint32_t a0 = p[2 * pr] & mgt, a1 = p[2 * pr + 1] & mgt, a2 = p[2 * pr] & ~mgt, a3 = p[2 * pr + 1] & ~mgt;
                    float l[4];
                    mma16c(l, a0, a1, a2, a3, 0x3f803f80u, 0x3f803f80u, 0.f, 0.f);
                    l[0] = rcp(l[0]); l[2] = rcp(l[2]);
#pragma unroll
                    for (int r = 0; r < 5; r++) {
                        const int t = pr * 5 + r;
                        float d[4];
                        mma16c(d, a0, a1, a2, a3, VT[t >> 1][(t & 1) * 2], VT[t >> 1][(t & 1) * 2 + 1], 0.f, 0.f);
                        const bool od = r == 2 ? (q & 2) : r > 2;
                        const float li = od ? l[2] : l[0];
                        own[t >> 1][(t & 1) * 2 + e] = pack2((od ? d[2] : d[0]) * li, (od ? d[3] : d[1]) * li);
                    }
                }
            };
            half(1, sb, sc);
            mbar_wait(BAR(B_HL + warp), 0);
            lds4(KH, q9 + 1408 + l16); lds4(KH + 4, q8 + 1408 + l16); lds2(KH + 8, kh + 1920);
#pragma unroll
            for (int s = 0; s < 5; s++) ldsm4t(VT[s], vh + s * 32);
            STAMP(5); STAMPT(25, 64);
            const float ninf = (tw & 63) == 0 ? -INFINITY : 0.f;
#pragma unroll
            for (int h = 0; h < 4; h++) {
                const int ta = (h >> 1) * 5 + (h & 1) * 3;
                mma16c(sc[h], Q[ta][0], Q[ta][1], Q[ta + 1][0], Q[ta + 1][1], KH[2 * h], KH[2 * h + 1], ninf, ninf);
                mma8(sc[h], qs[h][0], qs[h][1], KH[8 + (h >> 1)]);
            }
            half(0, sc, sb);
#pragma unroll
            for (int w = 0; w < 7; w++) op[w] = (const char*)X->o + (oo ^ (w * 512 + 512));
#pragma unroll
            for (int s = 0; s < 5; s++) {
                if (s == EARLY_LD) ldo(0, ab[0]);
                own[s][0] = s ? tagw(own[s][0], tc) : nz(own[s][0]); stg4_rlx((char*)X->o + oo + (4 - s) * 524288, own[s][0], own[s][1], own[s][2], own[s][3]);
            }
        }
        STAMP(6); STAMPT(21, 128); STAMPT(26, 64);
        float ac2[40];
#pragma unroll
        for (int i = 0; i < 40; i++) asm volatile("" : "=f"(ac2[i]));
        {
            const uint64_t d0 = mkdesc(SM0, 5120, 512, 2);
            mbar_wait(BAR(B_WO0), 0);
#pragma unroll
            for (int s = 1; s < 5; s++) own[s][0] -= tc;
            wg_fence();
#pragma unroll
            for (int s = 0; s < 5; s++) wgmma_rs_n80(ac2, own[s], d0 + (wobuf(0) >> 4) + s * 64, s);
            wg_commit();
            uint32_t fz = clock32();
            if (EARLY_LD >= 5) ldo(0, ab[0]);
            if (!LATE1) ldo(1, ab[1]);
            mbar_wait(BAR(B_WO), 0);
#pragma unroll
            for (int s = 0; s < 5; s++) {
                uint32_t (*cur)[4] = ab[s % 3];
                if (s == 0) await7<0>(cur, op, fz, sv);
                else {
                    if (s == 1) await7<1>(cur, op, fz, sv); else if (s == 2) await7<2>(cur, op, fz, sv); else if (s == 3) await7<3>(cur, op, fz, sv); else await7<4>(cur, op, fz, sv);
#pragma unroll
                    for (int w = 0; w < 7; w++) cur[w][0] -= tc;
                }
                if (s == 0) { STAMP(7); STAMPT(1, 128); }
                wg_fence();
#pragma unroll
                for (int w = 1; w < 8; w++) wgmma_rs_n80(ac2, cur[w - 1], d0 + (wobuf(w) >> 4) + s * 64, 1);
                wg_commit();
                if (s < 3) { if (s) wg_wait<1>(); else fz |= clock32(); if (s == 0 && LATE1) ldo(1, ab[1]); ldo(s + 2, ab[(s + 2) % 3]); }
                if (s == FD_AT && lane == 0) mbar_arrive(BAR(B_G2));
            }
        }
        mbar_wait(BAR(B_EP), 0);
        uint32_t tga[12], tst[12];
        const uint32_t ep = sm + OFF_EP + q * 48;
#pragma unroll
        for (int s = 0; s < 3; s++) { lds4(tga + 4 * s, ep + s * 16); lds4(tst + 4 * s, ep + 768 + min(g, 2) * 192 + s * 16); }
        uint4* const sp0 = pinp(&X->stats[j][tw * 16 + g]);
        const int dsrc = PIN((lane & ~3) | (g >> 1));
        wg_wait<0>();
        if (lane == 0) mbar_arrive(BAR(B_G4));
        STAMP(8); STAMPT(23, 128);
        {
            float gA[2][4] = {}, gB[2][4] = {}, sd[4] = {};
#pragma unroll
            for (int s = 0; s < 5; s++) {
#pragma unroll
                for (int e = 0; e < 4; e++) xr[s][e] = hf2(tga[2 * s + (e >> 1)], pack2(ac2[s * 8 + e * 2], ac2[s * 8 + e * 2 + 1]), xr[s][e]);
                mma16(sd, xr[s][0], xr[s][1], xr[s][2], xr[s][3], tst[2 * s], tst[2 * s + 1]);
                mma8(gA[0], xr[s][0], xr[s][1], xr[s][0]); mma8(gB[0], xr[s][0], xr[s][1], xr[s][1]);
                mma8(gA[1], xr[s][2], xr[s][3], xr[s][2]); mma8(gB[1], xr[s][2], xr[s][3], xr[s][3]);
            }
            const float l0 = __shfl_down_sync(~0u, sd[0], 1), l1 = __shfl_down_sync(~0u, sd[2], 1);
            const float q0 = __shfl_sync(~0u, fsel(g & 1, gA[0][1] + gA[1][1], gA[0][0] + gA[1][0]), dsrc), q1 = __shfl_sync(~0u, fsel(g & 1, gB[0][3] + gB[1][3], gB[0][2] + gB[1][2]), dsrc);
            stg4_if(q == 0, sp0, __float_as_uint(sd[0]), __float_as_uint(sd[1] + l0), __float_as_uint(q0), 1u);
            stg4_if(q == 0, sp0 + 8, __float_as_uint(sd[2]), __float_as_uint(sd[3] + l1), __float_as_uint(q1), 1u);
        }
        STAMP(9);
        uint32_t fg[5][4], fu[5][4], tcb[12], tsb[12];
        if (fi < 108) {
            mbar_wait(BAR(B_FG), 0);
#pragma unroll
            for (int s = 0; s < 5; s++) {
                const uint32_t off = sm + OFF_WG + (5 * warp + ((warp & 1) ? (s == 4 ? 0 : s + 1) : s)) * 1024 + frow * 64 + ((fh ^ ((lane >> 1) & 3)) << 4);
                ldsm4t(fg[s], off); ldsm4t(fu[s], off ^ 32);
            }
        }
        mbar_wait(BAR(B_EP2), 0);
#pragma unroll
        for (int s = 0; s < 3; s++) { lds4(tcb + 4 * s, ep + 192 + s * 16); lds4(tsb + 4 * s, ep + 384 + s * 16); }
        const int prow = (ti & 7) * 128 + warp * 16;
        int crow;
        {
            const float2 su = lds2f(sm + OFF_EP + EP_US + 16);
            uint32_t st[4][4]; int gd = 0;
            const uint4* sp = &X->stats[hi * 4][tw * 16 + (lane & 15)];
            uint2* const rp = pinp((uint2*)&X->ra[(tw >> 4) * 8 + (lane & 7)][0] + (tw & 15));
            const int tk = PIN(warp == j && lane < 8 ? prow * 2 + (ti >> 3) + 1 : 0);
            float v[3];
            bool bad;
            do {
                pause(P_ST);
#pragma unroll
                for (int e = 0; e < 4; e++) ldg4_rlx(st[e], sp + e * 2056);
                bad = __any_sync(~0u, (st[0][3] & st[1][3] & st[2][3] & st[3][3]) == 0);
#pragma unroll
                for (int e = 0; e < 3; e++) {
                    v[e] = (__uint_as_float(st[0][e]) + __uint_as_float(st[1][e])) + (__uint_as_float(st[2][e]) + __uint_as_float(st[3][e]));
                    v[e] += __shfl_xor_sync(~0u, v[e], 16);
                }
                gd++;
            } while (bad && gd < SPIN_LIMIT);
            STAMP(10);
            const float m = v[0] * (1.f / 640), rs = rsq(fmaxf(fmaf(v[2], 1.f / 640, 1e-5f) - m * m, 1e-5f));
            const uint32_t key = fkey(fmaf(rs, fmaf(-m, su.x, v[1]), su.y)), kmax = __reduce_max_sync(~0u, key);
            crow = __ffs(__ballot_sync(~0u, key == kmax)) - 1;
            stg2_if(tk, rp, kmax, tk + 2 * crow);
            const uint32_t rn = pack2(rs, -m * rbf(rs)), a0 = __shfl_sync(~0u, rn, g), a1 = __shfl_sync(~0u, rn, g + 8);
            rr0 = __byte_perm(a0, 0, 0x1010); nn0 = __byte_perm(a0, 0, 0x3232); rr1 = __byte_perm(a1, 0, 0x1010); nn1 = __byte_perm(a1, 0, 0x3232);
        }
        {
            const bool up = crow >= 8;
            const uint32_t rr = up ? rr1 : rr0, nn = up ? nn1 : nn0;
            if (g == (crow & 7)) {
                uint4* cp = &X->cand[j][tw * 20 + q];
#pragma unroll
                for (int s = 0; s < 5; s++) {
                    const uint32_t xa_ = up ? xr[s][1] : xr[s][0], xb_ = up ? xr[s][3] : xr[s][2];
                    stg4_rlx(cp + s * 4, nz(hf2(hf2(xa_, rr, nn), tcb[2 * s], tsb[2 * s])), hf2(hf2(xb_, rr, nn), tcb[2 * s + 1], tsb[2 * s + 1]), xa_, xb_);
                }
            }
        }
        if (lane == 0) mbar_arrive(BAR(B_G3));
        STAMP(11);
        const uint32_t stg = sm + 5 * WST + warp * 2560;
        {
            mbar_wait(BAR(B_EP3), 0);
#pragma unroll
            for (int s = 0; s < 3; s++) lds4(tga + 4 * s, ep + 576 + s * 16);
#pragma unroll
            for (int s = 0; s < 5; s++) {
#pragma unroll
                for (int e = 0; e < 4; e++) { const int t = 2 * s + (e >> 1); xr[s][e] = hf2(tga[t], hf2(hf2(xr[s][e], (e & 1) ? rr1 : rr0, (e & 1) ? nn1 : nn0), tcb[t], tsb[t]), xr[s][e]); }
            }
            mbar_wait(BAR(B_G4), 0);
#pragma unroll
            for (int s = 0; s < 5; s++) stsm4(stg + (lane & 15) * 160 + (odd ? (s == 4 ? 0 : s + 1) : s) * 32 + hi * 16, xr[s]);
            asm volatile("fence.proxy.async.shared::cta;" ::: "memory");
            __syncwarp();
            if (OUTPOS == 0 && elect1()) tma3d_st(&mout, 80 * j, ti >> 3, prow + (~crow & 8), stg + (~crow & 8) * 160);
        }
        STAMP(12);
        const char* cp = (const char*)pinp(&X->cand[warp][q]);
        uint32_t* const ap0 = pinp((uint32_t*)&X->ra[fi >> 1][8 + (fi & 1) * 4] + (lane & 8) + (lane & 3) * 2 + ((lane >> 2) & 1));
        const uint32_t rw = PIN(sm + OFF_RED - 256 + (q * 4 + (g >> 1)) * 80 + warp * 8 + (g & 1) * 4), rd = PIN(sm + OFF_RED - 256 + (lane & 15) * 80);
        if (smem_u32(sm_raw) != sm) return;
        mbar_wait(BAR(B_WIN), 0);
        uint32_t wv[4]; int gd = 0;
        lds4(wv, sm + OFF_EP + EP_US + 32);
        const uint32_t kwin = wv[0];
        const int tokwin = wv[1], win = wv[2];
        auto out2 = [&] {
            if (OUTPOS == 1 && elect1()) tma3d_st(&mout, 80 * j, ti >> 3, prow + (~crow & 8), stg + (~crow & 8) * 160);
            if (win != tw) {
                if (elect1()) tma3d_st(&mout, 80 * j, ti >> 3, prow + (crow & 8), stg + (crow & 8) * 160);
            } else {
#pragma unroll 1
                for (int r = crow & 8; r <= (crow | 7); r++)
                    if (r != crow && lane < 20) { uint32_t v[2]; lds2(v, stg + r * 160 + lane * 8); *(uint2*)(out + (size_t)((prow + r) * 2 + (ti >> 3)) * 640 + 80 * j + lane * 4) = make_uint2(v[0], v[1]); }
            }
        };
        STAMP(13);
        if (OUTPOS2 == 0) out2();
        if (fi < 108) {
            uint32_t hb[5][2];
            float mine;
            bool bad;
            cp += wv[3];
            do {
#pragma unroll
                for (int s = 0; s < 5; s++) ldg2_rlx(hb[s], cp + s * 64);
                bad = __any_sync(~0u, min(min(min(hb[0][0], hb[1][0]), min(hb[2][0], hb[3][0])), hb[4][0]) == 0);
                float dg[2][4] = {}, du[2][4] = {};
#pragma unroll
                for (int s = 0; s < 5; s++) {
                    mma16(dg[s & 1], fg[s][0], fg[s][1], fg[s][2], fg[s][3], hb[s][0], hb[s][1]);
                    mma16(du[s & 1], fu[s][0], fu[s][1], fu[s][2], fu[s][3], hb[s][0], hb[s][1]);
                }
                mine = fsel(q & 2, fsel(q & 1, du[1][2], du[1][0]), fsel(q & 1, dg[1][2], dg[1][0])) + fsel(q & 2, fsel(q & 1, du[0][2], du[0][0]), fsel(q & 1, dg[0][2], dg[0][0]));
                sts1f(rw, mine);
                gd++;
            } while (bad && gd < SPIN_LIMIT);
            bar_sync(2, 256);
            if (warp == 0) {
                uint32_t v[4][4];
#pragma unroll
                for (int e = 0; e < 4; e++) lds4(v[e], rd + e * 16);
                float t[2];
#pragma unroll
                for (int e = 0; e < 2; e++)
                    t[e] = ((__uint_as_float(v[0][e]) + __uint_as_float(v[0][e + 2])) + (__uint_as_float(v[1][e]) + __uint_as_float(v[1][e + 2]))) +
                           ((__uint_as_float(v[2][e]) + __uint_as_float(v[2][e + 2])) + (__uint_as_float(v[3][e]) + __uint_as_float(v[3][e + 2])));
                uint32_t pr = pack2(t[0], t[1]);
                if (!(fi & 1)) pr = pack2(blo(pr) * sigm(blo(pr)), bhi(pr) * sigm(bhi(pr)));
                stg1_if(lane < 16, ap0, nz(pr));
            }
        }
        STAMP(14);
        if (OUTPOS2 == 1) out2();
        if (fi >= 88) {
            const int d = fi - 88, dj = d / 5, dm = d - dj * 5, sp = (dj & 1) ? (dm == 0 ? 4 : dm - 1) : dm;
            const int ks0 = min(warp * 14, 94);
            const uint32_t frag = frow * 32 + ((fh ^ ((lane >> 2) & 1)) << 4);
            uint32_t fd[14][4];
            mbar_wait(BAR(B_FD), 0);
#pragma unroll
            for (int s = 0; s < 14; s++) ldsm4t(fd[s], sm + OFF_WD + (ks0 + s) * 512 + frag);
            const float sf = sigm(rbf(__uint_as_float((kwin & 0x80000000u) ? kwin & 0x7fffffffu : ~kwin)));
            const uint32_t sg = PIN(pack2(sf, sf));
            const uint32_t gbd = lds1(sm + OFF_EP + EP_GD + (lane & 7) * 4);
            uint32_t* const op = (uint32_t*)(out + (size_t)tokwin * 640 + d * 16) + (lane & 7);
            uint32_t bsv[4], ag[4], au[4];
            const uint4* ap = &X->ra[(ks0 >> 1) + min(g, 6)][8 + q];
            const uint32_t keep = warp == 7 && g < 2 ? 0u : ~0u;
            const uint32_t as = PIN(sm + 7 * WST + warp * 512 + q * 16), aw = PIN(sm + 7 * WST + warp * 512 + g * 64 + (q & 1) * 32 + (q >> 1) * 8);
            const uint32_t yw = PIN(sm + OFF_TAB + ((q & 1) * 4 + (g >> 1)) * 80 + warp * 8 + (g & 1) * 4), yr = PIN(sm + OFF_TAB + (lane & 7) * 80);
            bool bad;
            do {
                pause(P_A);
                ldg4_rlx(ag, ap); ldg4_rlx(au, ap + 4); ldg4_rlx(bsv, &X->cand[dj][win * 20 + sp * 4 + q]);
                bad = __any_sync(~0u, min(min(min(min(ag[0], ag[1]), min(ag[2], ag[3])), min(min(au[0], au[1]), min(au[2], au[3]))), bsv[0]) == 0);
                sts2(aw, hm2(ag[0], au[0]) & keep, hm2(ag[1], au[1]) & keep); sts2(aw + 16, hm2(ag[2], au[2]) & keep, hm2(ag[3], au[3]) & keep);
                gd++;
            } while (bad && gd < SPIN_LIMIT);
            STAMP(15);
            __syncwarp();
            float dy[4][4] = {};
            uint32_t av[7][4];
#pragma unroll
            for (int s = 0; s < 7; s++) lds4(av[s], as + s * 64);
#pragma unroll
            for (int s = 0; s < 7; s++) {
                mma16(dy[(2 * s) & 3], fd[2 * s][0], fd[2 * s][1], fd[2 * s][2], fd[2 * s][3], av[s][0], av[s][1]);
                mma16(dy[(2 * s + 1) & 3], fd[2 * s + 1][0], fd[2 * s + 1][1], fd[2 * s + 1][2], fd[2 * s + 1][3], av[s][2], av[s][3]);
            }
            sts1f(yw, (fsel(q & 1, dy[2][2], dy[2][0]) + fsel(q & 1, dy[3][2], dy[3][0])) + (fsel(q & 1, dy[0][2], dy[0][0]) + fsel(q & 1, dy[1][2], dy[1][0])));
            bar_sync(2, 256);
            if (warp == 0) {
                uint32_t v[4][4];
#pragma unroll
                for (int e = 0; e < 4; e++) lds4(v[e], yr + e * 16);
                float t[2];
#pragma unroll
                for (int e = 0; e < 2; e++)
                    t[e] = ((__uint_as_float(v[0][e]) + __uint_as_float(v[0][e + 2])) + (__uint_as_float(v[1][e]) + __uint_as_float(v[1][e + 2]))) +
                           ((__uint_as_float(v[2][e]) + __uint_as_float(v[2][e + 2])) + (__uint_as_float(v[3][e]) + __uint_as_float(v[3][e + 2])));
                const uint32_t hh = (lane & 4) ? bsv[1] : bsv[0], xx = (lane & 4) ? bsv[3] : bsv[2];
                if (lane < 8) *op = hf2(gbd, hf2(hm2(pack2(t[0], t[1]), sg), 0x3f803f80u, hh), xx);
            }
        }
        asm volatile("cp.async.bulk.commit_group;\ncp.async.bulk.wait_group.read 0;" ::: "memory");
        STAMP(16);
    }
}

typedef CUresult (*EncFn)(CUtensorMap*, CUtensorMapDataType, cuuint32_t, void*, const cuuint64_t*, const cuuint64_t*, const cuuint32_t*, const cuuint32_t*,
                          CUtensorMapInterleave, CUtensorMapSwizzle, CUtensorMapL2promotion, CUtensorMapFloatOOBfill);
static void make_map(EncFn enc, CUtensorMap* m, const void* base, int rank, const cuuint64_t* dims, const cuuint64_t* strides, const cuuint32_t* box, CUtensorMapSwizzle sw) {
    const cuuint32_t es[5] = {1, 1, 1, 1, 1};
    enc(m, CU_TENSOR_MAP_DATA_TYPE_BFLOAT16, rank, (void*)base, dims, strides, box, es, CU_TENSOR_MAP_INTERLEAVE_NONE, sw, CU_TENSOR_MAP_L2_PROMOTION_NONE, CU_TENSOR_MAP_FLOAT_OOB_FILL_NONE);
}

extern "C" void kernel_launch(void* const* d_in, const int* in_sizes, int n_in, void* d_out, int out_size) {
    typedef const __nv_bfloat16* P;
    P x = (P)d_in[0], wqkv = (P)d_in[1], wo = (P)d_in[2], wr = (P)d_in[4], wg = (P)d_in[5], wu = (P)d_in[6], wd = (P)d_in[7], c = (P)d_in[8], wmod = (P)d_in[9];
    void* fn = nullptr; cudaDriverEntryPointQueryResult qr;
    cudaGetDriverEntryPoint("cuTensorMapEncodeTiled", &fn, cudaEnableDefault, &qr);
    EncFn enc = (EncFn)fn;
    CUtensorMap mx, mw, mt, mo, mg, mu, md, mm, mw2, mout;
    { cuuint64_t d[] = {640, 2, 1024}, s[] = {1280, 2560}; cuuint32_t b[] = {64, 1, 128}; make_map(enc, &mx, x, 3, d, s, b, CU_TENSOR_MAP_SWIZZLE_128B); }
    { cuuint64_t d[] = {32, 640, 20, 3}, s[] = {3840, 64, 1280}; cuuint32_t b[] = {32, 16, 2, 3}; make_map(enc, &mw, wqkv, 4, d, s, b, CU_TENSOR_MAP_SWIZZLE_64B); }
    { cuuint64_t d[] = {640, 640, 3}, s[] = {3840, 1280}; cuuint32_t b[] = {16, 16, 3}; make_map(enc, &mt, wqkv, 3, d, s, b, CU_TENSOR_MAP_SWIZZLE_32B); }
    { cuuint64_t d[] = {640, 640}, s[] = {1280}; cuuint32_t b[] = {32, 40}; make_map(enc, &mo, wo, 2, d, s, b, CU_TENSOR_MAP_SWIZZLE_64B); }
    { cuuint64_t d[] = {1728, 640}, s[] = {3456}; cuuint32_t b[] = {32, 160}; make_map(enc, &mg, wg, 2, d, s, b, CU_TENSOR_MAP_SWIZZLE_64B); make_map(enc, &mu, wu, 2, d, s, b, CU_TENSOR_MAP_SWIZZLE_64B); }
    { cuuint64_t d[] = {640, 216, 8}, s[] = {1280, 1280 * 216}; cuuint32_t b[] = {16, 216, 8}; make_map(enc, &md, wd, 3, d, s, b, CU_TENSOR_MAP_SWIZZLE_32B); }
    { cuuint64_t d[] = {3840, 640}, s[] = {7680}; cuuint32_t b[] = {64, 80}; make_map(enc, &mm, wmod, 2, d, s, b, CU_TENSOR_MAP_SWIZZLE_128B); }
    { cuuint64_t d[] = {64, 640, 10, 3}, s[] = {3840, 128, 1280}; cuuint32_t b[] = {64, 16, 1, 3}; make_map(enc, &mw2, wqkv, 4, d, s, b, CU_TENSOR_MAP_SWIZZLE_128B); }
    { cuuint64_t d[] = {640, 2, 1024}, s[] = {1280, 2560}; cuuint32_t b[] = {80, 1, 8}; make_map(enc, &mout, d_out, 3, d, s, b, CU_TENSOR_MAP_SWIZZLE_NONE); }
    void* sp = nullptr;
    cudaGetSymbolAddress(&sp, g_s);
    cudaFuncSetAttribute(fused_kernel, cudaFuncAttributeMaxDynamicSharedMemorySize, SMEM_BYTES);
    fused_kernel<<<132, 384, SMEM_BYTES>>>(x, wmod, c, (Scratch*)sp, wqkv, wo, (__nv_bfloat16*)d_out, wr, wg, wu, wd, mm, mx, mw, mt, mo, mg, mu, md, mw2, mout);
}
```

```cpp
#include <cuda_runtime.h>
#include <cuda_bf16.h>
#include <cuda.h>
#include <stdint.h>

#define SPIN_LIMIT (1 << 17)

#define NCR 8
#define NCT 1
#define RPOS 0
#define RWAIT 0
#define CPF 32
#define RTB 1
#define STATV 0
#define OFFS 0
#define SWAPM 0xff
#define HPAUSE 0
#define HJOB 2
#define WGBAR 0
#define TSPLIT 0
#define ODLY 0
#define D_ST 400
#define D_REC 0
#define G3E 0
#define FGPOS 0
#define D_A 0
#define D_O 300
#define D_H 300
#define D_E 0
#define LATE2 0
#define WO16 1
#define XPF 0
constexpr int RV = 704;
struct __align__(4096) Exch {
    uint4 o[5 * 128 * 256];
    uint4 halo[112 * 160];
    uint4 stats[8][2056];
    uint4 cand[8][128 * 20 + 8];
    uint4 ra[64][24];
    uint4 pad[128 * RV - (128 * 256 + 112 * 160 + 8 * 2056 + 8 * (128 * 20 + 8) + 64 * 24)];
};
struct __align__(4096) Scratch {
    Exch x;
    uint4 tab[60][72];
    unsigned cnt;
};
__device__ Scratch g_s;
#define STAMP(n)
#define GSTAMP(n)
#define STAMPT(n, t)

constexpr uint32_t OFF_W = 163840, WST = 15360;
constexpr uint32_t OFF_WM = OFF_W + 2 * WST;
constexpr uint32_t OFF_FF = OFF_WM + 20480;
constexpr uint32_t OFF_P8 = 131072, VP = 176;
constexpr uint32_t OFF_WD = 129024, OFF_WG = 184320;
constexpr uint32_t OFF_TAB = 225280;
constexpr uint32_t OFF_RED = OFF_TAB + 2560;
constexpr uint32_t OFF_EP = OFF_TAB + 4096;
constexpr uint32_t EP_GD = 1344, EP_US = 1376;
constexpr uint32_t OFF_BAR = OFF_EP + 1424;
constexpr uint32_t OFF_PROF = OFF_BAR + 640;
constexpr uint32_t SMEM_BYTES = OFF_PROF + 128;
enum { B_XF = 0, B_WF = 10, B_WO0 = 30, B_WO, B_FG, B_FD, B_TB, B_HL = B_TB + 4, B_G0 = B_HL + 8, B_RDY, B_WIN, B_EP, B_EP2, B_EP3, B_G2, B_G3, B_G4, B_WE = 55, B_T0 = B_WE + 19 };
#define ALIGNED 1
#define WO_MASK 0x1f5000
#define P_TAB 100
#define P_REC 0
#define P_ST 0
#define P_A 0
#define RDELAY 600
#define OUTPOS2 1
#define EARLY_RST 0
#define OUTPOS 0
#define LAG 2
#define NOPF 0
#define SDELAY 1200
#define XWAIT 2
#define PFMAP 0
#define WLATE 0
#define SPLIT 1
#define P_O 0
#define P_H 0
#define LATE1 1
#define EARLY_LD 5
#define FD_AT 2
#define GU_MASK 0xaa00
#define TB_GO (B_WE + 16)
#define TB_GO2 B_G2
#define TDELAY 3900
#define PFN 5
#define PF0 1
#define RDY_AT 8
#define YSLEEP 300
#define MDELAY 2000
#define MPF 2
#define MPF0 6
#define XDELAY 600
#define RSLEEP 40
#define HALO_GO B_G0
constexpr uint32_t SM0 = 1024;
#define BAR0(i) (SM0 + OFF_BAR + 8 * (i))
#define BAR(i) (sm + OFF_BAR + 8 * (i))

__device__ __forceinline__ uint32_t smem_u32(const void* p) { return (uint32_t)__cvta_generic_to_shared(p); }
__device__ __forceinline__ void mbar_init(uint32_t b, int cnt) { asm volatile("mbarrier.init.shared::cta.b64 [%0], %1;" ::"r"(b), "r"(cnt) : "memory"); }
__device__ __forceinline__ void mbar_expect_tx(uint32_t b, uint32_t bytes) { asm volatile("mbarrier.arrive.expect_tx.shared::cta.b64 _, [%0], %1;" ::"r"(b), "r"(bytes) : "memory"); }
__device__ __forceinline__ void mbar_arrive(uint32_t b) { asm volatile("mbarrier.arrive.shared::cta.b64 _, [%0];" ::"r"(b) : "memory"); }
__device__ __forceinline__ bool mbar_try(uint32_t b, uint32_t par) {
    uint32_t ok;
    asm volatile("{.reg .pred p; mbarrier.try_wait.parity.shared::cta.b64 p, [%1], %2; selp.u32 %0, 1, 0, p;}" : "=r"(ok) : "r"(b), "r"(par) : "memory");
    return ok;
}
__device__ __forceinline__ void mbar_wait(uint32_t b, uint32_t par) {
    asm volatile("{.reg .pred p;\nW: mbarrier.try_wait.parity.shared::cta.b64 p, [%0], %1;\n@!p bra W;}" ::"r"(b), "r"(par) : "memory");
}
__device__ __forceinline__ void bar_sync(int id, int n) { asm volatile("bar.sync %0, %1;" ::"r"(id), "r"(n) : "memory"); }
__device__ __forceinline__ void tma2d(uint32_t dst, const CUtensorMap* m, int c0, int c1, uint32_t bar) {
    asm volatile("cp.async.bulk.tensor.2d.shared::cluster.global.mbarrier::complete_tx::bytes [%0], [%1, {%3, %4}], [%2];" ::"r"(dst), "l"(m), "r"(bar), "r"(c0), "r"(c1) : "memory");
}
__device__ __forceinline__ void tma3d(uint32_t dst, const CUtensorMap* m, int c0, int c1, int c2, uint32_t bar) {
    asm volatile("cp.async.bulk.tensor.3d.shared::cluster.global.mbarrier::complete_tx::bytes [%0], [%1, {%3, %4, %5}], [%2];" ::"r"(dst), "l"(m), "r"(bar), "r"(c0), "r"(c1), "r"(c2) : "memory");
}
__device__ __forceinline__ void tma4d(uint32_t dst, const CUtensorMap* m, int c0, int c1, int c2, int c3, uint32_t bar) {
    asm volatile("cp.async.bulk.tensor.4d.shared::cluster.global.mbarrier::complete_tx::bytes [%0], [%1, {%3, %4, %5, %6}], [%2];" ::"r"(dst), "l"(m), "r"(bar), "r"(c0), "r"(c1), "r"(c2), "r"(c3) : "memory");
}
__device__ __forceinline__ void l2_prefetch(const void* p, uint32_t bytes) { asm volatile("cp.async.bulk.prefetch.L2.global [%0], %1;" ::"l"(p), "r"(bytes) : "memory"); }
__device__ __forceinline__ void pf_map(const CUtensorMap* m) { asm volatile("prefetch.tensormap [%0];" ::"l"(m) : "memory"); }
__device__ __forceinline__ void wg_fence() { asm volatile("wgmma.fence.sync.aligned;" ::: "memory"); }
__device__ __forceinline__ void wg_commit() { asm volatile("wgmma.commit_group.sync.aligned;" ::: "memory"); }
template <int N> __device__ __forceinline__ void wg_wait() { asm volatile("wgmma.wait_group.sync.aligned %0;" ::"n"(N) : "memory"); }
__device__ __forceinline__ void ldsm4(uint32_t* r, uint32_t addr) { asm volatile("ldmatrix.sync.aligned.m8n8.x4.shared.b16 {%0,%1,%2,%3}, [%4];" : "=r"(r[0]), "=r"(r[1]), "=r"(r[2]), "=r"(r[3]) : "r"(addr) : "memory"); }
__device__ __forceinline__ void ldsm4t(uint32_t* r, uint32_t addr) { asm volatile("ldmatrix.sync.aligned.m8n8.x4.trans.shared.b16 {%0,%1,%2,%3}, [%4];" : "=r"(r[0]), "=r"(r[1]), "=r"(r[2]), "=r"(r[3]) : "r"(addr) : "memory"); }
__device__ __forceinline__ void stsm4(uint32_t addr, const uint32_t* r) { asm volatile("stmatrix.sync.aligned.m8n8.x4.shared.b16 [%4], {%0,%1,%2,%3};" ::"r"(r[0]), "r"(r[1]), "r"(r[2]), "r"(r[3]), "r"(addr) : "memory"); }
__device__ __forceinline__ void lds4(uint32_t* r, uint32_t addr) { asm volatile("ld.shared.v4.u32 {%0,%1,%2,%3}, [%4];" : "=r"(r[0]), "=r"(r[1]), "=r"(r[2]), "=r"(r[3]) : "r"(addr) : "memory"); }
__device__ __forceinline__ void sts4(uint32_t addr, const uint32_t* r) { asm volatile("st.shared.v4.u32 [%4], {%0,%1,%2,%3};" ::"r"(r[0]), "r"(r[1]), "r"(r[2]), "r"(r[3]), "r"(addr) : "memory"); }
__device__ __forceinline__ float2 lds2f(uint32_t addr) { float2 v; asm volatile("ld.shared.v2.f32 {%0,%1}, [%2];" : "=f"(v.x), "=f"(v.y) : "r"(addr) : "memory"); return v; }
__device__ __forceinline__ float lds1f(uint32_t addr) { float v; asm volatile("ld.shared.f32 %0, [%1];" : "=f"(v) : "r"(addr) : "memory"); return v; }
__device__ __forceinline__ void sts1f(uint32_t addr, float v) { asm volatile("st.shared.f32 [%0], %1;" ::"r"(addr), "f"(v) : "memory"); }
__device__ __forceinline__ void sts1(uint32_t addr, uint32_t v) { asm volatile("st.shared.u32 [%0], %1;" ::"r"(addr), "r"(v) : "memory"); }
__device__ __forceinline__ void ldg4_rlx(uint32_t* r, const void* p) { asm volatile("{.reg .b128 t; ld.relaxed.gpu.global.b128 t, [%4]; mov.b128 {%0,%1,%2,%3}, t;}" : "=r"(r[0]), "=r"(r[1]), "=r"(r[2]), "=r"(r[3]) : "l"(p) : "memory"); }
__device__ __forceinline__ void ldg2_rlx(uint32_t* r, const void* p) { asm volatile("{.reg .b64 t; ld.relaxed.gpu.global.b64 t, [%2]; mov.b64 {%0,%1}, t;}" : "=r"(r[0]), "=r"(r[1]) : "l"(p) : "memory"); }
__device__ __forceinline__ uint32_t ldg1_rlx(const void* p) { uint32_t v; asm volatile("ld.relaxed.gpu.global.u32 %0, [%1];" : "=r"(v) : "l"(p) : "memory"); return v; }
__device__ __forceinline__ void stg4_rlx(void* p, uint32_t a, uint32_t b, uint32_t c, uint32_t d) { asm volatile("{.reg .b128 t; mov.b128 t, {%1,%2,%3,%4}; st.relaxed.gpu.global.b128 [%0], t;}" ::"l"(p), "r"(a), "r"(b), "r"(c), "r"(d) : "memory"); }
__device__ __forceinline__ void stg2_rlx(void* p, uint32_t a, uint32_t b) { asm volatile("{.reg .b64 t; mov.b64 t, {%1,%2}; st.relaxed.gpu.global.b64 [%0], t;}" ::"l"(p), "r"(a), "r"(b) : "memory"); }
__device__ __forceinline__ void stg1_rlx(void* p, uint32_t a) { asm volatile("st.relaxed.gpu.global.u32 [%0], %1;" ::"l"(p), "r"(a) : "memory"); }
__device__ __forceinline__ void ldg4_nc(uint32_t* r, const void* p) { asm volatile("ld.global.nc.L1::no_allocate.v4.u32 {%0,%1,%2,%3}, [%4];" : "=r"(r[0]), "=r"(r[1]), "=r"(r[2]), "=r"(r[3]) : "l"(p)); }
__device__ __forceinline__ uint64_t mkdesc(uint32_t addr, uint32_t lbo, uint32_t sbo, uint32_t sw) { return (uint64_t)((addr & 0x3FFFF) >> 4) | ((uint64_t)(lbo >> 4) << 16) | ((uint64_t)(sbo >> 4) << 32) | ((uint64_t)sw << 62); }
__device__ __forceinline__ uint32_t pack2(float lo, float hi) { uint32_t r; asm("cvt.rn.bf16x2.f32 %0, %1, %2;" : "=r"(r) : "f"(hi), "f"(lo)); return r; }
__device__ __forceinline__ float blo(uint32_t v) { return __uint_as_float(v << 16); }
__device__ __forceinline__ float bhi(uint32_t v) { return __uint_as_float(v & 0xffff0000u); }
__device__ __forceinline__ float rbf(float x) { return blo(pack2(x, 0.f)); }
__device__ __forceinline__ uint32_t hf2(uint32_t a, uint32_t b, uint32_t c) { uint32_t r; asm("fma.rn.bf16x2 %0, %1, %2, %3;" : "=r"(r) : "r"(a), "r"(b), "r"(c)); return r; }
__device__ __forceinline__ uint32_t movm(uint32_t a) { uint32_t r; asm volatile("movmatrix.sync.aligned.m8n8.trans.b16 %0, %1;" : "=r"(r) : "r"(a)); return r; }
__device__ __forceinline__ float ex2(float x) { float r; asm("ex2.approx.ftz.f32 %0, %1;" : "=f"(r) : "f"(x)); return r; }
__device__ __forceinline__ void mma16(float* d, uint32_t a0, uint32_t a1, uint32_t a2, uint32_t a3, uint32_t b0, uint32_t b1) {
    asm("mma.sync.aligned.m16n8k16.row.col.f32.bf16.bf16.f32 {%0,%1,%2,%3}, {%4,%5,%6,%7}, {%8,%9}, {%0,%1,%2,%3};"
                 : "+f"(d[0]), "+f"(d[1]), "+f"(d[2]), "+f"(d[3]) : "r"(a0), "r"(a1), "r"(a2), "r"(a3), "r"(b0), "r"(b1));
}
__device__ __forceinline__ void mma8(float* d, uint32_t a0, uint32_t a1, uint32_t b0) {
    asm("mma.sync.aligned.m16n8k8.row.col.f32.bf16.bf16.f32 {%0,%1,%2,%3}, {%4,%5}, {%6}, {%0,%1,%2,%3};"
                 : "+f"(d[0]), "+f"(d[1]), "+f"(d[2]), "+f"(d[3]) : "r"(a0), "r"(a1), "r"(b0));
}
__device__ __forceinline__ uint32_t umax4(const uint32_t* v, uint32_t m) { return max(max(max(v[0], v[1]), max(v[2], v[3])), m); }
__device__ __forceinline__ uint32_t fkey(float f) { const uint32_t u = __float_as_uint(f); return u ^ (((int)u >> 31) | 0x80000000u); }
__device__ __forceinline__ float rcp(float x) { float r; asm("rcp.approx.ftz.f32 %0, %1;" : "=f"(r) : "f"(x)); return r; }
__device__ __forceinline__ float sigm(float x) { return rcp(1.f + ex2(x * -1.4426950408889634f)); }
__device__ __forceinline__ void mma16c(float* d, uint32_t a0, uint32_t a1, uint32_t a2, uint32_t a3, uint32_t b0, uint32_t b1, float c0, float c1) {
    asm("mma.sync.aligned.m16n8k16.row.col.f32.bf16.bf16.f32 {%0,%1,%2,%3}, {%4,%5,%6,%7}, {%8,%9}, {%10,%11,%12,%12};"
                 : "=f"(d[0]), "=f"(d[1]), "=f"(d[2]), "=f"(d[3]) : "r"(a0), "r"(a1), "r"(a2), "r"(a3), "r"(b0), "r"(b1), "f"(c0), "f"(c1), "f"(0.f));
}
__device__ __forceinline__ void ldsm2t(uint32_t* r, uint32_t addr) { asm volatile("ldmatrix.sync.aligned.m8n8.x2.trans.shared.b16 {%0,%1}, [%2];" : "=r"(r[0]), "=r"(r[1]) : "r"(addr) : "memory"); }
__device__ __forceinline__ void stsm2(uint32_t addr, uint32_t a, uint32_t b) { asm volatile("stmatrix.sync.aligned.m8n8.x2.shared.b16 [%2], {%0,%1};" ::"r"(a), "r"(b), "r"(addr) : "memory"); }
__device__ __forceinline__ void lds2(uint32_t* r, uint32_t addr) { asm volatile("ld.shared.v2.u32 {%0,%1}, [%2];" : "=r"(r[0]), "=r"(r[1]) : "r"(addr) : "memory"); }
__device__ __forceinline__ void sts2(uint32_t addr, uint32_t a, uint32_t b) { asm volatile("st.shared.v2.u32 [%2], {%0,%1};" ::"r"(a), "r"(b), "r"(addr) : "memory"); }
__device__ __forceinline__ void sts16(uint32_t addr, uint32_t v) { asm volatile("st.shared.u16 [%0], %1;" ::"r"(addr), "h"((unsigned short)v) : "memory"); }
__device__ __forceinline__ uint32_t lds1(uint32_t addr) { uint32_t v; asm volatile("ld.shared.u32 %0, [%1];" : "=r"(v) : "r"(addr) : "memory"); return v; }
__device__ __forceinline__ bool elect1() { uint32_t p; asm volatile("{.reg .pred P; elect.sync _|P, 0xffffffff; selp.u32 %0, 1, 0, P;}" : "=r"(p)); return p; }
__device__ __forceinline__ void tma2d_mc(uint32_t dst, const CUtensorMap* m, int c0, int c1, uint32_t bar) {
    asm volatile("cp.async.bulk.tensor.2d.shared::cluster.global.mbarrier::complete_tx::bytes.multicast::cluster [%0], [%1, {%3, %4}], [%2], %5;" ::"r"(dst), "l"(m), "r"(bar), "r"(c0), "r"(c1), "h"((unsigned short)3) : "memory");
}
__device__ __forceinline__ void tma3d_mc(uint32_t dst, const CUtensorMap* m, int c0, int c1, int c2, uint32_t bar) {
    asm volatile("cp.async.bulk.tensor.3d.shared::cluster.global.mbarrier::complete_tx::bytes.multicast::cluster [%0], [%1, {%3, %4, %5}], [%2], %6;" ::"r"(dst), "l"(m), "r"(bar), "r"(c0), "r"(c1), "r"(c2), "h"((unsigned short)3) : "memory");
}
__device__ __forceinline__ void tma4d_mc(uint32_t dst, const CUtensorMap* m, int c0, int c1, int c2, int c3, uint32_t bar) {
    asm volatile("cp.async.bulk.tensor.4d.shared::cluster.global.mbarrier::complete_tx::bytes.multicast::cluster [%0], [%1, {%3, %4, %5, %6}], [%2], %7;" ::"r"(dst), "l"(m), "r"(bar), "r"(c0), "r"(c1), "r"(c2), "r"(c3), "h"((unsigned short)3) : "memory");
}
__device__ __forceinline__ void mbar_arrive_cl(uint32_t b) { asm volatile("mbarrier.arrive.shared::cluster.b64 _, [%0];" ::"r"(b) : "memory"); }
__device__ __forceinline__ uint32_t hm2(uint32_t a, uint32_t b) { uint32_t r; asm("mul.rn.bf16x2 %0, %1, %2;" : "=r"(r) : "r"(a), "r"(b)); return r; }
__device__ __forceinline__ uint32_t clock32() { uint32_t c; asm volatile("mov.u32 %0, %clock;" : "=r"(c)); return c; }
__device__ __forceinline__ uint32_t ldsm1(uint32_t addr) { uint32_t r; asm volatile("ldmatrix.sync.aligned.m8n8.x1.shared.b16 {%0}, [%1];" : "=r"(r) : "r"(addr) : "memory"); return r; }
__device__ __forceinline__ float rsq(float x) { float r; asm("rsqrt.approx.ftz.f32 %0, %1;" : "=f"(r) : "f"(x)); return r; }
__device__ __forceinline__ void pause_until(uint32_t t0, uint32_t n) {
    asm volatile("{.reg .pred p; .reg .u32 t;\nP: mov.u32 t, %clock; sub.u32 t, t, %0; setp.lt.u32 p, t, %1;\n@p bra.uni P;}" ::"r"(t0), "r"(n) : "memory");
}
__device__ __forceinline__ void pause(uint32_t n) { if (n) { const uint32_t t = clock32(); while (clock32() - t < n) {} } }
__device__ __forceinline__ uint32_t wbuf(int it) {
    const uint32_t v = it < 4 ? it + 8 : (uint32_t)(0x8302418302b1a908ull >> (4 * it - 16)) & 15;
    return v * WST + (v >> 3) * (OFF_W - 8 * WST);
}
__device__ __forceinline__ uint32_t wobuf(int w) { return ((0x30241765u >> (4 * w)) & 7) * WST; }
__device__ __forceinline__ uint32_t inc(uint32_t v) { uint32_t r; asm volatile("{.reg .u32 t; or.b32 t, %1, 255; add.u32 %0, t, 1;}" : "=r"(r) : "r"(v)); return r; }
__device__ __forceinline__ uint32_t ldg1_acq(const void* p) { uint32_t v; asm volatile("ld.acquire.gpu.global.u32 %0, [%1];" : "=r"(v) : "l"(p) : "memory"); return v; }
__device__ __forceinline__ void tma3d_st(const CUtensorMap* m, int c0, int c1, int c2, uint32_t src) {
    asm volatile("cp.async.bulk.tensor.3d.global.shared::cta.bulk_group [%0, {%2, %3, %4}], [%1];" ::"l"(m), "r"(src), "r"(c0), "r"(c1), "r"(c2) : "memory");
}
__device__ __forceinline__ uint32_t nz(uint32_t v) { uint32_t r; asm("max.u32 %0, %1, 1;" : "=r"(r) : "r"(v)); return r; }
__device__ __forceinline__ uint32_t tagw(uint32_t w, uint32_t tc) { return ((w & 0x8000ffffu) | min(max(w & 0x7fff0000u, 0x20000000u), 0x5fff0000u)) + tc; }
template <int S_> __device__ __forceinline__ void await7(uint32_t (*r)[4], const char* const* p, uint32_t fz, uint32_t stale) {
    if (S_ == 0) asm volatile("{.reg .b128 t; .reg .pred p; .reg .u32 m, k, n;\nmov.u32 n, %clock; or.b32 n, n, %37; shr.u32 n, n, 31;\nL:\n"
        "min.u32 m, %0, %4; min.u32 m, m, %8; min.u32 m, m, %12; min.u32 m, m, %16; min.u32 m, m, %20; min.u32 m, m, %24;\n"
        "setp.eq.u32 p, m, 0; vote.sync.any.pred p, p, 0xffffffff; add.u32 n, n, 1; setp.lt.and.u32 p, n, %36, p;\n@!p bra.uni D;\n"
        "setp.eq.u32 p, %0, 0; mov.b128 t, {%0,%1,%2,%3}; @p ld.relaxed.gpu.global.b128 t, [%28+%35]; mov.b128 {%0,%1,%2,%3}, t;\n"
        "setp.eq.u32 p, %4, 0; mov.b128 t, {%4,%5,%6,%7}; @p ld.relaxed.gpu.global.b128 t, [%29+%35]; mov.b128 {%4,%5,%6,%7}, t;\n"
        "setp.eq.u32 p, %8, 0; mov.b128 t, {%8,%9,%10,%11}; @p ld.relaxed.gpu.global.b128 t, [%30+%35]; mov.b128 {%8,%9,%10,%11}, t;\n"
        "setp.eq.u32 p, %12, 0; mov.b128 t, {%12,%13,%14,%15}; @p ld.relaxed.gpu.global.b128 t, [%31+%35]; mov.b128 {%12,%13,%14,%15}, t;\n"
        "setp.eq.u32 p, %16, 0; mov.b128 t, {%16,%17,%18,%19}; @p ld.relaxed.gpu.global.b128 t, [%32+%35]; mov.b128 {%16,%17,%18,%19}, t;\n"
        "setp.eq.u32 p, %20, 0; mov.b128 t, {%20,%21,%22,%23}; @p ld.relaxed.gpu.global.b128 t, [%33+%35]; mov.b128 {%20,%21,%22,%23}, t;\n"
        "setp.eq.u32 p, %24, 0; mov.b128 t, {%24,%25,%26,%27}; @p ld.relaxed.gpu.global.b128 t, [%34+%35]; mov.b128 {%24,%25,%26,%27}, t;\n"
        "bra.uni L;\nD:}"
        : "+r"(r[0][0]), "+r"(r[0][1]), "+r"(r[0][2]), "+r"(r[0][3]), "+r"(r[1][0]), "+r"(r[1][1]), "+r"(r[1][2]), "+r"(r[1][3]), "+r"(r[2][0]), "+r"(r[2][1]), "+r"(r[2][2]), "+r"(r[2][3]), "+r"(r[3][0]), "+r"(r[3][1]), "+r"(r[3][2]), "+r"(r[3][3]), "+r"(r[4][0]), "+r"(r[4][1]), "+r"(r[4][2]), "+r"(r[4][3]), "+r"(r[5][0]), "+r"(r[5][1]), "+r"(r[5][2]), "+r"(r[5][3]), "+r"(r[6][0]), "+r"(r[6][1]), "+r"(r[6][2]), "+r"(r[6][3])
        : "l"(p[0]), "l"(p[1]), "l"(p[2]), "l"(p[3]), "l"(p[4]), "l"(p[5]), "l"(p[6]), "n"((4 - S_) * 524288), "n"(SPIN_LIMIT), "r"(fz), "r"(stale) : "memory");
    else asm volatile("{.reg .b128 t; .reg .pred p; .reg .u32 m, k, n;\nmov.u32 n, %clock; or.b32 n, n, %37; shr.u32 n, n, 31;\nL:\n"
        "xor.b32 m, %0, %38; xor.b32 k, %4, %38; and.b32 m, m, k; xor.b32 k, %8, %38; and.b32 m, m, k; xor.b32 k, %12, %38; and.b32 m, m, k; xor.b32 k, %16, %38; and.b32 m, m, k;\n"
        "xor.b32 k, %20, %38; and.b32 m, m, k; xor.b32 k, %24, %38; and.b32 m, m, k; and.b32 m, m, 0x40000000;\n"
        "setp.eq.u32 p, m, 0; vote.sync.any.pred p, p, 0xffffffff; add.u32 n, n, 1; setp.lt.and.u32 p, n, %36, p;\n@!p bra.uni D;\n"
        "xor.b32 k, %0, %38; and.b32 k, k, 0x40000000; setp.eq.u32 p, k, 0; mov.b128 t, {%0,%1,%2,%3}; @p ld.relaxed.gpu.global.b128 t, [%28+%35]; mov.b128 {%0,%1,%2,%3}, t;\n"
        "xor.b32 k, %4, %38; and.b32 k, k, 0x40000000; setp.eq.u32 p, k, 0; mov.b128 t, {%4,%5,%6,%7}; @p ld.relaxed.gpu.global.b128 t, [%29+%35]; mov.b128 {%4,%5,%6,%7}, t;\n"
        "xor.b32 k, %8, %38; and.b32 k, k, 0x40000000; setp.eq.u32 p, k, 0; mov.b128 t, {%8,%9,%10,%11}; @p ld.relaxed.gpu.global.b128 t, [%30+%35]; mov.b128 {%8,%9,%10,%11}, t;\n"
        "xor.b32 k, %12, %38; and.b32 k, k, 0x40000000; setp.eq.u32 p, k, 0; mov.b128 t, {%12,%13,%14,%15}; @p ld.relaxed.gpu.global.b128 t, [%31+%35]; mov.b128 {%12,%13,%14,%15}, t;\n"
        "xor.b32 k, %16, %38; and.b32 k, k, 0x40000000; setp.eq.u32 p, k, 0; mov.b128 t, {%16,%17,%18,%19}; @p ld.relaxed.gpu.global.b128 t, [%32+%35]; mov.b128 {%16,%17,%18,%19}, t;\n"
        "xor.b32 k, %20, %38; and.b32 k, k, 0x40000000; setp.eq.u32 p, k, 0; mov.b128 t, {%20,%21,%22,%23}; @p ld.relaxed.gpu.global.b128 t, [%33+%35]; mov.b128 {%20,%21,%22,%23}, t;\n"
        "xor.b32 k, %24, %38; and.b32 k, k, 0x40000000; setp.eq.u32 p, k, 0; mov.b128 t, {%24,%25,%26,%27}; @p ld.relaxed.gpu.global.b128 t, [%34+%35]; mov.b128 {%24,%25,%26,%27}, t;\n"
        "bra.uni L;\nD:}"
        : "+r"(r[0][0]), "+r"(r[0][1]), "+r"(r[0][2]), "+r"(r[0][3]), "+r"(r[1][0]), "+r"(r[1][1]), "+r"(r[1][2]), "+r"(r[1][3]), "+r"(r[2][0]), "+r"(r[2][1]), "+r"(r[2][2]), "+r"(r[2][3]), "+r"(r[3][0]), "+r"(r[3][1]), "+r"(r[3][2]), "+r"(r[3][3]), "+r"(r[4][0]), "+r"(r[4][1]), "+r"(r[4][2]), "+r"(r[4][3]), "+r"(r[5][0]), "+r"(r[5][1]), "+r"(r[5][2]), "+r"(r[5][3]), "+r"(r[6][0]), "+r"(r[6][1]), "+r"(r[6][2]), "+r"(r[6][3])
        : "l"(p[0]), "l"(p[1]), "l"(p[2]), "l"(p[3]), "l"(p[4]), "l"(p[5]), "l"(p[6]), "n"((4 - S_) * 524288), "n"(SPIN_LIMIT), "r"(fz), "r"(stale) : "memory");
}
template <class T> __device__ __forceinline__ T* pinp(T* p) { return (T*)__shfl_xor_sync(~0u, (unsigned long long)p, 0); }
__device__ __forceinline__ float fsel(bool c, float a, float b) { float r; asm("{.reg .pred p; setp.ne.u32 p, %3, 0; selp.f32 %0, %1, %2, p;}" : "=f"(r) : "f"(a), "f"(b), "r"((int)c)); return r; }
__device__ __forceinline__ void stg4_if(bool c, void* p, uint32_t a, uint32_t b, uint32_t d, uint32_t e) {
    asm volatile("{.reg .b128 t; .reg .pred p; setp.ne.u32 p, %5, 0; mov.b128 t, {%1,%2,%3,%4}; @p st.relaxed.gpu.global.b128 [%0], t;}" ::"l"(p), "r"(a), "r"(b), "r"(d), "r"(e), "r"((int)c) : "memory");
}
__device__ __forceinline__ void stg2_if(bool c, void* p, uint32_t a, uint32_t b) {
    asm volatile("{.reg .b64 t; .reg .pred p; setp.ne.u32 p, %3, 0; mov.b64 t, {%1,%2}; @p st.relaxed.gpu.global.b64 [%0], t;}" ::"l"(p), "r"(a), "r"(b), "r"((int)c) : "memory");
}
__device__ __forceinline__ void stg1_if(bool c, void* p, uint32_t a) {
    asm volatile("{.reg .pred p; setp.ne.u32 p, %2, 0; @p st.relaxed.gpu.global.u32 [%0], %1;}" ::"l"(p), "r"(a), "r"((int)c) : "memory");
}
__device__ __forceinline__ void ldg4_again(uint32_t* r, const void* p) {
    asm volatile("{.reg .b128 t; .reg .pred p; setp.eq.u32 p, %3, 0; mov.b128 t, {%0,%1,%2,%3}; @p ld.relaxed.gpu.global.b128 t, [%4]; mov.b128 {%0,%1,%2,%3}, t;}"
                 : "+r"(r[0]), "+r"(r[1]), "+r"(r[2]), "+r"(r[3]) : "l"(p) : "memory");
}
__device__ __forceinline__ void wgmma_rs_n192(float* d, const uint32_t* a, uint64_t bdesc, int accum) {
    asm volatile("{.reg .pred p; setp.ne.b32 p, %101, 0; wgmma.mma_async.sync.aligned.m64n192k16.f32.bf16.bf16 {%0,%1,%2,%3,%4,%5,%6,%7,%8,%9,%10,%11,%12,%13,%14,%15,%16,%17,%18,%19,%20,%21,%22,%23,%24,%25,%26,%27,%28,%29,%30,%31,%32,%33,%34,%35,%36,%37,%38,%39,%40,%41,%42,%43,%44,%45,%46,%47,%48,%49,%50,%51,%52,%53,%54,%55,%56,%57,%58,%59,%60,%61,%62,%63,%64,%65,%66,%67,%68,%69,%70,%71,%72,%73,%74,%75,%76,%77,%78,%79,%80,%81,%82,%83,%84,%85,%86,%87,%88,%89,%90,%91,%92,%93,%94,%95}, {%96,%97,%98,%99}, %100, p, 1, 1, 1;}"
        : "+f"(d[0]),"+f"(d[1]),"+f"(d[2]),"+f"(d[3]),"+f"(d[4]),"+f"(d[5]),"+f"(d[6]),"+f"(d[7]),"+f"(d[8]),"+f"(d[9]),"+f"(d[10]),"+f"(d[11]),"+f"(d[12]),"+f"(d[13]),"+f"(d[14]),"+f"(d[15]),"+f"(d[16]),"+f"(d[17]),"+f"(d[18]),"+f"(d[19]),"+f"(d[20]),"+f"(d[21]),"+f"(d[22]),"+f"(d[23]),"+f"(d[24]),"+f"(d[25]),"+f"(d[26]),"+f"(d[27]),"+f"(d[28]),"+f"(d[29]),"+f"(d[30]),"+f"(d[31]),"+f"(d[32]),"+f"(d[33]),"+f"(d[34]),"+f"(d[35]),"+f"(d[36]),"+f"(d[37]),"+f"(d[38]),"+f"(d[39]),"+f"(d[40]),"+f"(d[41]),"+f"(d[42]),"+f"(d[43]),"+f"(d[44]),"+f"(d[45]),"+f"(d[46]),"+f"(d[47]),"+f"(d[48]),"+f"(d[49]),"+f"(d[50]),"+f"(d[51]),"+f"(d[52]),"+f"(d[53]),"+f"(d[54]),"+f"(d[55]),"+f"(d[56]),"+f"(d[57]),"+f"(d[58]),"+f"(d[59]),"+f"(d[60]),"+f"(d[61]),"+f"(d[62]),"+f"(d[63]),"+f"(d[64]),"+f"(d[65]),"+f"(d[66]),"+f"(d[67]),"+f"(d[68]),"+f"(d[69]),"+f"(d[70]),"+f"(d[71]),"+f"(d[72]),"+f"(d[73]),"+f"(d[74]),"+f"(d[75]),"+f"(d[76]),"+f"(d[77]),"+f"(d[78]),"+f"(d[79]),"+f"(d[80]),"+f"(d[81]),"+f"(d[82]),"+f"(d[83]),"+f"(d[84]),"+f"(d[85]),"+f"(d[86]),"+f"(d[87]),"+f"(d[88]),"+f"(d[89]),"+f"(d[90]),"+f"(d[91]),"+f"(d[92]),"+f"(d[93]),"+f"(d[94]),"+f"(d[95])
        : "r"(a[0]), "r"(a[1]), "r"(a[2]), "r"(a[3]), "l"(bdesc), "r"(accum));
}
__device__ __forceinline__ void wgmma_rs_n48(float* d, const uint32_t* a, uint64_t bdesc, int accum) {
    asm volatile("{.reg .pred p; setp.ne.b32 p, %29, 0; wgmma.mma_async.sync.aligned.m64n48k16.f32.bf16.bf16 {%0,%1,%2,%3,%4,%5,%6,%7,%8,%9,%10,%11,%12,%13,%14,%15,%16,%17,%18,%19,%20,%21,%22,%23}, {%24,%25,%26,%27}, %28, p, 1, 1, 1;}"
        : "+f"(d[0]),"+f"(d[1]),"+f"(d[2]),"+f"(d[3]),"+f"(d[4]),"+f"(d[5]),"+f"(d[6]),"+f"(d[7]),"+f"(d[8]),"+f"(d[9]),"+f"(d[10]),"+f"(d[11]),"+f"(d[12]),"+f"(d[13]),"+f"(d[14]),"+f"(d[15]),"+f"(d[16]),"+f"(d[17]),"+f"(d[18]),"+f"(d[19]),"+f"(d[20]),"+f"(d[21]),"+f"(d[22]),"+f"(d[23])
        : "r"(a[0]), "r"(a[1]), "r"(a[2]), "r"(a[3]), "l"(bdesc), "r"(accum));
}
__device__ __forceinline__ void wgmma_rs_n80(float* d, const uint32_t* a, uint64_t bdesc, int accum) {
    asm volatile("{.reg .pred p; setp.ne.b32 p, %45, 0; wgmma.mma_async.sync.aligned.m64n80k16.f32.bf16.bf16 {%0,%1,%2,%3,%4,%5,%6,%7,%8,%9,%10,%11,%12,%13,%14,%15,%16,%17,%18,%19,%20,%21,%22,%23,%24,%25,%26,%27,%28,%29,%30,%31,%32,%33,%34,%35,%36,%37,%38,%39}, {%40,%41,%42,%43}, %44, p, 1, 1, 1;}"
        : "+f"(d[0]),"+f"(d[1]),"+f"(d[2]),"+f"(d[3]),"+f"(d[4]),"+f"(d[5]),"+f"(d[6]),"+f"(d[7]),"+f"(d[8]),"+f"(d[9]),"+f"(d[10]),"+f"(d[11]),"+f"(d[12]),"+f"(d[13]),"+f"(d[14]),"+f"(d[15]),"+f"(d[16]),"+f"(d[17]),"+f"(d[18]),"+f"(d[19]),"+f"(d[20]),"+f"(d[21]),"+f"(d[22]),"+f"(d[23]),"+f"(d[24]),"+f"(d[25]),"+f"(d[26]),"+f"(d[27]),"+f"(d[28]),"+f"(d[29]),"+f"(d[30]),"+f"(d[31]),"+f"(d[32]),"+f"(d[33]),"+f"(d[34]),"+f"(d[35]),"+f"(d[36]),"+f"(d[37]),"+f"(d[38]),"+f"(d[39])
        : "r"(a[0]), "r"(a[1]), "r"(a[2]), "r"(a[3]), "l"(bdesc), "r"(accum));
}

__global__ void __cluster_dims__(2, 1, 1) __launch_bounds__(384, 1)
fused_kernel(const __nv_bfloat16* __restrict__ xin, const __nv_bfloat16* __restrict__ wmod, const __nv_bfloat16* __restrict__ cvec, Scratch* __restrict__ S,
             const __nv_bfloat16* __restrict__ wqkv, const __nv_bfloat16* __restrict__ wo, __nv_bfloat16* __restrict__ out,
             const __nv_bfloat16* __restrict__ wr, const __nv_bfloat16* __restrict__ wg, const __nv_bfloat16* __restrict__ wu,
             const __nv_bfloat16* __restrict__ wd,
             const __grid_constant__ CUtensorMap mm, const __grid_constant__ CUtensorMap mx, const __grid_constant__ CUtensorMap mw,
             const __grid_constant__ CUtensorMap mt, const __grid_constant__ CUtensorMap mo, const __grid_constant__ CUtensorMap mg,
             const __grid_constant__ CUtensorMap mu, const __grid_constant__ CUtensorMap md,
             const __grid_constant__ CUtensorMap mw2, const __grid_constant__ CUtensorMap mout,
             const __grid_constant__ CUtensorMap mo2) {
    extern __shared__ __align__(1024) char sm_raw[];
    const int bid = blockIdx.x;
    const uint32_t sm = ((bid & 1) << 24) + SM0;
    STAMP(30);
    const uint32_t t_start = clock32();
    if (bid < CPF && threadIdx.x == 0)
        asm volatile("cp.async.bulk.prefetch.tensor.2d.L2.global [%0, {%1, %2}];" ::"l"(&mm), "r"((bid & 1) * 640 + (bid >> 4) * 64), "r"(((bid >> 1) & 7) * 80) : "memory");
    const int cl = bid >> 1, rank = bid & 1, c7 = ((cl - 36) * 37) >> 8;
    const int grp = cl < 4 ? 0 : (cl < 36 ? (cl - 4) & 7 : cl - 35 - 7 * c7);
    const int ti = grp * 2 + rank;
    auto ldx = [&](int c) { mbar_expect_tx(BAR(B_XF + c), 16384); tma3d(sm + c * 16384, &mx, c * 64, ti >> 3, (ti & 7) * 128, BAR(B_XF + c)); };
    if (threadIdx.x == 256 && bid < 128) {
        mbar_init(BAR(B_XF), 1); mbar_init(BAR(B_XF + 1), 1);
        if (XDELAY > 1) pause_until(t_start, XDELAY);
        ldx(0); ldx(1);
        STAMPT(22, 256);
#pragma unroll
        for (int i = 2; i < 10; i++) mbar_init(BAR(B_XF + i), 1);
        mbar_init(BAR(B_T0), 1);
        asm volatile("fence.mbarrier_init.release.cluster;" ::: "memory");
        ldx(2); ldx(3); ldx(4);
    }
    const int warp = __shfl_sync(~0u, threadIdx.x >> 5, 0);

#define PIN(v) __shfl_xor_sync(~0u, (v), 0)
#define LANE_VARS const int tid = PIN(threadIdx.x), lane = tid & 31, g = lane >> 2, q = lane & 3; \
    const uint32_t frow = (lane & 7) + (lane >> 4) * 8, fh = (lane >> 3) & 1;
    if (bid >= 128) {
        LANE_VARS
        const int h = bid - 128;
        if (warp >= 8) {
            if (warp == 8) return;
            const int t = tid - 288;
            if (t < 90) stg4_rlx(&S->tab[(5 + t / 9) * 4 + h][t % 9], 0u, 0u, 0u, 0u);
            __syncwarp();
            asm volatile("bar.arrive 1, 352;" ::: "memory");
            bar_sync(2, 96);
            if (t == 0) asm volatile("red.release.gpu.global.add.u32 [%0], 32;" ::"l"(&S->cnt) : "memory");
            return;
        }
        const uint32_t slot = sm + warp * 20480, bar = BAR(warp * 2);
        auto column = [&](int job) {
            const int n = job * 4 + h;
            return job < 10 ? ((h & 1) ? (job < 5 ? 10 : 30) : (job < 5 ? 0 : 10)) + (n >> 1) : (n < 50 ? n - 10 : n);
        };
        auto load = [&](int job) {
            mbar_expect_tx(bar + (job & 1) * 8, 10240);
            tma2d(slot + (job & 1) * 10240, &mm, column(job) * 64, warp * 80, bar + (job & 1) * 8);
        };
        if (elect1()) { mbar_init(bar, 1); mbar_init(bar + 8, 1); load(0); }
        __syncwarp();
        uint32_t b[10];
#pragma unroll
        for (int s = 0; s < 10; s++) b[s] = ldg1_rlx((const uint32_t*)cvec + warp * 40 + s * 4 + q);
        if (lane < 8 && warp < 5) stg4_rlx(&S->tab[warp * 4 + h][lane], 0u, 0u, 0u, 0u);
#pragma unroll
        for (int s = 0; s < 10; s++) b[s] = pack2(blo(b[s]) * sigm(blo(b[s])), bhi(b[s]) * sigm(bhi(b[s])));
        const uint32_t fa = slot + frow * 128 + ((fh ^ (lane & 7)) << 4);
        const int c0 = (lane >> 3) * 16 + (lane & 1) * 8 + (lane & 6);
#pragma unroll 1
        for (int job = 0; job < 15; job++) {
            uint32_t w2 = 0;
            if (job >= 5) w2 = ldg1_rlx(wr + (column(job) % 10) * 64 + c0);

            mbar_wait(bar + (job & 1) * 8, (job >> 1) & 1);
            if (job == 0) { if (elect1()) load(1); __syncwarp(); }
            float d[4][4] = {};
#pragma unroll
            for (int s = 0; s < 5; s++) {
#pragma unroll
                for (int m = 0; m < 4; m++) { uint32_t a[4]; ldsm4t(a, (fa ^ (m * 32)) + (job & 1) * 10240 + s * 2048); mma16(d[m], a[0], a[1], a[2], a[3], b[2 * s], b[2 * s + 1]); }
            }
            const uint32_t red = sm + OFF_W + (job & 1) * 2048;
            sts1f(red + (warp * 64 + q * 8 + g) * 4, q == 0 ? d[0][0] : (q == 1 ? d[0][2] : (q == 2 ? d[1][0] : d[1][2])));
            sts1f(red + (warp * 64 + 32 + q * 8 + g) * 4, q == 0 ? d[2][0] : (q == 1 ? d[2][2] : (q == 2 ? d[3][0] : d[3][2])));
            __syncwarp();
            if (HPAUSE && job == HJOB) pause_until(t_start, HPAUSE);
            if (job < 13 && elect1()) load(job + 2);
            __syncwarp();
            bar_sync(0, 256);
            if (job == 5) bar_sync(1, 352);
            if (warp == (job & 7)) {
                float y0 = 0.f, y1 = 0.f;
#pragma unroll
                for (int w = 0; w < 8; w++) { const float2 v = lds2f(red + (w * 64 + c0) * 4); y0 += v.x; y1 += v.y; }
                const uint32_t t = hf2(pack2(y0, y1), 0x3f803f80u, ((h & 1) && job < 10) ? 0x3f803f80u : 0x80008000u);
                uint32_t* const p = (uint32_t*)&S->tab[job * 4 + h][0];
                stg1_rlx(p + lane, nz(t));
                float dot = fmaf(blo(t), blo(w2), bhi(t) * bhi(w2));
#pragma unroll
                for (int o = 16; o; o >>= 1) dot += __shfl_xor_sync(~0u, dot, o);
                if (lane == 0) stg1_rlx(p + 32, dot == 0.f ? 0x80000000u : __float_as_uint(dot));
            }
            if (job == 0) STAMP(27);
            if (job == 8) STAMP(28);
        }
        STAMP(17);
        return;
    }
    uint32_t ep0;
    if (__builtin_expect(warp == 8, 1)) {
        asm volatile("barrier.cluster.arrive.relaxed.aligned;" ::: "memory");
        if (elect1()) {
#pragma unroll 1
            for (int c = 5; c < 10; c++) ldx(c);
        }
        __syncwarp();
    } else {
        if (warp < 8) {
            if (elect1()) {
#pragma unroll
                for (int i = 0; i < 8; i++) { const int b = B_WF + warp * 8 + i; mbar_init(BAR(b), b >= B_WE ? 16 : (b >= B_G2 ? 8 : (b >= B_EP ? 2 : (b == B_WO ? 7 : 1)))); }
                asm volatile("fence.mbarrier_init.release.cluster;" ::: "memory");
            }
            __syncwarp();
        }
        if (warp == 9) ep0 = ldg1_rlx(&S->cnt);
        asm volatile("barrier.cluster.arrive.relaxed.aligned;" ::: "memory");
    }
    const int sl = cl < 4 ? 4 + cl : (cl < 36 ? (cl - 4) >> 3 : 4 + c7);
    const int j = sl ^ (((sl + 2) >> 2) & (SWAPM >> grp) & 1), role = ti * 8 + j, odd = j & 1;
    const int fi = j * 16 + ti;
    const int al = ((j + 1) & 2) == 0;
    Exch* const X = &S->x;
    if (warp >= 8) {
        asm volatile("setmaxnreg.dec.sync.aligned.u32 72;");
        if (warp == 8) {
            asm volatile("barrier.cluster.wait.aligned;" ::: "memory");
            if (!elect1()) return;
            const int col_main = 80 * j + 16 * odd, col_tail = 80 * j + (odd ? 0 : 64);
            auto load_w = [&](int it) {
                const uint32_t b = BAR(B_WF + it), dst = sm + wbuf(it) + rank * 6144;
                mbar_expect_tx(b, WST);
                tma4d_mc(dst, al ? &mw2 : &mw, 0, it * 32 + rank * 16, col_main >> (5 + al), 0, b);
                tma3d_mc(dst + 12288 - rank * 4608, &mt, col_tail, it * 32 + rank * 16, 0, b);
            };
            int it = 0, wn = 0, gn = 0;
#pragma unroll 1
            for (int r = -2; r < 19; r++) {
                if (r == -2 && WLATE) mbar_wait(BAR(B_XF + WLATE), 0);
                if (r == -1) mbar_wait(BAR(B_XF + XWAIT), 0);
                if (r >= 0) mbar_wait(BAR(B_WE + r), 0);
                const int lim = min(r < 2 ? (r == 1 ? 7 : 2 * r + 6) : r + 7, 20);
#pragma unroll 1
                for (; it < lim; it++) load_w(it);
                if (r == -1 || r == 0) l2_prefetch(wqkv + (size_t)(384 + r * 256 + role * 2) * 1920, 2 * 3840);
                if (r == 0) l2_prefetch(wo + role * 3200, 6400);
                if (MPF == 1 && r >= MPF0 && r < MPF0 + 5) l2_prefetch(wmod + (size_t)(role * 5 + r - MPF0) * 3840 + 1280, 5120);
                if (MPF == 2 && r >= MPF0 && r < MPF0 + 10) l2_prefetch(wmod + (size_t)(role * 5 + ((r - MPF0) >> 1)) * 3840 + 1920 + (r & 1) * 1280, 1280);
                if (((GU_MASK >> (r + 2)) & 1) && fi < 108) { if (gn == 0) mbar_expect_tx(BAR(B_FG), 40960); tma2d(sm + OFF_WG + gn * 10240, (fi & 1) ? &mu : &mg, (fi >> 1) * 32, gn * 160, BAR(B_FG)); gn++; }
#pragma unroll 1
                for (int n = ((WO_MASK >> (r + 2)) & 1) + (r == 14); n > 0; n--) {
                    const int row = (j ^ wn) * 80 + rank * 40;
                    const uint32_t b = BAR(wn ? B_WO : B_WO0), dst = sm + wobuf(wn) + rank * 2560;
                    mbar_expect_tx(b, WO16 ? 12800 : WST);
                    tma2d_mc(dst, &mo, col_main, row, b); tma2d_mc(dst + 5120, &mo, col_main + 32, row, b); tma2d_mc(dst + 10240, WO16 ? &mo2 : &mo, col_tail, row, b);
                    wn++;
                }
                if (!NOPF && r >= PF0 && r < PF0 + 3 * PFN) { const int m = (r - PF0) / PFN; l2_prefetch((m == 0 ? wg : (m == 1 ? wu : wd)) + role * 8640 + (r - PF0 - m * PFN) * (8640 / PFN), 17280 / PFN); }
            }
            STAMPT(24, 256);
            if (fi >= 88) { mbar_wait(BAR(B_G2), 0); mbar_expect_tx(BAR(B_FD), 55296); tma3d(sm + OFF_WD, &md, (fi - 88) * 16, 0, 0, BAR(B_FD)); }
            return;
        }
        asm volatile("barrier.cluster.wait.aligned;" ::: "memory");
        const int tid = threadIdx.x, lane = tid & 31, fh = (lane >> 3) & 1;
        int gd = 0;
        if (warp == 9) {
            {
                uint32_t ta = sm + OFF_TAB + fh * 1280 + (lane >> 4) * 128 + (lane & 4) * 16 + (lane & 1) * 32 + (lane & 2) * 4;
                const uint4* tp = &S->tab[lane >> 3][lane & 7];
                pause_until(t_start, TDELAY);
#pragma unroll 1
                for (int e = 0; e < 5; e++) {
                    uint32_t w[4];
                    if (e > 1) mbar_wait(BAR(B_WE + 4 * e - 8), 0);
                    while (true) {
                        ldg4_rlx(w, tp);
                        if (!__any_sync(~0u, min(min(w[0], w[1]), min(w[2], w[3])) == 0) || ++gd > SPIN_LIMIT) break;
                        pause(P_TAB);
                    }
                    sts2(ta, w[0], w[1]); sts2(ta + 16, w[2], w[3]);
                    __syncwarp();
                    if (e == 0) { STAMPT(2, 288); if (lane == 0) sts1(sm + OFF_EP + EP_US + 8, ep0 << 22 & 0x40000000u); }
                    if (lane == 0) mbar_arrive(BAR(e ? B_TB - 1 + e : B_T0));
                    ta += 256; tp += 288;
                }
            }
            uint32_t h[5][4];
            while (ldg1_acq(&S->cnt) != inc(ep0) && ++gd < SPIN_LIMIT) __nanosleep(YSLEEP);
            __syncwarp();
            if (lane == 0) mbar_arrive(BAR(B_RDY));
            mbar_wait(BAR(HALO_GO), 0);
            pause(D_H);
            if ((ti & 7) == 0) {
#pragma unroll
                for (int s = 0; s < 20; s++) h[s >> 2][s & 3] = 0;
            } else {
                do {
                    pause(P_H);
#pragma unroll
                    for (int s = 0; s < 5; s++) ldg4_rlx(h[s], &X->halo[(role - 8 - (ti & 8)) * 160 + s * 32 + lane]);
                } while (__any_sync(~0u, min(min(min(h[0][0], h[1][0]), min(h[2][0], h[3][0])), h[4][0]) == 0) && ++gd < SPIN_LIMIT);
            }
            const uint32_t p8 = sm + OFF_P8 - 4096, va = p8 + 2048 + (lane & 7) * VP + (lane >> 3) * 16;
            sts4(p8 + 2048 + 1408 + lane * 16, h[0]); sts4(p8 + 1408 + lane * 16, h[1]); sts2(p8 + (lane >> 4) * 2048 + 1920 + (lane & 15) * 8, h[2][0], h[2][1]);
            stsm4(va, h[3]); stsm4(va + 64, h[4]); stsm2(va + 128, h[2][2], h[2][3]);
            __syncwarp();
            if (lane == 0) mbar_arrive(BAR(B_HL));
            STAMPT(19, 288);
            mbar_wait(BAR(B_G3), 0);
            pause(D_REC);
            do {
                pause(P_REC);
                ldg4_rlx(h[0], &X->ra[(lane >> 3) * 8 + grp][lane & 7]); ldg4_rlx(h[1], &X->ra[(lane >> 3) * 8 + 32 + grp][lane & 7]);
            } while (__any_sync(~0u, min(min(h[0][1], h[0][3]), min(h[1][1], h[1][3])) == 0) && ++gd < SPIN_LIMIT);
            const uint32_t kwin = __reduce_max_sync(~0u, max(max(h[0][0], h[0][2]), max(h[1][0], h[1][2])));
            const uint32_t tok = __reduce_min_sync(~0u, min(min(h[0][0] == kwin ? h[0][1] : 2048u, h[0][2] == kwin ? h[0][3] : 2048u), min(h[1][0] == kwin ? h[1][1] : 2048u, h[1][2] == kwin ? h[1][3] : 2048u)));
            if (lane == 0) {
                const uint32_t t = (tok - 1) & 2047, wi = (t & 1) * 64 + (t >> 5), wv[4] = {kwin, t, wi, wi * 320};
                sts4(sm + OFF_EP + EP_US + 32, wv); mbar_arrive(BAR(B_WIN));
            }
            if (lane < 8 && role < 20) stg4_rlx(&S->tab[role][lane], 0u, 0u, 0u, 0u);
            return;
        }
        const int at = tid - 320;
        const int kg = at < 40 ? 80 * j + 2 * at : max(fi - 88, 0) * 16 + 2 * (at & 7);
        const uint32_t w2 = *(const uint32_t*)(wr + kg);
        mbar_wait(BAR(B_WF + RWAIT), 0);
        if (RTB) mbar_wait(BAR(B_T0), 0);
        {
            uint4* p = &X->o[4 * 128 * 256] + role * RV + at;
#pragma unroll 1
            for (int r = 0; r < RV / 64; r++) {
                stg4_rlx(p, 0u, 0u, 0u, 0u);
                p += 64;
                __nanosleep(RSLEEP);
            }
        }
        bar_sync(5, 64);
        if (at == 0) { mbar_wait(BAR(B_TB), 0); }
        if (at == 0) asm volatile("red.release.gpu.global.add.u32 [%0], 1;" ::"l"(&S->cnt) : "memory");
        mbar_wait(BAR(B_RDY), 0);
        const uint32_t* const mp = (const uint32_t*)&S->tab[0][0] + ((kg >> 4) & 3) * 8 + (kg & 6) + ((kg >> 3) & 1);
        const int p = odd ? (at < 8 ? at + 32 : at - 8) : at, lm = min(lane, 9);
        const uint32_t a = sm + OFF_EP + (p & 3) * 48 + (p >> 2) * 4;
#pragma unroll 1
        for (int ph = 0; ph < 4; ph++) {
            uint32_t v, us;
            mbar_wait(BAR(ph < 2 ? TB_GO : TB_GO2), 0);
            while (true) {
                v = ldg1_rlx(mp + (ph < 2 ? 20 + ph + (kg >> 6) * 2 : 20 + ph * 10 + (kg >> 6)) * 288);
                us = ldg1_rlx(&S->tab[ph < 2 ? 20 + ph + lm * 2 : 20 + ph * 10 + lm][8]);
                if (!__any_sync(~0u, min(v, us) == 0) || ++gd > SPIN_LIMIT) break;
                __nanosleep(200);
            }
            if (at < 40) {
                sts1(a + ph * 192, v);
                if (ph == 1) {
                    const float u0 = blo(v) * blo(w2), u1 = bhi(v) * bhi(w2);
                    const uint32_t uh = pack2(u0, u1);
                    sts1(a + 768, 0x3f803f80u); sts1(a + 960, uh); sts1(a + 1152, pack2(u0 - blo(uh), u1 - bhi(uh)));
                }
            } else sts1(sm + OFF_EP + EP_GD + (at & 7) * 4, v);
            float t = lane < 10 ? __uint_as_float(us) : 0.f;
#pragma unroll
            for (int o = 1; o < 16; o <<= 1) t += __shfl_xor_sync(~0u, t, o);
            if (at == 0) sts1f(sm + OFF_EP + EP_US + 12 + ph * 4, t);
            __syncwarp();
            if (lane == 0 && ph) mbar_arrive(BAR(B_EP - 1 + ph));
        }
        STAMPT(20, 320);
    } else {
        asm volatile("setmaxnreg.inc.sync.aligned.u32 216;");
        asm volatile("barrier.cluster.wait.aligned;" ::: "memory");
        LANE_VARS
        const int tw = ti * 8 + warp;
        const uint32_t oo = tw * 4096 + j * 512 + lane * 16;
        const uint32_t pair = (uint32_t)(lane & 1) << 24;
        const uint32_t hi = lane >> 4, xa = sm + (warp * 16 + (lane & 15)) * 128 + ((hi ^ (lane & 7)) << 4);
        const uint32_t p8 = sm + OFF_P8 + warp * 2048, q8 = p8 - (warp ? 2048 : 4096), q9 = p8 - 2048 + (warp ? 16384 : 0);
        const uint32_t l16 = PIN(lane * 16), kt = PIN(hi * 16384 + (lane & 15) * 8), va = PIN(p8 + (lane & 7) * VP + (lane >> 3) * 16);
        const uint32_t vb = PIN(p8 + (lane & 7) * VP + hi * 16384 + fh * 16), vc = PIN(p8 + (lane & 7) * VP + fh * 16384 + hi * 16);
        const uint32_t vh = PIN((fh ? p8 : q9) + (lane & 7) * VP + hi * 16), kh = PIN((hi ? q9 : q8) + (lane & 15) * 8);
        const uint32_t mgt = PIN((2 * q > g ? 0xffffu : 0u) | (2 * q + 1 > g ? 0xffff0000u : 0u));
        uint32_t rr0, rr1, nn0, nn1;
        {
            float gA[2][4] = {}, gB[2][4] = {};
            uint32_t xb = sm + (warp * 16 + frow) * 128 + ((fh ^ (lane & 7)) << 4), one[16];
#pragma unroll
            for (int k = 0; k < 16; k++) one[k] = 0x3f803f80u + ((uint32_t)tid >> (12 + k));
#pragma unroll 1
            for (int c = 0; c < 10; c += 2) {
                mbar_wait(BAR(B_XF + c), 0); mbar_wait(BAR(B_XF + c + 1), 0);
                uint32_t a[8][4];
#pragma unroll
                for (int k = 0; k < 8; k++) ldsm4(a[k], (xb ^ ((k & 3) * 32)) + (k >> 2) * 16384);
                xb += 32768;
#pragma unroll
                for (int k = 0; k < 8; k++) {
                    uint32_t t[4];
#pragma unroll
                    for (int e = 0; e < 4; e++) asm volatile("mov.b32 %0, %1;" : "=r"(t[e]) : "r"(a[k][e]));
                    mma16(gA[k & 1], t[0], one[(k & 3) * 4], t[1], one[(k & 3) * 4 + 1], a[k][0], a[k][1]);
                    mma16(gB[k & 1], t[2], one[(k & 3) * 4 + 2], t[3], one[(k & 3) * 4 + 3], a[k][2], a[k][3]);
                }
            }
            const int src = (lane & ~3) | (g >> 1), e = g & 1;
            const float ss0 = __shfl_sync(~0u, e ? gA[0][1] + gA[1][1] : gA[0][0] + gA[1][0], src), ss1 = __shfl_sync(~0u, e ? gB[0][1] + gB[1][1] : gB[0][0] + gB[1][0], src);
            const float m0 = __shfl_sync(~0u, e ? gA[0][3] + gA[1][3] : gA[0][2] + gA[1][2], src) * (1.f / 640), m1 = __shfl_sync(~0u, e ? gB[0][3] + gB[1][3] : gB[0][2] + gB[1][2], src) * (1.f / 640);
            const float r0 = rbf(rsq(fmaxf(ss0 * (1.f / 640) - m0 * m0, 0.f) + 1e-5f)), r1 = rbf(rsq(fmaxf(ss1 * (1.f / 640) - m1 * m1, 0.f) + 1e-5f));
            rr0 = pack2(r0, r0); rr1 = pack2(r1, r1); nn0 = pack2(-m0 * r0, -m0 * r0); nn1 = pack2(-m1 * r1, -m1 * r1);
        }
        uint32_t xr[5][4];
#pragma unroll
        for (int s = 0; s < 5; s++) {
            const int ks = 5 * j + (odd ? (s == 4 ? 0 : s + 1) : s);
            ldsm4(xr[s], (xa ^ ((ks & 3) * 32)) + (ks >> 2) * 16384);
        }
        STAMP(0);
        mbar_wait(BAR(B_T0), 0);
        if (WGBAR) bar_sync(1, 256);
        float acc[120];
#pragma unroll
        for (int i = 0; i < 120; i++) asm volatile("" : "=f"(acc[i]));
        {
            uint32_t a[2][2][4], raw[2][4], tt[2][4];
            uint32_t tb = sm + OFF_TAB + q * 16, xp = xa;
            auto load = [&](int u) {
                ldsm4(raw[0], xp ^ (u * 64)); ldsm4(raw[1], xp ^ (u * 64 + 32));
                lds4(tt[0], tb + u * 64 + 1280); lds4(tt[1], tb + u * 64);
            };
            auto xform = [&](uint32_t (*dst)[4]) {
#pragma unroll
                for (int h = 0; h < 2; h++) {
                    dst[h][0] = hf2(hf2(raw[h][0], rr0, nn0), tt[0][2 * h], tt[1][2 * h]); dst[h][1] = hf2(hf2(raw[h][1], rr1, nn1), tt[0][2 * h], tt[1][2 * h]);
                    dst[h][2] = hf2(hf2(raw[h][2], rr0, nn0), tt[0][2 * h + 1], tt[1][2 * h + 1]); dst[h][3] = hf2(hf2(raw[h][3], rr1, nn1), tt[0][2 * h + 1], tt[1][2 * h + 1]);
                }
            };
            const uint64_t dm0 = al ? mkdesc(SM0, 2048, 1024, 1) : mkdesc(SM0, 1024, 512, 2), dt0 = mkdesc(SM0 + 12288, 512, 256, 3);
            load(0); xform(a[0]);
            STAMP(3);
#pragma unroll 1
            for (int i2 = 0; i2 < 10; i2++) {
#pragma unroll
                for (int u = 0; u < 2; u++) {
                    const int it = i2 * 2 + u;
                    const uint32_t bo = wbuf(it) >> 4;
                    mbar_wait(BAR(B_WF + it), 0);
                    if (LAG && warp < 4 && i2 * 2 + u == 20 - LAG) bar_sync(4, 256);
                    wg_fence();
#pragma unroll
                    for (int h = 0; h < 2; h++) { wgmma_rs_n192(acc, a[u][h], dm0 + bo + h * 384, (u | h) ? 1 : i2); wgmma_rs_n48(acc + 96, a[u][h], dt0 + bo + h * 96, (u | h) ? 1 : i2); }
                    wg_commit();
                    if (LAG && u == 1 && warp >= 4 && i2 == 9) asm volatile("bar.arrive 4, 256;" ::: "memory");
                    if (u == 1) { xp += 16384; tb += 128; }
                    if (u == 1 && (i2 & 1) && i2 < 9) mbar_wait(BAR(B_TB + (i2 >> 1)), 0);
                    load(u ^ 1);
                    wg_wait<1>();
                    if (lane < 2 && (u == 1 || i2 > 0)) mbar_arrive_cl(pair + BAR0(B_WE - 1 + it));
                    xform(a[u ^ 1]);
                }
            }
        }
        uint32_t own[5][4], ab[3][7][4], sv, tc;
        const char* op[7];
        auto ldo = [&](int s, uint32_t (*dst)[4]) {
#pragma unroll
            for (int w = 0; w < 7; w++) ldg4_rlx(dst[w], op[w] + (4 - s) * 524288);
        };
        {
            uint32_t Q[10][2], K[2][10], V[2][10];
            mbar_wait(BAR(B_RDY), 0);
            sv = lds1(sm + OFF_EP + EP_US + 8); tc = (sv ^ 0x40000000u) - 0x20000000u;
            wg_wait<0>();
            STAMP(4); STAMPT(18, 128);
#define ACC_IDX(t, m) (odd_ ? (t >= 2 ? m * 32 + (t - 2) * 4 : 96 + m * 8 + t * 4) : (t < 8 ? m * 32 + t * 4 : 96 + m * 8 + (t - 8) * 4))
#define PACK1(odd_v) { constexpr bool odd_ = odd_v; _Pragma("unroll") for (int t = 0; t < 10; t++) { \
                K[1][t] = pack2(acc[ACC_IDX(t, 1) + 2], acc[ACC_IDX(t, 1) + 3]); V[1][t] = pack2(acc[ACC_IDX(t, 2) + 2], acc[ACC_IDX(t, 2) + 3]); \
                V[0][t] = pack2(acc[ACC_IDX(t, 2)], acc[ACC_IDX(t, 2) + 1]); } }
#define PACK2(odd_v) { constexpr bool odd_ = odd_v; _Pragma("unroll") for (int t = 0; t < 10; t++) { \
                K[0][t] = pack2(acc[ACC_IDX(t, 1)], acc[ACC_IDX(t, 1) + 1]); \
                Q[t][0] = pack2(acc[ACC_IDX(t, 0)], acc[ACC_IDX(t, 0) + 1]); Q[t][1] = pack2(acc[ACC_IDX(t, 0) + 2], acc[ACC_IDX(t, 0) + 3]); } }
            if (odd) PACK1(true) else PACK1(false)
            if (warp == 7 && (~ti & 7)) {
                uint4* hp = &X->halo[(role - (ti & 8)) * 160 + lane];
                K[1][0] = nz(K[1][0]); K[1][5] = nz(K[1][5]); K[1][2] = nz(K[1][2]); V[1][0] = nz(V[1][0]); V[1][4] = nz(V[1][4]);
                stg4_rlx(hp, K[1][0], K[1][1], K[1][3], K[1][4]); stg4_rlx(hp + 32, K[1][5], K[1][6], K[1][8], K[1][9]); stg4_rlx(hp + 64, K[1][2], K[1][7], V[1][8], V[1][9]);
                stg4_rlx(hp + 96, V[1][0], V[1][1], V[1][2], V[1][3]); stg4_rlx(hp + 128, V[1][4], V[1][5], V[1][6], V[1][7]);
            }
            {
                const uint32_t k0[4] = {K[1][0], K[1][1], K[1][3], K[1][4]}, k1[4] = {K[1][5], K[1][6], K[1][8], K[1][9]}, vl[4] = {V[0][8], V[0][9], V[1][8], V[1][9]};
                sts4(p8 + 16384 + 1408 + l16, k0); sts4(p8 + 1408 + l16, k1); sts2(p8 + 1920 + kt, K[1][2], K[1][7]);
                stsm4(va + 16384, V[1]); stsm4(va + 16384 + 64, V[1] + 4); stsm4(vb + 128, vl);
                stsm4(va, V[0]); stsm4(va + 64, V[0] + 4);
            }
            __syncwarp();
            if (lane == 0) mbar_arrive(BAR(B_HL + 1 + warp));
            uint32_t VT[5][4], KH[10];
#pragma unroll
            for (int s = 0; s < 5; s++) ldsm4t(VT[s], vc + s * 32);
            if (odd) PACK2(true) else PACK2(false)
            float sb[4][4], sc[4][4];
            uint32_t qs[4][2];
#pragma unroll
            for (int h = 0; h < 4; h++) {
                const int ts = (h >> 1) * 5 + 2, ta = (h >> 1) * 5 + (h & 1) * 3;
                const bool mine = (q >> 1) == (h & 1);
                qs[h][0] = mine ? Q[ts][0] : 0u; qs[h][1] = mine ? Q[ts][1] : 0u;
                mma16c(sb[h], Q[ta][0], Q[ta][1], Q[ta + 1][0], Q[ta + 1][1], K[0][ta], K[0][ta + 1], 0.f, 0.f);
                mma16c(sc[h], Q[ta][0], Q[ta][1], Q[ta + 1][0], Q[ta + 1][1], K[1][ta], K[1][ta + 1], 0.f, 0.f);
                mma8(sb[h], qs[h][0], qs[h][1], K[0][ts]);
                mma8(sc[h], qs[h][0], qs[h][1], K[1][ts]);
            }
            const bool gt0 = mgt & 1, gt1 = (int)mgt < 0;
            auto half = [&](int e, float (*pv)[4], float (*cu)[4]) {
                const float cs = 0.22360679774997896f * 1.4426950408889634f;
                uint32_t p[4];
                float t0[4], t1[4], m[4];
#pragma unroll
                for (int h = 0; h < 4; h++) { t0[h] = gt0 ? pv[h][2 * e] : cu[h][2 * e]; t1[h] = gt1 ? pv[h][2 * e + 1] : cu[h][2 * e + 1]; m[h] = fmaxf(t0[h], t1[h]); }
#pragma unroll
                for (int h = 0; h < 4; h++) m[h] = fmaxf(m[h], __shfl_xor_sync(~0u, m[h], 1));
#pragma unroll
                for (int h = 0; h < 4; h++) m[h] = fmaxf(m[h], __shfl_xor_sync(~0u, m[h], 2)) * -cs;
#pragma unroll
                for (int h = 0; h < 4; h++) p[h] = pack2(ex2(fmaf(t0[h], cs, m[h])), ex2(fmaf(t1[h], cs, m[h])));
#pragma unroll
                for (int pr = 0; pr < 2; pr++) {
                    const uint32_t a0 = p[2 * pr] & mgt, a1 = p[2 * pr + 1] & mgt, a2 = p[2 * pr] & ~mgt, a3 = p[2 * pr + 1] & ~mgt;
                    float l[4];
                    mma16c(l, a0, a1, a2, a3, 0x3f803f80u, 0x3f803f80u, 0.f, 0.f);
                    l[0] = rcp(l[0]); l[2] = rcp(l[2]);
#pragma unroll
                    for (int r = 0; r < 5; r++) {
                        const int t = pr * 5 + r;
                        float d[4];
                        mma16c(d, a0, a1, a2, a3, VT[t >> 1][(t & 1) * 2], VT[t >> 1][(t & 1) * 2 + 1], 0.f, 0.f);
                        const bool od = r == 2 ? (q & 2) : r > 2;
                        const float li = od ? l[2] : l[0];
                        own[t >> 1][(t & 1) * 2 + e] = pack2((od ? d[2] : d[0]) * li, (od ? d[3] : d[1]) * li);
                    }
                }
            };
            half(1, sb, sc);
            mbar_wait(BAR(B_HL + warp), 0);
            lds4(KH, q9 + 1408 + l16); lds4(KH + 4, q8 + 1408 + l16); lds2(KH + 8, kh + 1920);
#pragma unroll
            for (int s = 0; s < 5; s++) ldsm4t(VT[s], vh + s * 32);
            STAMP(5); STAMPT(25, 64);
            const float ninf = (tw & 63) == 0 ? -INFINITY : 0.f;
#pragma unroll
            for (int h = 0; h < 4; h++) {
                const int ta = (h >> 1) * 5 + (h & 1) * 3;
                mma16c(sc[h], Q[ta][0], Q[ta][1], Q[ta + 1][0], Q[ta + 1][1], KH[2 * h], KH[2 * h + 1], ninf, ninf);
                mma8(sc[h], qs[h][0], qs[h][1], KH[8 + (h >> 1)]);
            }
            half(0, sc, sb);
#pragma unroll
            for (int w = 0; w < 7; w++) op[w] = (const char*)X->o + (oo ^ (w * 512 + 512));
#pragma unroll
            for (int s = 0; s < 5; s++) {
                if (s == EARLY_LD) { if (D_E) pause(D_E); ldo(0, ab[0]); }
                own[s][0] = s ? tagw(own[s][0], tc) : nz(own[s][0]); stg4_rlx((char*)X->o + oo + (4 - s) * 524288, own[s][0], own[s][1], own[s][2], own[s][3]);
            }
        }
        STAMP(6); STAMPT(21, 128); STAMPT(26, 64);
        float ac2[40];
#pragma unroll
        for (int i = 0; i < 40; i++) asm volatile("" : "=f"(ac2[i]));
        {
            const uint64_t d0 = mkdesc(SM0, 5120, 512, 2);
            mbar_wait(BAR(B_WO0), 0);
#pragma unroll
            for (int s = 1; s < 5; s++) own[s][0] -= tc;
            wg_fence();
#pragma unroll
            for (int s = 0; s < 5; s++) wgmma_rs_n80(ac2, own[s], d0 + (wobuf(0) >> 4) + s * 64, s);
            wg_commit();
            uint32_t fz = clock32();
            if (D_O && EARLY_LD >= 5) pause_until(fz, D_O);
            if (EARLY_LD >= 5) ldo(0, ab[0]);
            if (!LATE1) ldo(1, ab[1]);
            mbar_wait(BAR(B_WO), 0);
#pragma unroll
            for (int s = 0; s < 5; s++) {
                uint32_t (*cur)[4] = ab[s % 3];
                if (s == 0) await7<0>(cur, op, fz, sv);
                else {
                    if (s == 1) await7<1>(cur, op, fz, sv); else if (s == 2) await7<2>(cur, op, fz, sv); else if (s == 3) await7<3>(cur, op, fz, sv); else await7<4>(cur, op, fz, sv);
#pragma unroll
                    for (int w = 0; w < 7; w++) cur[w][0] -= tc;
                }
                if (s == 0) { STAMP(7); STAMPT(1, 128); }
                wg_fence();
#pragma unroll
                for (int w = 1; w < 8; w++) wgmma_rs_n80(ac2, cur[w - 1], d0 + (wobuf(w) >> 4) + s * 64, 1);
                wg_commit();
                if (s < 3) { if (s) wg_wait<1>(); else fz |= clock32(); if (s == 0 && LATE1) ldo(1, ab[1]); if (s == 1 && LATE2) ldo(2, ab[2]); if (s || !LATE2) ldo(s + 2, ab[(s + 2) % 3]); }
                if (s == FD_AT && lane == 0) mbar_arrive(BAR(B_G2));
            }
        }
        mbar_wait(BAR(B_EP), 0);
        uint32_t tga[12], tst[12];
        const uint32_t ep = sm + OFF_EP + q * 48;
#pragma unroll
        for (int s = 0; s < 3; s++) { lds4(tga + 4 * s, ep + s * 16); lds4(tst + 4 * s, ep + 768 + min(g, 2) * 192 + s * 16); }
        uint4* const sp0 = pinp(&X->stats[j][tw * 16 + g]);
        const int prow = (ti & 7) * 128 + warp * 16;
        const uint4* const sp = pinp(&X->stats[hi * 4][tw * 16 + (lane & 15)]);
        const int dsrc = PIN((lane & ~3) | (g >> 1));
        wg_wait<0>();
        if (lane == 0) mbar_arrive(BAR(B_G4));
        STAMP(8); STAMPT(23, 128);
        {
            float gA[2][4] = {}, gB[2][4] = {}, sd[4] = {};
#pragma unroll
            for (int s = 0; s < 5; s++) {
#pragma unroll
                for (int e = 0; e < 4; e++) xr[s][e] = hf2(tga[2 * s + (e >> 1)], pack2(ac2[s * 8 + e * 2], ac2[s * 8 + e * 2 + 1]), xr[s][e]);
                mma16(sd, xr[s][0], xr[s][1], xr[s][2], xr[s][3], tst[2 * s], tst[2 * s + 1]);
                mma8(gA[0], xr[s][0], xr[s][1], xr[s][0]); mma8(gB[0], xr[s][0], xr[s][1], xr[s][1]);
                mma8(gA[1], xr[s][2], xr[s][3], xr[s][2]); mma8(gB[1], xr[s][2], xr[s][3], xr[s][3]);
            }
            const float l0 = __shfl_down_sync(~0u, sd[0], 1), l1 = __shfl_down_sync(~0u, sd[2], 1);
            const float q0 = __shfl_sync(~0u, fsel(g & 1, gA[0][1] + gA[1][1], gA[0][0] + gA[1][0]), dsrc), q1 = __shfl_sync(~0u, fsel(g & 1, gB[0][3] + gB[1][3], gB[0][2] + gB[1][2]), dsrc);
            stg4_if(q == 0, sp0, __float_as_uint(sd[0]), __float_as_uint(sd[1] + l0), __float_as_uint(q0), 1u);
            stg4_if(q == 0, sp0 + 8, __float_as_uint(sd[2]), __float_as_uint(sd[3] + l1), __float_as_uint(q1), 1u);
        }
        const uint32_t t9 = clock32();
        STAMP(9);
        uint32_t fg[5][4], fu[5][4], tcb[12], tsb[12];
        uint32_t st[4][4];
        auto ldfg = [&] {
        if (fi < 108) {
            mbar_wait(BAR(B_FG), 0);
#pragma unroll
            for (int s = 0; s < 5; s++) {
                const uint32_t off = sm + OFF_WG + (5 * warp + ((warp & 1) ? (s == 4 ? 0 : s + 1) : s)) * 1024 + frow * 64 + ((fh ^ ((lane >> 1) & 3)) << 4);
                ldsm4t(fg[s], off); ldsm4t(fu[s], off ^ 32);
            }
        }
        };
        if (FGPOS == 0) ldfg();
        if (D_ST) pause_until(t9, D_ST);
#pragma unroll
        for (int e = 0; e < 4; e++) ldg4_rlx(st[e], sp + e * 2056);
        if (FGPOS == 1) ldfg();
        mbar_wait(BAR(B_EP2), 0);
#pragma unroll
        for (int s = 0; s < 3; s++) { lds4(tcb + 4 * s, ep + 192 + s * 16); lds4(tsb + 4 * s, ep + 384 + s * 16); }
        int crow;
        {
            const float2 su = lds2f(sm + OFF_EP + EP_US + 16);
            int gd = 0;
            uint2* const rp = pinp((uint2*)&X->ra[(tw >> 4) * 8 + (lane & 7)][0] + (tw & 15));
            const int tk = PIN(warp == j && lane < 8 ? prow * 2 + (ti >> 3) + 1 : 0);
            float v[3];
            bool bad;
            while (true) {
                bad = __any_sync(~0u, (st[0][3] & st[1][3] & st[2][3] & st[3][3]) == 0);
#pragma unroll
                for (int e = 0; e < 3; e++) {
                    v[e] = (__uint_as_float(st[0][e]) + __uint_as_float(st[1][e])) + (__uint_as_float(st[2][e]) + __uint_as_float(st[3][e]));
                    v[e] += __shfl_xor_sync(~0u, v[e], 16);
                }
                if (!bad || ++gd > SPIN_LIMIT) break;
#pragma unroll
                for (int e = 0; e < 4; e++) ldg4_again(st[e], sp + e * 2056);
            }
            STAMP(10);
            const float m = v[0] * (1.f / 640), rs = rsq(fmaxf(fmaf(v[2], 1.f / 640, 1e-5f) - m * m, 1e-5f));
            const uint32_t key = fkey(fmaf(rs, fmaf(-m, su.x, v[1]), su.y)), kmax = __reduce_max_sync(~0u, key);
            crow = __ffs(__ballot_sync(~0u, key == kmax)) - 1;
            stg2_if(tk, rp, kmax, tk + 2 * crow);
            if (G3E && lane == 0) mbar_arrive(BAR(B_G3));
            const uint32_t rn = pack2(rs, -m * rbf(rs)), a0 = __shfl_sync(~0u, rn, g), a1 = __shfl_sync(~0u, rn, g + 8);
            rr0 = __byte_perm(a0, 0, 0x1010); nn0 = __byte_perm(a0, 0, 0x3232); rr1 = __byte_perm(a1, 0, 0x1010); nn1 = __byte_perm(a1, 0, 0x3232);
        }
        {
            const bool up = crow >= 8;
            const uint32_t rr = up ? rr1 : rr0, nn = up ? nn1 : nn0;
            if (g == (crow & 7)) {
                uint4* cp = &X->cand[j][tw * 20 + q];
#pragma unroll
                for (int s = 0; s < 5; s++) {
                    const uint32_t xa_ = up ? xr[s][1] : xr[s][0], xb_ = up ? xr[s][3] : xr[s][2];
                    stg4_rlx(cp + s * 4, nz(hf2(hf2(xa_, rr, nn), tcb[2 * s], tsb[2 * s])), hf2(hf2(xb_, rr, nn), tcb[2 * s + 1], tsb[2 * s + 1]), xa_, xb_);
                }
            }
        }
        if (!G3E && lane == 0) mbar_arrive(BAR(B_G3));
        STAMP(11);
        const uint32_t stg = sm + 5 * WST + warp * 2560;
        {
            mbar_wait(BAR(B_EP3), 0);
#pragma unroll
            for (int s = 0; s < 3; s++) lds4(tga + 4 * s, ep + 576 + s * 16);
#pragma unroll
            for (int s = 0; s < 5; s++) {
#pragma unroll
                for (int e = 0; e < 4; e++) { const int t = 2 * s + (e >> 1); xr[s][e] = hf2(tga[t], hf2(hf2(xr[s][e], (e & 1) ? rr1 : rr0, (e & 1) ? nn1 : nn0), tcb[t], tsb[t]), xr[s][e]); }
            }
            mbar_wait(BAR(B_G4), 0);
#pragma unroll
            for (int s = 0; s < 5; s++) stsm4(stg + (lane & 15) * 160 + (odd ? (s == 4 ? 0 : s + 1) : s) * 32 + hi * 16, xr[s]);
            asm volatile("fence.proxy.async.shared::cta;" ::: "memory");
            __syncwarp();
            if (OUTPOS == 0 && elect1()) tma3d_st(&mout, 80 * j, ti >> 3, prow + (~crow & 8), stg + (~crow & 8) * 160);
        }
        STAMP(12);
        const char* cp = (const char*)pinp(&X->cand[warp][q]);
        uint32_t* const ap0 = pinp((uint32_t*)&X->ra[fi >> 1][8 + (fi & 1) * 4] + (lane & 8) + (lane & 3) * 2 + ((lane >> 2) & 1));
        const uint32_t rw = PIN(sm + OFF_RED - 256 + (q * 4 + (g >> 1)) * 80 + warp * 8 + (g & 1) * 4), rd = PIN(sm + OFF_RED - 256 + (lane & 15) * 80);
        if (smem_u32(sm_raw) != sm) return;
        mbar_wait(BAR(B_WIN), 0);
        uint32_t wv[4]; int gd = 0;
        lds4(wv, sm + OFF_EP + EP_US + 32);
        const uint32_t kwin = wv[0];
        const int tokwin = wv[1], win = wv[2];
        auto out2 = [&] {
            if (OUTPOS == 1 && elect1()) tma3d_st(&mout, 80 * j, ti >> 3, prow + (~crow & 8), stg + (~crow & 8) * 160);
            if (win != tw) {
                if (elect1()) tma3d_st(&mout, 80 * j, ti >> 3, prow + (crow & 8), stg + (crow & 8) * 160);
            } else {
#pragma unroll 1
                for (int r = crow & 8; r <= (crow | 7); r++)
                    if (r != crow && lane < 20) { uint32_t v[2]; lds2(v, stg + r * 160 + lane * 8); *(uint2*)(out + (size_t)((prow + r) * 2 + (ti >> 3)) * 640 + 80 * j + lane * 4) = make_uint2(v[0], v[1]); }
            }
        };
        const uint32_t t13 = clock32();
        STAMP(13);
        if (OUTPOS2 == 0) out2();
        if (fi < 108) {
            uint32_t hb[5][2];
            float mine;
            bool bad;
            cp += wv[3];
            do {
#pragma unroll
                for (int s = 0; s < 5; s++) ldg2_rlx(hb[s], cp + s * 64);
                bad = __any_sync(~0u, min(min(min(hb[0][0], hb[1][0]), min(hb[2][0], hb[3][0])), hb[4][0]) == 0);
                float dg[2][4] = {}, du[2][4] = {};
#pragma unroll
                for (int s = 0; s < 5; s++) {
                    mma16(dg[s & 1], fg[s][0], fg[s][1], fg[s][2], fg[s][3], hb[s][0], hb[s][1]);
                    mma16(du[s & 1], fu[s][0], fu[s][1], fu[s][2], fu[s][3], hb[s][0], hb[s][1]);
                }
                mine = fsel(q & 2, fsel(q & 1, du[1][2], du[1][0]), fsel(q & 1, dg[1][2], dg[1][0])) + fsel(q & 2, fsel(q & 1, du[0][2], du[0][0]), fsel(q & 1, dg[0][2], dg[0][0]));
                sts1f(rw, mine);
                gd++;
            } while (bad && gd < SPIN_LIMIT);
            bar_sync(2, 256);
            if (warp == 0) {
                uint32_t v[4][4];
#pragma unroll
                for (int e = 0; e < 4; e++) lds4(v[e], rd + e * 16);
                float t[2];
#pragma unroll
                for (int e = 0; e < 2; e++)
                    t[e] = ((__uint_as_float(v[0][e]) + __uint_as_float(v[0][e + 2])) + (__uint_as_float(v[1][e]) + __uint_as_float(v[1][e + 2]))) +
                           ((__uint_as_float(v[2][e]) + __uint_as_float(v[2][e + 2])) + (__uint_as_float(v[3][e]) + __uint_as_float(v[3][e + 2])));
                uint32_t pr = pack2(t[0], t[1]);
                if (!(fi & 1)) pr = pack2(blo(pr) * sigm(blo(pr)), bhi(pr) * sigm(bhi(pr)));
                stg1_if(lane < 16, ap0, nz(pr));
            }
        }
        STAMP(14);
        if (OUTPOS2 == 1) { if (ODLY && fi < 88) pause(ODLY); out2(); }
        if (fi >= 88) {
            const int d = fi - 88, dj = d / 5, dm = d - dj * 5, sp = (dj & 1) ? (dm == 0 ? 4 : dm - 1) : dm;
            const int ks0 = min(warp * 14, 94);
            const uint32_t frag = frow * 32 + ((fh ^ ((lane >> 2) & 1)) << 4);
            uint32_t fd[14][4];
            mbar_wait(BAR(B_FD), 0);
#pragma unroll
            for (int s = 0; s < 14; s++) ldsm4t(fd[s], sm + OFF_WD + (ks0 + s) * 512 + frag);
            const float sf = sigm(rbf(__uint_as_float((kwin & 0x80000000u) ? kwin & 0x7fffffffu : ~kwin)));
            const uint32_t sg = PIN(pack2(sf, sf));
            const uint32_t gbd = lds1(sm + OFF_EP + EP_GD + (lane & 7) * 4);
            uint32_t* const op = (uint32_t*)(out + (size_t)tokwin * 640 + d * 16) + (lane & 7);
            uint32_t bsv[4], ag[4], au[4];
            const uint4* ap = &X->ra[(ks0 >> 1) + min(g, 6)][8 + q];
            const uint32_t keep = warp == 7 && g < 2 ? 0u : ~0u;
            const uint32_t as = PIN(sm + 7 * WST + warp * 512 + q * 16), aw = PIN(sm + 7 * WST + warp * 512 + g * 64 + (q & 1) * 32 + (q >> 1) * 8);
            const uint32_t yw = PIN(sm + OFF_TAB + ((q & 1) * 4 + (g >> 1)) * 80 + warp * 8 + (g & 1) * 4), yr = PIN(sm + OFF_TAB + (lane & 7) * 80);
            bool bad;
            if (D_A) pause_until(t13, D_A);
            do {
                pause(P_A);
                ldg4_rlx(ag, ap); ldg4_rlx(au, ap + 4); ldg4_rlx(bsv, &X->cand[dj][win * 20 + sp * 4 + q]);
                bad = __any_sync(~0u, min(min(min(min(ag[0], ag[1]), min(ag[2], ag[3])), min(min(au[0], au[1]), min(au[2], au[3]))), bsv[0]) == 0);
                sts2(aw, hm2(ag[0], au[0]) & keep, hm2(ag[1], au[1]) & keep); sts2(aw + 16, hm2(ag[2], au[2]) & keep, hm2(ag[3], au[3]) & keep);
                gd++;
            } while (bad && gd < SPIN_LIMIT);
            STAMP(15);
            __syncwarp();
            float dy[4][4] = {};
            uint32_t av[7][4];
#pragma unroll
            for (int s = 0; s < 7; s++) lds4(av[s], as + s * 64);
#pragma unroll
            for (int s = 0; s < 7; s++) {
                mma16(dy[(2 * s) & 3], fd[2 * s][0], fd[2 * s][1], fd[2 * s][2], fd[2 * s][3], av[s][0], av[s][1]);
                mma16(dy[(2 * s + 1) & 3], fd[2 * s + 1][0], fd[2 * s + 1][1], fd[2 * s + 1][2], fd[2 * s + 1][3], av[s][2], av[s][3]);
            }
            sts1f(yw, (fsel(q & 1, dy[2][2], dy[2][0]) + fsel(q & 1, dy[3][2], dy[3][0])) + (fsel(q & 1, dy[0][2], dy[0][0]) + fsel(q & 1, dy[1][2], dy[1][0])));
            bar_sync(2, 256);
            if (warp == 0) {
                uint32_t v[4][4];
#pragma unroll
                for (int e = 0; e < 4; e++) lds4(v[e], yr + e * 16);
                float t[2];
#pragma unroll
                for (int e = 0; e < 2; e++)
                    t[e] = ((__uint_as_float(v[0][e]) + __uint_as_float(v[0][e + 2])) + (__uint_as_float(v[1][e]) + __uint_as_float(v[1][e + 2]))) +
                           ((__uint_as_float(v[2][e]) + __uint_as_float(v[2][e + 2])) + (__uint_as_float(v[3][e]) + __uint_as_float(v[3][e + 2])));
                const uint32_t hh = (lane & 4) ? bsv[1] : bsv[0], xx = (lane & 4) ? bsv[3] : bsv[2];
                if (lane < 8) *op = hf2(gbd, hf2(hm2(pack2(t[0], t[1]), sg), 0x3f803f80u, hh), xx);
            }
        }
        asm volatile("cp.async.bulk.commit_group;\ncp.async.bulk.wait_group.read 0;" ::: "memory");
        STAMP(16);
    }
}

typedef CUresult (*EncFn)(CUtensorMap*, CUtensorMapDataType, cuuint32_t, void*, const cuuint64_t*, const cuuint64_t*, const cuuint32_t*, const cuuint32_t*,
                          CUtensorMapInterleave, CUtensorMapSwizzle, CUtensorMapL2promotion, CUtensorMapFloatOOBfill);
static void make_map(EncFn enc, CUtensorMap* m, const void* base, int rank, const cuuint64_t* dims, const cuuint64_t* strides, const cuuint32_t* box, CUtensorMapSwizzle sw) {
    const cuuint32_t es[5] = {1, 1, 1, 1, 1};
    enc(m, CU_TENSOR_MAP_DATA_TYPE_BFLOAT16, rank, (void*)base, dims, strides, box, es, CU_TENSOR_MAP_INTERLEAVE_NONE, sw, CU_TENSOR_MAP_L2_PROMOTION_NONE, CU_TENSOR_MAP_FLOAT_OOB_FILL_NONE);
}

extern "C" void kernel_launch(void* const* d_in, const int* in_sizes, int n_in, void* d_out, int out_size) {
    typedef const __nv_bfloat16* P;
    P x = (P)d_in[0], wqkv = (P)d_in[1], wo = (P)d_in[2], wr = (P)d_in[4], wg = (P)d_in[5], wu = (P)d_in[6], wd = (P)d_in[7], c = (P)d_in[8], wmod = (P)d_in[9];
    void* fn = nullptr; cudaDriverEntryPointQueryResult qr;
    cudaGetDriverEntryPoint("cuTensorMapEncodeTiled", &fn, cudaEnableDefault, &qr);
    EncFn enc = (EncFn)fn;
    CUtensorMap mx, mw, mt, mo, mg, mu, md, mm, mw2, mout, mo2;
    { cuuint64_t d[] = {640, 2, 1024}, s[] = {1280, 2560}; cuuint32_t b[] = {64, 1, 128}; make_map(enc, &mx, x, 3, d, s, b, CU_TENSOR_MAP_SWIZZLE_128B); }
    { cuuint64_t d[] = {32, 640, 20, 3}, s[] = {3840, 64, 1280}; cuuint32_t b[] = {32, 16, 2, 3}; make_map(enc, &mw, wqkv, 4, d, s, b, CU_TENSOR_MAP_SWIZZLE_64B); }
    { cuuint64_t d[] = {640, 640, 3}, s[] = {3840, 1280}; cuuint32_t b[] = {16, 16, 3}; make_map(enc, &mt, wqkv, 3, d, s, b, CU_TENSOR_MAP_SWIZZLE_32B); }
    { cuuint64_t d[] = {640, 640}, s[] = {1280}; cuuint32_t b[] = {32, 40}; make_map(enc, &mo, wo, 2, d, s, b, CU_TENSOR_MAP_SWIZZLE_64B);
      b[0] = 16; make_map(enc, &mo2, wo, 2, d, s, b, CU_TENSOR_MAP_SWIZZLE_64B); }
    { cuuint64_t d[] = {1728, 640}, s[] = {3456}; cuuint32_t b[] = {32, 160}; make_map(enc, &mg, wg, 2, d, s, b, CU_TENSOR_MAP_SWIZZLE_64B); make_map(enc, &mu, wu, 2, d, s, b, CU_TENSOR_MAP_SWIZZLE_64B); }
    { cuuint64_t d[] = {640, 216, 8}, s[] = {1280, 1280 * 216}; cuuint32_t b[] = {16, 216, 8}; make_map(enc, &md, wd, 3, d, s, b, CU_TENSOR_MAP_SWIZZLE_32B); }
    { cuuint64_t d[] = {3840, 640}, s[] = {7680}; cuuint32_t b[] = {64, 80}; make_map(enc, &mm, wmod, 2, d, s, b, CU_TENSOR_MAP_SWIZZLE_128B); }
    { cuuint64_t d[] = {64, 640, 10, 3}, s[] = {3840, 128, 1280}; cuuint32_t b[] = {64, 16, 1, 3}; make_map(enc, &mw2, wqkv, 4, d, s, b, CU_TENSOR_MAP_SWIZZLE_128B); }
    { cuuint64_t d[] = {640, 2, 1024}, s[] = {1280, 2560}; cuuint32_t b[] = {80, 1, 8}; make_map(enc, &mout, d_out, 3, d, s, b, CU_TENSOR_MAP_SWIZZLE_NONE); }
    void* sp = nullptr;
    cudaGetSymbolAddress(&sp, g_s);
    cudaFuncSetAttribute(fused_kernel, cudaFuncAttributeMaxDynamicSharedMemorySize, SMEM_BYTES);
    fused_kernel<<<132, 384, SMEM_BYTES>>>(x, wmod, c, (Scratch*)sp, wqkv, wo, (__nv_bfloat16*)d_out, wr, wg, wu, wd, mm, mx, mw, mt, mo, mg, mu, md, mw2, mout, mo2);
}
```

```cpp
#include <cuda_runtime.h>
#include <cuda_bf16.h>
#include <cuda.h>
#include <stdint.h>

#define SPIN_LIMIT (1 << 17)

#define NCR 8
#define NCT 1
#define RPOS 0
#define RWAIT 0
#define CPF 32
#define RTB 1
#define STATV 0
#define OFFS 0
#define SWAPM 0xff
#define HPAUSE 0
#define HJOB 2
#define WGBAR 0
#define TSPLIT 0
#define ODLY 0
#define D_ST 400
#define D_REC 0
#define G3E 0
#define FGPOS 0
#define D_A 0
#define D_O 300
#define D_H 300
#define D_E 0
#define LATE2 0
#define WO16 1
#define MERGE 1
#define SF 2
#define PK 1
#define XPF 0
constexpr int RV = 704;
struct __align__(4096) Exch {
    uint4 o[5 * 128 * 256];
    uint4 halo[112 * 160];
    uint4 stats[8][2056];
    uint4 cand[8][128 * 20 + 8];
    uint4 ra[64][24];
    uint4 pad[128 * RV - (128 * 256 + 112 * 160 + 8 * 2056 + 8 * (128 * 20 + 8) + 64 * 24)];
};
struct __align__(4096) Scratch {
    Exch x;
    uint4 tab[60][72];
    unsigned cnt;
};
__device__ Scratch g_s;
#define STAMP(n)
#define GSTAMP(n)
#define STAMPT(n, t)

constexpr uint32_t OFF_W = 163840, WST = 15360;
constexpr uint32_t OFF_WM = OFF_W + 2 * WST;
constexpr uint32_t OFF_FF = OFF_WM + 20480;
constexpr uint32_t OFF_P8 = 131072, VP = 176;
constexpr uint32_t OFF_WD = 129024, OFF_WG = 184320;
constexpr uint32_t OFF_TAB = 225280;
constexpr uint32_t OFF_RED = OFF_TAB + 2560;
constexpr uint32_t OFF_EP = OFF_TAB + 4096;
constexpr uint32_t EP_GD = 1344, EP_US = 1376;
constexpr uint32_t OFF_BAR = OFF_EP + 1424;
constexpr uint32_t OFF_PROF = OFF_BAR + 640;
constexpr uint32_t SMEM_BYTES = OFF_PROF + 128;
enum { B_XF = 0, B_WF = 10, B_WO0 = 30, B_WO, B_FG, B_FD, B_TB, B_HL = B_TB + 4, B_G0 = B_HL + 8, B_RDY, B_WIN, B_EP, B_EP2, B_EP3, B_G2, B_G3, B_G4, B_WE = 55, B_T0 = B_WE + 19 };
#define ALIGNED 1
#define WO_MASK 0x1f5000
#define P_TAB 100
#define P_REC 0
#define P_ST 0
#define P_A 0
#define RDELAY 600
#define OUTPOS2 1
#define EARLY_RST 0
#define OUTPOS 0
#define LAG 2
#define NOPF 0
#define SDELAY 1200
#define XWAIT 2
#define PFMAP 0
#define WLATE 0
#define SPLIT 1
#define P_O 0
#define P_H 0
#define LATE1 1
#define EARLY_LD 5
#define FD_AT 2
#define GU_MASK 0xaa00
#define TB_GO B_HL
#define TB_GO2 B_G2
#define TDELAY 3900
#define PFN 5
#define PF0 1
#define RDY_AT 8
#define YSLEEP 300
#define MDELAY 2000
#define MPF 2
#define MPF0 6
#define XDELAY 600
#define RSLEEP 40
#define HALO_GO B_G0
constexpr uint32_t SM0 = 1024;
#define BAR0(i) (SM0 + OFF_BAR + 8 * (i))
#define BAR(i) (sm + OFF_BAR + 8 * (i))

__device__ __forceinline__ uint32_t smem_u32(const void* p) { return (uint32_t)__cvta_generic_to_shared(p); }
__device__ __forceinline__ void mbar_init(uint32_t b, int cnt) { asm volatile("mbarrier.init.shared::cta.b64 [%0], %1;" ::"r"(b), "r"(cnt) : "memory"); }
__device__ __forceinline__ void mbar_expect_tx(uint32_t b, uint32_t bytes) { asm volatile("mbarrier.arrive.expect_tx.shared::cta.b64 _, [%0], %1;" ::"r"(b), "r"(bytes) : "memory"); }
__device__ __forceinline__ void mbar_arrive(uint32_t b) { asm volatile("mbarrier.arrive.shared::cta.b64 _, [%0];" ::"r"(b) : "memory"); }
__device__ __forceinline__ bool mbar_try(uint32_t b, uint32_t par) {
    uint32_t ok;
    asm volatile("{.reg .pred p; mbarrier.try_wait.parity.shared::cta.b64 p, [%1], %2; selp.u32 %0, 1, 0, p;}" : "=r"(ok) : "r"(b), "r"(par) : "memory");
    return ok;
}
__device__ __forceinline__ void mbar_wait(uint32_t b, uint32_t par) {
    asm volatile("{.reg .pred p;\nW: mbarrier.try_wait.parity.shared::cta.b64 p, [%0], %1;\n@!p bra W;}" ::"r"(b), "r"(par) : "memory");
}
__device__ __forceinline__ void bar_sync(int id, int n) { asm volatile("bar.sync %0, %1;" ::"r"(id), "r"(n) : "memory"); }
__device__ __forceinline__ void tma2d(uint32_t dst, const CUtensorMap* m, int c0, int c1, uint32_t bar) {
    asm volatile("cp.async.bulk.tensor.2d.shared::cluster.global.mbarrier::complete_tx::bytes [%0], [%1, {%3, %4}], [%2];" ::"r"(dst), "l"(m), "r"(bar), "r"(c0), "r"(c1) : "memory");
}
__device__ __forceinline__ void tma3d(uint32_t dst, const CUtensorMap* m, int c0, int c1, int c2, uint32_t bar) {
    asm volatile("cp.async.bulk.tensor.3d.shared::cluster.global.mbarrier::complete_tx::bytes [%0], [%1, {%3, %4, %5}], [%2];" ::"r"(dst), "l"(m), "r"(bar), "r"(c0), "r"(c1), "r"(c2) : "memory");
}
__device__ __forceinline__ void tma4d(uint32_t dst, const CUtensorMap* m, int c0, int c1, int c2, int c3, uint32_t bar) {
    asm volatile("cp.async.bulk.tensor.4d.shared::cluster.global.mbarrier::complete_tx::bytes [%0], [%1, {%3, %4, %5, %6}], [%2];" ::"r"(dst), "l"(m), "r"(bar), "r"(c0), "r"(c1), "r"(c2), "r"(c3) : "memory");
}
__device__ __forceinline__ void l2_prefetch(const void* p, uint32_t bytes) { asm volatile("cp.async.bulk.prefetch.L2.global [%0], %1;" ::"l"(p), "r"(bytes) : "memory"); }
__device__ __forceinline__ void pf_map(const CUtensorMap* m) { asm volatile("prefetch.tensormap [%0];" ::"l"(m) : "memory"); }
__device__ __forceinline__ void wg_fence() { asm volatile("wgmma.fence.sync.aligned;" ::: "memory"); }
__device__ __forceinline__ void wg_commit() { asm volatile("wgmma.commit_group.sync.aligned;" ::: "memory"); }
template <int N> __device__ __forceinline__ void wg_wait() { asm volatile("wgmma.wait_group.sync.aligned %0;" ::"n"(N) : "memory"); }
__device__ __forceinline__ void ldsm4(uint32_t* r, uint32_t addr) { asm volatile("ldmatrix.sync.aligned.m8n8.x4.shared.b16 {%0,%1,%2,%3}, [%4];" : "=r"(r[0]), "=r"(r[1]), "=r"(r[2]), "=r"(r[3]) : "r"(addr) : "memory"); }
__device__ __forceinline__ void ldsm4t(uint32_t* r, uint32_t addr) { asm volatile("ldmatrix.sync.aligned.m8n8.x4.trans.shared.b16 {%0,%1,%2,%3}, [%4];" : "=r"(r[0]), "=r"(r[1]), "=r"(r[2]), "=r"(r[3]) : "r"(addr) : "memory"); }
__device__ __forceinline__ void stsm4(uint32_t addr, const uint32_t* r) { asm volatile("stmatrix.sync.aligned.m8n8.x4.shared.b16 [%4], {%0,%1,%2,%3};" ::"r"(r[0]), "r"(r[1]), "r"(r[2]), "r"(r[3]), "r"(addr) : "memory"); }
__device__ __forceinline__ void lds4(uint32_t* r, uint32_t addr) { asm volatile("ld.shared.v4.u32 {%0,%1,%2,%3}, [%4];" : "=r"(r[0]), "=r"(r[1]), "=r"(r[2]), "=r"(r[3]) : "r"(addr) : "memory"); }
__device__ __forceinline__ void sts4(uint32_t addr, const uint32_t* r) { asm volatile("st.shared.v4.u32 [%4], {%0,%1,%2,%3};" ::"r"(r[0]), "r"(r[1]), "r"(r[2]), "r"(r[3]), "r"(addr) : "memory"); }
__device__ __forceinline__ float2 lds2f(uint32_t addr) { float2 v; asm volatile("ld.shared.v2.f32 {%0,%1}, [%2];" : "=f"(v.x), "=f"(v.y) : "r"(addr) : "memory"); return v; }
__device__ __forceinline__ float lds1f(uint32_t addr) { float v; asm volatile("ld.shared.f32 %0, [%1];" : "=f"(v) : "r"(addr) : "memory"); return v; }
__device__ __forceinline__ void sts1f(uint32_t addr, float v) { asm volatile("st.shared.f32 [%0], %1;" ::"r"(addr), "f"(v) : "memory"); }
__device__ __forceinline__ void sts1(uint32_t addr, uint32_t v) { asm volatile("st.shared.u32 [%0], %1;" ::"r"(addr), "r"(v) : "memory"); }
__device__ __forceinline__ void ldg4_rlx(uint32_t* r, const void* p) { asm volatile("{.reg .b128 t; ld.relaxed.gpu.global.b128 t, [%4]; mov.b128 {%0,%1,%2,%3}, t;}" : "=r"(r[0]), "=r"(r[1]), "=r"(r[2]), "=r"(r[3]) : "l"(p) : "memory"); }
__device__ __forceinline__ void ldg2_rlx(uint32_t* r, const void* p) { asm volatile("{.reg .b64 t; ld.relaxed.gpu.global.b64 t, [%2]; mov.b64 {%0,%1}, t;}" : "=r"(r[0]), "=r"(r[1]) : "l"(p) : "memory"); }
__device__ __forceinline__ uint32_t ldg1_rlx(const void* p) { uint32_t v; asm volatile("ld.relaxed.gpu.global.u32 %0, [%1];" : "=r"(v) : "l"(p) : "memory"); return v; }
__device__ __forceinline__ void stg4_rlx(void* p, uint32_t a, uint32_t b, uint32_t c, uint32_t d) { asm volatile("{.reg .b128 t; mov.b128 t, {%1,%2,%3,%4}; st.relaxed.gpu.global.b128 [%0], t;}" ::"l"(p), "r"(a), "r"(b), "r"(c), "r"(d) : "memory"); }
__device__ __forceinline__ void stg2_rlx(void* p, uint32_t a, uint32_t b) { asm volatile("{.reg .b64 t; mov.b64 t, {%1,%2}; st.relaxed.gpu.global.b64 [%0], t;}" ::"l"(p), "r"(a), "r"(b) : "memory"); }
__device__ __forceinline__ void stg1_rlx(void* p, uint32_t a) { asm volatile("st.relaxed.gpu.global.u32 [%0], %1;" ::"l"(p), "r"(a) : "memory"); }
__device__ __forceinline__ void ldg4_nc(uint32_t* r, const void* p) { asm volatile("ld.global.nc.L1::no_allocate.v4.u32 {%0,%1,%2,%3}, [%4];" : "=r"(r[0]), "=r"(r[1]), "=r"(r[2]), "=r"(r[3]) : "l"(p)); }
__device__ __forceinline__ uint64_t mkdesc(uint32_t addr, uint32_t lbo, uint32_t sbo, uint32_t sw) { return (uint64_t)((addr & 0x3FFFF) >> 4) | ((uint64_t)(lbo >> 4) << 16) | ((uint64_t)(sbo >> 4) << 32) | ((uint64_t)sw << 62); }
__device__ __forceinline__ uint32_t pack2(float lo, float hi) { uint32_t r; asm("cvt.rn.bf16x2.f32 %0, %1, %2;" : "=r"(r) : "f"(hi), "f"(lo)); return r; }
__device__ __forceinline__ float blo(uint32_t v) { return __uint_as_float(v << 16); }
__device__ __forceinline__ float bhi(uint32_t v) { return __uint_as_float(v & 0xffff0000u); }
__device__ __forceinline__ float rbf(float x) { return blo(pack2(x, 0.f)); }
__device__ __forceinline__ uint32_t hf2(uint32_t a, uint32_t b, uint32_t c) { uint32_t r; asm("fma.rn.bf16x2 %0, %1, %2, %3;" : "=r"(r) : "r"(a), "r"(b), "r"(c)); return r; }
__device__ __forceinline__ uint32_t movm(uint32_t a) { uint32_t r; asm volatile("movmatrix.sync.aligned.m8n8.trans.b16 %0, %1;" : "=r"(r) : "r"(a)); return r; }
__device__ __forceinline__ float ex2(float x) { float r; asm("ex2.approx.ftz.f32 %0, %1;" : "=f"(r) : "f"(x)); return r; }
__device__ __forceinline__ void mma16(float* d, uint32_t a0, uint32_t a1, uint32_t a2, uint32_t a3, uint32_t b0, uint32_t b1) {
    asm("mma.sync.aligned.m16n8k16.row.col.f32.bf16.bf16.f32 {%0,%1,%2,%3}, {%4,%5,%6,%7}, {%8,%9}, {%0,%1,%2,%3};"
                 : "+f"(d[0]), "+f"(d[1]), "+f"(d[2]), "+f"(d[3]) : "r"(a0), "r"(a1), "r"(a2), "r"(a3), "r"(b0), "r"(b1));
}
__device__ __forceinline__ void mma8(float* d, uint32_t a0, uint32_t a1, uint32_t b0) {
    asm("mma.sync.aligned.m16n8k8.row.col.f32.bf16.bf16.f32 {%0,%1,%2,%3}, {%4,%5}, {%6}, {%0,%1,%2,%3};"
                 : "+f"(d[0]), "+f"(d[1]), "+f"(d[2]), "+f"(d[3]) : "r"(a0), "r"(a1), "r"(b0));
}
__device__ __forceinline__ uint32_t umax4(const uint32_t* v, uint32_t m) { return max(max(max(v[0], v[1]), max(v[2], v[3])), m); }
__device__ __forceinline__ uint32_t fkey(float f) { const uint32_t u = __float_as_uint(f); return u ^ (((int)u >> 31) | 0x80000000u); }
__device__ __forceinline__ float rcp(float x) { float r; asm("rcp.approx.ftz.f32 %0, %1;" : "=f"(r) : "f"(x)); return r; }
__device__ __forceinline__ float sigm(float x) { return rcp(1.f + ex2(x * -1.4426950408889634f)); }
__device__ __forceinline__ void mma16c(float* d, uint32_t a0, uint32_t a1, uint32_t a2, uint32_t a3, uint32_t b0, uint32_t b1, float c0, float c1) {
    asm("mma.sync.aligned.m16n8k16.row.col.f32.bf16.bf16.f32 {%0,%1,%2,%3}, {%4,%5,%6,%7}, {%8,%9}, {%10,%11,%12,%12};"
                 : "=f"(d[0]), "=f"(d[1]), "=f"(d[2]), "=f"(d[3]) : "r"(a0), "r"(a1), "r"(a2), "r"(a3), "r"(b0), "r"(b1), "f"(c0), "f"(c1), "f"(0.f));
}
__device__ __forceinline__ void ldsm2t(uint32_t* r, uint32_t addr) { asm volatile("ldmatrix.sync.aligned.m8n8.x2.trans.shared.b16 {%0,%1}, [%2];" : "=r"(r[0]), "=r"(r[1]) : "r"(addr) : "memory"); }
__device__ __forceinline__ void stsm2(uint32_t addr, uint32_t a, uint32_t b) { asm volatile("stmatrix.sync.aligned.m8n8.x2.shared.b16 [%2], {%0,%1};" ::"r"(a), "r"(b), "r"(addr) : "memory"); }
__device__ __forceinline__ void lds2(uint32_t* r, uint32_t addr) { asm volatile("ld.shared.v2.u32 {%0,%1}, [%2];" : "=r"(r[0]), "=r"(r[1]) : "r"(addr) : "memory"); }
__device__ __forceinline__ void sts2(uint32_t addr, uint32_t a, uint32_t b) { asm volatile("st.shared.v2.u32 [%2], {%0,%1};" ::"r"(a), "r"(b), "r"(addr) : "memory"); }
__device__ __forceinline__ void sts16(uint32_t addr, uint32_t v) { asm volatile("st.shared.u16 [%0], %1;" ::"r"(addr), "h"((unsigned short)v) : "memory"); }
__device__ __forceinline__ uint32_t lds1(uint32_t addr) { uint32_t v; asm volatile("ld.shared.u32 %0, [%1];" : "=r"(v) : "r"(addr) : "memory"); return v; }
__device__ __forceinline__ bool elect1() { uint32_t p; asm volatile("{.reg .pred P; elect.sync _|P, 0xffffffff; selp.u32 %0, 1, 0, P;}" : "=r"(p)); return p; }
__device__ __forceinline__ void tma2d_mc(uint32_t dst, const CUtensorMap* m, int c0, int c1, uint32_t bar) {
    asm volatile("cp.async.bulk.tensor.2d.shared::cluster.global.mbarrier::complete_tx::bytes.multicast::cluster [%0], [%1, {%3, %4}], [%2], %5;" ::"r"(dst), "l"(m), "r"(bar), "r"(c0), "r"(c1), "h"((unsigned short)3) : "memory");
}
__device__ __forceinline__ void tma3d_mc(uint32_t dst, const CUtensorMap* m, int c0, int c1, int c2, uint32_t bar) {
    asm volatile("cp.async.bulk.tensor.3d.shared::cluster.global.mbarrier::complete_tx::bytes.multicast::cluster [%0], [%1, {%3, %4, %5}], [%2], %6;" ::"r"(dst), "l"(m), "r"(bar), "r"(c0), "r"(c1), "r"(c2), "h"((unsigned short)3) : "memory");
}
__device__ __forceinline__ void tma4d_mc(uint32_t dst, const CUtensorMap* m, int c0, int c1, int c2, int c3, uint32_t bar) {
    asm volatile("cp.async.bulk.tensor.4d.shared::cluster.global.mbarrier::complete_tx::bytes.multicast::cluster [%0], [%1, {%3, %4, %5, %6}], [%2], %7;" ::"r"(dst), "l"(m), "r"(bar), "r"(c0), "r"(c1), "r"(c2), "r"(c3), "h"((unsigned short)3) : "memory");
}
__device__ __forceinline__ void mbar_arrive_cl(uint32_t b) { asm volatile("mbarrier.arrive.shared::cluster.b64 _, [%0];" ::"r"(b) : "memory"); }
__device__ __forceinline__ uint32_t hm2(uint32_t a, uint32_t b) { uint32_t r; asm("mul.rn.bf16x2 %0, %1, %2;" : "=r"(r) : "r"(a), "r"(b)); return r; }
__device__ __forceinline__ uint32_t clock32() { uint32_t c; asm volatile("mov.u32 %0, %clock;" : "=r"(c)); return c; }
__device__ __forceinline__ uint32_t ldsm1(uint32_t addr) { uint32_t r; asm volatile("ldmatrix.sync.aligned.m8n8.x1.shared.b16 {%0}, [%1];" : "=r"(r) : "r"(addr) : "memory"); return r; }
__device__ __forceinline__ float rsq(float x) { float r; asm("rsqrt.approx.ftz.f32 %0, %1;" : "=f"(r) : "f"(x)); return r; }
__device__ __forceinline__ void pause_until(uint32_t t0, uint32_t n) {
    asm volatile("{.reg .pred p; .reg .u32 t;\nP: mov.u32 t, %clock; sub.u32 t, t, %0; setp.lt.u32 p, t, %1;\n@p bra.uni P;}" ::"r"(t0), "r"(n) : "memory");
}
__device__ __forceinline__ void pause(uint32_t n) { if (n) { const uint32_t t = clock32(); while (clock32() - t < n) {} } }
__device__ __forceinline__ uint32_t wbuf(int it) {
    const uint32_t v = it < 4 ? it + 8 : (uint32_t)(0x8302418302b1a908ull >> (4 * it - 16)) & 15;
    return v * WST + (v >> 3) * (OFF_W - 8 * WST);
}
__device__ __forceinline__ uint32_t wobuf(int w) { return ((0x30241765u >> (4 * w)) & 7) * WST; }
__device__ __forceinline__ uint32_t inc(uint32_t v) { uint32_t r; asm volatile("{.reg .u32 t; or.b32 t, %1, 255; add.u32 %0, t, 1;}" : "=r"(r) : "r"(v)); return r; }
__device__ __forceinline__ uint32_t ldg1_acq(const void* p) { uint32_t v; asm volatile("ld.acquire.gpu.global.u32 %0, [%1];" : "=r"(v) : "l"(p) : "memory"); return v; }
__device__ __forceinline__ void tma3d_st(const CUtensorMap* m, int c0, int c1, int c2, uint32_t src) {
    asm volatile("cp.async.bulk.tensor.3d.global.shared::cta.bulk_group [%0, {%2, %3, %4}], [%1];" ::"l"(m), "r"(src), "r"(c0), "r"(c1), "r"(c2) : "memory");
}
__device__ __forceinline__ uint32_t nz(uint32_t v) { uint32_t r; asm("max.u32 %0, %1, 1;" : "=r"(r) : "r"(v)); return r; }
__device__ __forceinline__ uint32_t tagw(uint32_t w, uint32_t tc) { return ((w & 0x8000ffffu) | min(max(w & 0x7fff0000u, 0x20000000u), 0x5fff0000u)) + tc; }
template <int S_> __device__ __forceinline__ void await7(uint32_t (*r)[4], const char* const* p, uint32_t fz, uint32_t stale) {
    if (S_ == 0) asm volatile("{.reg .b128 t; .reg .pred p; .reg .u32 m, k, n;\nmov.u32 n, %clock; or.b32 n, n, %37; shr.u32 n, n, 31;\nL:\n"
        "min.u32 m, %0, %4; min.u32 m, m, %8; min.u32 m, m, %12; min.u32 m, m, %16; min.u32 m, m, %20; min.u32 m, m, %24;\n"
        "setp.eq.u32 p, m, 0; vote.sync.any.pred p, p, 0xffffffff; add.u32 n, n, 1; setp.lt.and.u32 p, n, %36, p;\n@!p bra.uni D;\n"
        "setp.eq.u32 p, %0, 0; mov.b128 t, {%0,%1,%2,%3}; @p ld.relaxed.gpu.global.b128 t, [%28+%35]; mov.b128 {%0,%1,%2,%3}, t;\n"
        "setp.eq.u32 p, %4, 0; mov.b128 t, {%4,%5,%6,%7}; @p ld.relaxed.gpu.global.b128 t, [%29+%35]; mov.b128 {%4,%5,%6,%7}, t;\n"
        "setp.eq.u32 p, %8, 0; mov.b128 t, {%8,%9,%10,%11}; @p ld.relaxed.gpu.global.b128 t, [%30+%35]; mov.b128 {%8,%9,%10,%11}, t;\n"
        "setp.eq.u32 p, %12, 0; mov.b128 t, {%12,%13,%14,%15}; @p ld.relaxed.gpu.global.b128 t, [%31+%35]; mov.b128 {%12,%13,%14,%15}, t;\n"
        "setp.eq.u32 p, %16, 0; mov.b128 t, {%16,%17,%18,%19}; @p ld.relaxed.gpu.global.b128 t, [%32+%35]; mov.b128 {%16,%17,%18,%19}, t;\n"
        "setp.eq.u32 p, %20, 0; mov.b128 t, {%20,%21,%22,%23}; @p ld.relaxed.gpu.global.b128 t, [%33+%35]; mov.b128 {%20,%21,%22,%23}, t;\n"
        "setp.eq.u32 p, %24, 0; mov.b128 t, {%24,%25,%26,%27}; @p ld.relaxed.gpu.global.b128 t, [%34+%35]; mov.b128 {%24,%25,%26,%27}, t;\n"
        "bra.uni L;\nD:}"
        : "+r"(r[0][0]), "+r"(r[0][1]), "+r"(r[0][2]), "+r"(r[0][3]), "+r"(r[1][0]), "+r"(r[1][1]), "+r"(r[1][2]), "+r"(r[1][3]), "+r"(r[2][0]), "+r"(r[2][1]), "+r"(r[2][2]), "+r"(r[2][3]), "+r"(r[3][0]), "+r"(r[3][1]), "+r"(r[3][2]), "+r"(r[3][3]), "+r"(r[4][0]), "+r"(r[4][1]), "+r"(r[4][2]), "+r"(r[4][3]), "+r"(r[5][0]), "+r"(r[5][1]), "+r"(r[5][2]), "+r"(r[5][3]), "+r"(r[6][0]), "+r"(r[6][1]), "+r"(r[6][2]), "+r"(r[6][3])
        : "l"(p[0]), "l"(p[1]), "l"(p[2]), "l"(p[3]), "l"(p[4]), "l"(p[5]), "l"(p[6]), "n"((4 - S_) * 524288), "n"(SPIN_LIMIT), "r"(fz), "r"(stale) : "memory");
    else asm volatile("{.reg .b128 t; .reg .pred p; .reg .u32 m, k, n;\nmov.u32 n, %clock; or.b32 n, n, %37; shr.u32 n, n, 31;\nL:\n"
        "xor.b32 m, %0, %38; xor.b32 k, %4, %38; and.b32 m, m, k; xor.b32 k, %8, %38; and.b32 m, m, k; xor.b32 k, %12, %38; and.b32 m, m, k; xor.b32 k, %16, %38; and.b32 m, m, k;\n"
        "xor.b32 k, %20, %38; and.b32 m, m, k; xor.b32 k, %24, %38; and.b32 m, m, k; and.b32 m, m, 0x40000000;\n"
        "setp.eq.u32 p, m, 0; vote.sync.any.pred p, p, 0xffffffff; add.u32 n, n, 1; setp.lt.and.u32 p, n, %36, p;\n@!p bra.uni D;\n"
        "xor.b32 k, %0, %38; and.b32 k, k, 0x40000000; setp.eq.u32 p, k, 0; mov.b128 t, {%0,%1,%2,%3}; @p ld.relaxed.gpu.global.b128 t, [%28+%35]; mov.b128 {%0,%1,%2,%3}, t;\n"
        "xor.b32 k, %4, %38; and.b32 k, k, 0x40000000; setp.eq.u32 p, k, 0; mov.b128 t, {%4,%5,%6,%7}; @p ld.relaxed.gpu.global.b128 t, [%29+%35]; mov.b128 {%4,%5,%6,%7}, t;\n"
        "xor.b32 k, %8, %38; and.b32 k, k, 0x40000000; setp.eq.u32 p, k, 0; mov.b128 t, {%8,%9,%10,%11}; @p ld.relaxed.gpu.global.b128 t, [%30+%35]; mov.b128 {%8,%9,%10,%11}, t;\n"
        "xor.b32 k, %12, %38; and.b32 k, k, 0x40000000; setp.eq.u32 p, k, 0; mov.b128 t, {%12,%13,%14,%15}; @p ld.relaxed.gpu.global.b128 t, [%31+%35]; mov.b128 {%12,%13,%14,%15}, t;\n"
        "xor.b32 k, %16, %38; and.b32 k, k, 0x40000000; setp.eq.u32 p, k, 0; mov.b128 t, {%16,%17,%18,%19}; @p ld.relaxed.gpu.global.b128 t, [%32+%35]; mov.b128 {%16,%17,%18,%19}, t;\n"
        "xor.b32 k, %20, %38; and.b32 k, k, 0x40000000; setp.eq.u32 p, k, 0; mov.b128 t, {%20,%21,%22,%23}; @p ld.relaxed.gpu.global.b128 t, [%33+%35]; mov.b128 {%20,%21,%22,%23}, t;\n"
        "xor.b32 k, %24, %38; and.b32 k, k, 0x40000000; setp.eq.u32 p, k, 0; mov.b128 t, {%24,%25,%26,%27}; @p ld.relaxed.gpu.global.b128 t, [%34+%35]; mov.b128 {%24,%25,%26,%27}, t;\n"
        "bra.uni L;\nD:}"
        : "+r"(r[0][0]), "+r"(r[0][1]), "+r"(r[0][2]), "+r"(r[0][3]), "+r"(r[1][0]), "+r"(r[1][1]), "+r"(r[1][2]), "+r"(r[1][3]), "+r"(r[2][0]), "+r"(r[2][1]), "+r"(r[2][2]), "+r"(r[2][3]), "+r"(r[3][0]), "+r"(r[3][1]), "+r"(r[3][2]), "+r"(r[3][3]), "+r"(r[4][0]), "+r"(r[4][1]), "+r"(r[4][2]), "+r"(r[4][3]), "+r"(r[5][0]), "+r"(r[5][1]), "+r"(r[5][2]), "+r"(r[5][3]), "+r"(r[6][0]), "+r"(r[6][1]), "+r"(r[6][2]), "+r"(r[6][3])
        : "l"(p[0]), "l"(p[1]), "l"(p[2]), "l"(p[3]), "l"(p[4]), "l"(p[5]), "l"(p[6]), "n"((4 - S_) * 524288), "n"(SPIN_LIMIT), "r"(fz), "r"(stale) : "memory");
}
template <class T> __device__ __forceinline__ T* pinp(T* p) { return (T*)__shfl_xor_sync(~0u, (unsigned long long)p, 0); }
__device__ __forceinline__ float fsel(bool c, float a, float b) { float r; asm("{.reg .pred p; setp.ne.u32 p, %3, 0; selp.f32 %0, %1, %2, p;}" : "=f"(r) : "f"(a), "f"(b), "r"((int)c)); return r; }
__device__ __forceinline__ void stg4_if(bool c, void* p, uint32_t a, uint32_t b, uint32_t d, uint32_t e) {
    asm volatile("{.reg .b128 t; .reg .pred p; setp.ne.u32 p, %5, 0; mov.b128 t, {%1,%2,%3,%4}; @p st.relaxed.gpu.global.b128 [%0], t;}" ::"l"(p), "r"(a), "r"(b), "r"(d), "r"(e), "r"((int)c) : "memory");
}
__device__ __forceinline__ void stg2_if(bool c, void* p, uint32_t a, uint32_t b) {
    asm volatile("{.reg .b64 t; .reg .pred p; setp.ne.u32 p, %3, 0; mov.b64 t, {%1,%2}; @p st.relaxed.gpu.global.b64 [%0], t;}" ::"l"(p), "r"(a), "r"(b), "r"((int)c) : "memory");
}
__device__ __forceinline__ void stg1_if(bool c, void* p, uint32_t a) {
    asm volatile("{.reg .pred p; setp.ne.u32 p, %2, 0; @p st.relaxed.gpu.global.u32 [%0], %1;}" ::"l"(p), "r"(a), "r"((int)c) : "memory");
}
__device__ __forceinline__ void ldg4_again(uint32_t* r, const void* p) {
    asm volatile("{.reg .b128 t; .reg .pred p; setp.eq.u32 p, %3, 0; mov.b128 t, {%0,%1,%2,%3}; @p ld.relaxed.gpu.global.b128 t, [%4]; mov.b128 {%0,%1,%2,%3}, t;}"
                 : "+r"(r[0]), "+r"(r[1]), "+r"(r[2]), "+r"(r[3]) : "l"(p) : "memory");
}
__device__ __forceinline__ void wgmma_rs_n192(float* d, const uint32_t* a, uint64_t bdesc, int accum) {
    asm volatile("{.reg .pred p; setp.ne.b32 p, %101, 0; wgmma.mma_async.sync.aligned.m64n192k16.f32.bf16.bf16 {%0,%1,%2,%3,%4,%5,%6,%7,%8,%9,%10,%11,%12,%13,%14,%15,%16,%17,%18,%19,%20,%21,%22,%23,%24,%25,%26,%27,%28,%29,%30,%31,%32,%33,%34,%35,%36,%37,%38,%39,%40,%41,%42,%43,%44,%45,%46,%47,%48,%49,%50,%51,%52,%53,%54,%55,%56,%57,%58,%59,%60,%61,%62,%63,%64,%65,%66,%67,%68,%69,%70,%71,%72,%73,%74,%75,%76,%77,%78,%79,%80,%81,%82,%83,%84,%85,%86,%87,%88,%89,%90,%91,%92,%93,%94,%95}, {%96,%97,%98,%99}, %100, p, 1, 1, 1;}"
        : "+f"(d[0]),"+f"(d[1]),"+f"(d[2]),"+f"(d[3]),"+f"(d[4]),"+f"(d[5]),"+f"(d[6]),"+f"(d[7]),"+f"(d[8]),"+f"(d[9]),"+f"(d[10]),"+f"(d[11]),"+f"(d[12]),"+f"(d[13]),"+f"(d[14]),"+f"(d[15]),"+f"(d[16]),"+f"(d[17]),"+f"(d[18]),"+f"(d[19]),"+f"(d[20]),"+f"(d[21]),"+f"(d[22]),"+f"(d[23]),"+f"(d[24]),"+f"(d[25]),"+f"(d[26]),"+f"(d[27]),"+f"(d[28]),"+f"(d[29]),"+f"(d[30]),"+f"(d[31]),"+f"(d[32]),"+f"(d[33]),"+f"(d[34]),"+f"(d[35]),"+f"(d[36]),"+f"(d[37]),"+f"(d[38]),"+f"(d[39]),"+f"(d[40]),"+f"(d[41]),"+f"(d[42]),"+f"(d[43]),"+f"(d[44]),"+f"(d[45]),"+f"(d[46]),"+f"(d[47]),"+f"(d[48]),"+f"(d[49]),"+f"(d[50]),"+f"(d[51]),"+f"(d[52]),"+f"(d[53]),"+f"(d[54]),"+f"(d[55]),"+f"(d[56]),"+f"(d[57]),"+f"(d[58]),"+f"(d[59]),"+f"(d[60]),"+f"(d[61]),"+f"(d[62]),"+f"(d[63]),"+f"(d[64]),"+f"(d[65]),"+f"(d[66]),"+f"(d[67]),"+f"(d[68]),"+f"(d[69]),"+f"(d[70]),"+f"(d[71]),"+f"(d[72]),"+f"(d[73]),"+f"(d[74]),"+f"(d[75]),"+f"(d[76]),"+f"(d[77]),"+f"(d[78]),"+f"(d[79]),"+f"(d[80]),"+f"(d[81]),"+f"(d[82]),"+f"(d[83]),"+f"(d[84]),"+f"(d[85]),"+f"(d[86]),"+f"(d[87]),"+f"(d[88]),"+f"(d[89]),"+f"(d[90]),"+f"(d[91]),"+f"(d[92]),"+f"(d[93]),"+f"(d[94]),"+f"(d[95])
        : "r"(a[0]), "r"(a[1]), "r"(a[2]), "r"(a[3]), "l"(bdesc), "r"(accum));
}
__device__ __forceinline__ void wgmma_rs_n48(float* d, const uint32_t* a, uint64_t bdesc, int accum) {
    asm volatile("{.reg .pred p; setp.ne.b32 p, %29, 0; wgmma.mma_async.sync.aligned.m64n48k16.f32.bf16.bf16 {%0,%1,%2,%3,%4,%5,%6,%7,%8,%9,%10,%11,%12,%13,%14,%15,%16,%17,%18,%19,%20,%21,%22,%23}, {%24,%25,%26,%27}, %28, p, 1, 1, 1;}"
        : "+f"(d[0]),"+f"(d[1]),"+f"(d[2]),"+f"(d[3]),"+f"(d[4]),"+f"(d[5]),"+f"(d[6]),"+f"(d[7]),"+f"(d[8]),"+f"(d[9]),"+f"(d[10]),"+f"(d[11]),"+f"(d[12]),"+f"(d[13]),"+f"(d[14]),"+f"(d[15]),"+f"(d[16]),"+f"(d[17]),"+f"(d[18]),"+f"(d[19]),"+f"(d[20]),"+f"(d[21]),"+f"(d[22]),"+f"(d[23])
        : "r"(a[0]), "r"(a[1]), "r"(a[2]), "r"(a[3]), "l"(bdesc), "r"(accum));
}
__device__ __forceinline__ void wgmma_rs_n80(float* d, const uint32_t* a, uint64_t bdesc, int accum) {
    asm volatile("{.reg .pred p; setp.ne.b32 p, %45, 0; wgmma.mma_async.sync.aligned.m64n80k16.f32.bf16.bf16 {%0,%1,%2,%3,%4,%5,%6,%7,%8,%9,%10,%11,%12,%13,%14,%15,%16,%17,%18,%19,%20,%21,%22,%23,%24,%25,%26,%27,%28,%29,%30,%31,%32,%33,%34,%35,%36,%37,%38,%39}, {%40,%41,%42,%43}, %44, p, 1, 1, 1;}"
        : "+f"(d[0]),"+f"(d[1]),"+f"(d[2]),"+f"(d[3]),"+f"(d[4]),"+f"(d[5]),"+f"(d[6]),"+f"(d[7]),"+f"(d[8]),"+f"(d[9]),"+f"(d[10]),"+f"(d[11]),"+f"(d[12]),"+f"(d[13]),"+f"(d[14]),"+f"(d[15]),"+f"(d[16]),"+f"(d[17]),"+f"(d[18]),"+f"(d[19]),"+f"(d[20]),"+f"(d[21]),"+f"(d[22]),"+f"(d[23]),"+f"(d[24]),"+f"(d[25]),"+f"(d[26]),"+f"(d[27]),"+f"(d[28]),"+f"(d[29]),"+f"(d[30]),"+f"(d[31]),"+f"(d[32]),"+f"(d[33]),"+f"(d[34]),"+f"(d[35]),"+f"(d[36]),"+f"(d[37]),"+f"(d[38]),"+f"(d[39])
        : "r"(a[0]), "r"(a[1]), "r"(a[2]), "r"(a[3]), "l"(bdesc), "r"(accum));
}

__global__ void __cluster_dims__(2, 1, 1) __launch_bounds__(384, 1)
fused_kernel(const __nv_bfloat16* __restrict__ xin, const __nv_bfloat16* __restrict__ wmod, const __nv_bfloat16* __restrict__ cvec, Scratch* __restrict__ S,
             const __nv_bfloat16* __restrict__ wqkv, const __nv_bfloat16* __restrict__ wo, __nv_bfloat16* __restrict__ out,
             const __nv_bfloat16* __restrict__ wr, const __nv_bfloat16* __restrict__ wg, const __nv_bfloat16* __restrict__ wu,
             const __nv_bfloat16* __restrict__ wd,
             const __grid_constant__ CUtensorMap mm, const __grid_constant__ CUtensorMap mx, const __grid_constant__ CUtensorMap mw,
             const __grid_constant__ CUtensorMap mt, const __grid_constant__ CUtensorMap mo, const __grid_constant__ CUtensorMap mg,
             const __grid_constant__ CUtensorMap mu, const __grid_constant__ CUtensorMap md,
             const __grid_constant__ CUtensorMap mw2, const __grid_constant__ CUtensorMap mout,
             const __grid_constant__ CUtensorMap mo2) {
    extern __shared__ __align__(1024) char sm_raw[];
    const int bid = blockIdx.x;
    const uint32_t sm = ((bid & 1) << 24) + SM0;
    STAMP(30);
    const uint32_t t_start = clock32();
    if (bid < CPF && threadIdx.x == 0)
        asm volatile("cp.async.bulk.prefetch.tensor.2d.L2.global [%0, {%1, %2}];" ::"l"(&mm), "r"((bid & 1) * 640 + (bid >> 4) * 64), "r"(((bid >> 1) & 7) * 80) : "memory");
    const int cl = bid >> 1, rank = bid & 1, c7 = ((cl - 36) * 37) >> 8;
    const int grp = cl < 4 ? 0 : (cl < 36 ? (cl - 4) & 7 : cl - 35 - 7 * c7);
    const int ti = grp * 2 + rank;
    auto ldx = [&](int c) { mbar_expect_tx(BAR(B_XF + c), 16384); tma3d(sm + c * 16384, &mx, c * 64, ti >> 3, (ti & 7) * 128, BAR(B_XF + c)); };
    if (threadIdx.x == 256 && bid < 128) {
        mbar_init(BAR(B_XF), 1); mbar_init(BAR(B_XF + 1), 1);
        if (XDELAY > 1) pause_until(t_start, XDELAY);
        ldx(0); ldx(1);
        STAMPT(22, 256);
#pragma unroll
        for (int i = 2; i < 10; i++) mbar_init(BAR(B_XF + i), 1);
        mbar_init(BAR(B_T0), 1);
        asm volatile("fence.mbarrier_init.release.cluster;" ::: "memory");
        ldx(2); ldx(3); ldx(4);
    }
    const int warp = __shfl_sync(~0u, threadIdx.x >> 5, 0);

#define PIN(v) __shfl_xor_sync(~0u, (v), 0)
#define LANE_VARS const int tid = PIN(threadIdx.x), lane = tid & 31, g = lane >> 2, q = lane & 3; \
    const uint32_t frow = (lane & 7) + (lane >> 4) * 8, fh = (lane >> 3) & 1;
    if (bid >= 128) {
        LANE_VARS
        const int h = bid - 128;
        if (warp >= 8) {
            if (warp == 8) return;
            const int t = tid - 288;
            if (t < 90) stg4_rlx(&S->tab[(5 + t / 9) * 4 + h][t % 9], 0u, 0u, 0u, 0u);
            __syncwarp();
            asm volatile("bar.arrive 1, 352;" ::: "memory");
            bar_sync(2, 96);
            if (t == 0) asm volatile("red.release.gpu.global.add.u32 [%0], 32;" ::"l"(&S->cnt) : "memory");
            return;
        }
        const uint32_t slot = sm + warp * 20480, bar = BAR(warp * 2);
        auto column = [&](int job) {
            const int n = job * 4 + h;
            return job < 10 ? ((h & 1) ? (job < 5 ? 10 : 30) : (job < 5 ? 0 : 10)) + (n >> 1) : (n < 50 ? n - 10 : n);
        };
        auto load = [&](int job) {
            mbar_expect_tx(bar + (job & 1) * 8, 10240);
            tma2d(slot + (job & 1) * 10240, &mm, column(job) * 64, warp * 80, bar + (job & 1) * 8);
        };
        if (elect1()) { mbar_init(bar, 1); mbar_init(bar + 8, 1); load(0); }
        __syncwarp();
        uint32_t b[10];
#pragma unroll
        for (int s = 0; s < 10; s++) b[s] = ldg1_rlx((const uint32_t*)cvec + warp * 40 + s * 4 + q);
        if (lane < 8 && warp < 5) stg4_rlx(&S->tab[warp * 4 + h][lane], 0u, 0u, 0u, 0u);
#pragma unroll
        for (int s = 0; s < 10; s++) b[s] = pack2(blo(b[s]) * sigm(blo(b[s])), bhi(b[s]) * sigm(bhi(b[s])));
        const uint32_t fa = slot + frow * 128 + ((fh ^ (lane & 7)) << 4);
        const int c0 = (lane >> 3) * 16 + (lane & 1) * 8 + (lane & 6);
#pragma unroll 1
        for (int job = 0; job < 15; job++) {
            uint32_t w2 = 0;
            if (job >= 5) w2 = ldg1_rlx(wr + (column(job) % 10) * 64 + c0);

            mbar_wait(bar + (job & 1) * 8, (job >> 1) & 1);
            if (job == 0) { if (elect1()) load(1); __syncwarp(); }
            float d[4][4] = {};
#pragma unroll
            for (int s = 0; s < 5; s++) {
#pragma unroll
                for (int m = 0; m < 4; m++) { uint32_t a[4]; ldsm4t(a, (fa ^ (m * 32)) + (job & 1) * 10240 + s * 2048); mma16(d[m], a[0], a[1], a[2], a[3], b[2 * s], b[2 * s + 1]); }
            }
            const uint32_t red = sm + OFF_W + (job & 1) * 2048;
            sts1f(red + (warp * 64 + q * 8 + g) * 4, q == 0 ? d[0][0] : (q == 1 ? d[0][2] : (q == 2 ? d[1][0] : d[1][2])));
            sts1f(red + (warp * 64 + 32 + q * 8 + g) * 4, q == 0 ? d[2][0] : (q == 1 ? d[2][2] : (q == 2 ? d[3][0] : d[3][2])));
            __syncwarp();
            if (HPAUSE && job == HJOB) pause_until(t_start, HPAUSE);
            if (job < 13 && elect1()) load(job + 2);
            __syncwarp();
            bar_sync(0, 256);
            if (job == 5) bar_sync(1, 352);
            if (warp == (job & 7)) {
                float y0 = 0.f, y1 = 0.f;
#pragma unroll
                for (int w = 0; w < 8; w++) { const float2 v = lds2f(red + (w * 64 + c0) * 4); y0 += v.x; y1 += v.y; }
                const uint32_t t = hf2(pack2(y0, y1), 0x3f803f80u, ((h & 1) && job < 10) ? 0x3f803f80u : 0x80008000u);
                uint32_t* const p = (uint32_t*)&S->tab[job * 4 + h][0];
                stg1_rlx(p + lane, nz(t));
                float dot = fmaf(blo(t), blo(w2), bhi(t) * bhi(w2));
#pragma unroll
                for (int o = 16; o; o >>= 1) dot += __shfl_xor_sync(~0u, dot, o);
                if (lane == 0) stg1_rlx(p + 32, dot == 0.f ? 0x80000000u : __float_as_uint(dot));
            }
            if (job == 0) STAMP(27);
            if (job == 8) STAMP(28);
        }
        STAMP(17);
        return;
    }
    uint32_t ep0;
    if (__builtin_expect(warp == 8, 1)) {
        asm volatile("barrier.cluster.arrive.relaxed.aligned;" ::: "memory");
        if (elect1()) {
#pragma unroll 1
            for (int c = 5; c < 10; c++) ldx(c);
        }
        __syncwarp();
    } else {
        if (warp < 8) {
            if (elect1()) {
#pragma unroll
                for (int i = 0; i < 8; i++) { const int b = B_WF + warp * 8 + i; mbar_init(BAR(b), b >= B_WE ? 16 : (b >= B_G2 ? 8 : (b >= B_EP ? 2 : (b == B_WO ? 7 : 1)))); }
                asm volatile("fence.mbarrier_init.release.cluster;" ::: "memory");
            }
            __syncwarp();
        }
        if (warp == 9) ep0 = ldg1_rlx(&S->cnt);
        asm volatile("barrier.cluster.arrive.relaxed.aligned;" ::: "memory");
    }
    const int sl = cl < 4 ? 4 + cl : (cl < 36 ? (cl - 4) >> 3 : 4 + c7);
    const int j = sl ^ (((sl + 2) >> 2) & (SWAPM >> grp) & 1), role = ti * 8 + j, odd = j & 1;
    const int fi = j * 16 + ti;
    const int al = ((j + 1) & 2) == 0;
    Exch* const X = &S->x;
    if (warp >= 8) {
        asm volatile("setmaxnreg.dec.sync.aligned.u32 72;");
        if (warp == 8) {
            asm volatile("barrier.cluster.wait.aligned;" ::: "memory");
            if (!elect1()) return;
            const int col_main = 80 * j + 16 * odd, col_tail = 80 * j + (odd ? 0 : 64);
            auto load_w = [&](int it) {
                const uint32_t b = BAR(B_WF + it), dst = sm + wbuf(it) + rank * 6144;
                mbar_expect_tx(b, WST);
                tma4d_mc(dst, al ? &mw2 : &mw, 0, it * 32 + rank * 16, col_main >> (5 + al), 0, b);
                tma3d_mc(dst + 12288 - rank * 4608, &mt, col_tail, it * 32 + rank * 16, 0, b);
            };
            int it = 0, wn = 0, gn = 0;
#pragma unroll 1
            for (int r = -2; r < 19; r++) {
                if (r == -2 && WLATE) mbar_wait(BAR(B_XF + WLATE), 0);
                if (r == -1) mbar_wait(BAR(B_XF + XWAIT), 0);
                if (r >= 0) mbar_wait(BAR(B_WE + r), 0);
                const int lim = min(r < 2 ? (r == 1 ? 7 : 2 * r + 6) : r + 7, 20);
#pragma unroll 1
                for (; it < lim; it++) load_w(it);
                if (r == -1 || r == 0) l2_prefetch(wqkv + (size_t)(384 + r * 256 + role * 2) * 1920, 2 * 3840);
                if (r == 0) l2_prefetch(wo + role * 3200, 6400);
                if (MPF == 1 && r >= MPF0 && r < MPF0 + 5) l2_prefetch(wmod + (size_t)(role * 5 + r - MPF0) * 3840 + 1280, 5120);
                if (MPF == 2 && r >= MPF0 && r < MPF0 + 10) l2_prefetch(wmod + (size_t)(role * 5 + ((r - MPF0) >> 1)) * 3840 + 1920 + (r & 1) * 1280, 1280);
                if (((GU_MASK >> (r + 2)) & 1) && fi < 108) { if (gn == 0) mbar_expect_tx(BAR(B_FG), 40960); tma2d(sm + OFF_WG + gn * 10240, (fi & 1) ? &mu : &mg, (fi >> 1) * 32, gn * 160, BAR(B_FG)); gn++; }
#pragma unroll 1
                for (int n = ((WO_MASK >> (r + 2)) & 1) + (r == 14); n > 0; n--) {
                    const int row = (j ^ wn) * 80 + rank * 40;
                    const uint32_t b = BAR(wn ? B_WO : B_WO0), dst = sm + wobuf(wn) + rank * 2560;
                    mbar_expect_tx(b, WO16 ? 12800 : WST);
                    tma2d_mc(dst, &mo, col_main, row, b); tma2d_mc(dst + 5120, &mo, col_main + 32, row, b); tma2d_mc(dst + 10240, WO16 ? &mo2 : &mo, col_tail, row, b);
                    wn++;
                }
                if (!NOPF && r >= PF0 && r < PF0 + 3 * PFN) { const int m = (r - PF0) / PFN; l2_prefetch((m == 0 ? wg : (m == 1 ? wu : wd)) + role * 8640 + (r - PF0 - m * PFN) * (8640 / PFN), 17280 / PFN); }
            }
            STAMPT(24, 256);
            if (fi >= 88) { mbar_wait(BAR(B_G2), 0); mbar_expect_tx(BAR(B_FD), 55296); tma3d(sm + OFF_WD, &md, (fi - 88) * 16, 0, 0, BAR(B_FD)); }
            return;
        }
        asm volatile("barrier.cluster.wait.aligned;" ::: "memory");
        const int tid = threadIdx.x, lane = tid & 31, fh = (lane >> 3) & 1;
        int gd = 0;
        if (warp == 9) {
            {
                uint32_t ta = sm + OFF_TAB + fh * 1280 + (lane >> 4) * 128 + (lane & 4) * 16 + (lane & 1) * 32 + (lane & 2) * 4;
                const uint4* tp = &S->tab[lane >> 3][lane & 7];
                pause_until(t_start, TDELAY);
#pragma unroll 1
                for (int e = 0; e < 5; e++) {
                    uint32_t w[4];
                    if (e > 1) mbar_wait(BAR(B_WE + 4 * e - 8), 0);
                    while (true) {
                        ldg4_rlx(w, tp);
                        if (!__any_sync(~0u, min(min(w[0], w[1]), min(w[2], w[3])) == 0) || ++gd > SPIN_LIMIT) break;
                        pause(P_TAB);
                    }
                    sts2(ta, w[0], w[1]); sts2(ta + 16, w[2], w[3]);
                    __syncwarp();
                    if (e == 0) { STAMPT(2, 288); if (lane == 0) sts1(sm + OFF_EP + EP_US + 8, ep0 << 22 & 0x40000000u); }
                    if (lane == 0) mbar_arrive(BAR(e ? B_TB - 1 + e : B_T0));
                    ta += 256; tp += 288;
                }
            }
            uint32_t h[5][4];
            while (ldg1_acq(&S->cnt) != inc(ep0) && ++gd < SPIN_LIMIT) __nanosleep(YSLEEP);
            __syncwarp();
            if (lane == 0) mbar_arrive(BAR(B_RDY));
            mbar_wait(BAR(HALO_GO), 0);
            pause(D_H);
            if ((ti & 7) == 0) {
#pragma unroll
                for (int s = 0; s < 20; s++) h[s >> 2][s & 3] = 0;
            } else {
                do {
                    pause(P_H);
#pragma unroll
                    for (int s = 0; s < 5; s++) ldg4_rlx(h[s], &X->halo[(role - 8 - (ti & 8)) * 160 + s * 32 + lane]);
                } while (__any_sync(~0u, min(min(min(h[0][0], h[1][0]), min(h[2][0], h[3][0])), h[4][0]) == 0) && ++gd < SPIN_LIMIT);
            }
            const uint32_t p8 = sm + OFF_P8 - 4096, va = p8 + 2048 + (lane & 7) * VP + (lane >> 3) * 16;
            sts4(p8 + 2048 + 1408 + lane * 16, h[0]); sts4(p8 + 1408 + lane * 16, h[1]); sts2(p8 + (lane >> 4) * 2048 + 1920 + (lane & 15) * 8, h[2][0], h[2][1]);
            stsm4(va, h[3]); stsm4(va + 64, h[4]); stsm2(va + 128, h[2][2], h[2][3]);
            __syncwarp();
            if (lane == 0) mbar_arrive(BAR(B_HL));
            STAMPT(19, 288);
            mbar_wait(BAR(B_G3), 0);
            pause(D_REC);
            do {
                pause(P_REC);
                ldg4_rlx(h[0], &X->ra[(lane >> 3) * 8 + grp][lane & 7]); ldg4_rlx(h[1], &X->ra[(lane >> 3) * 8 + 32 + grp][lane & 7]);
            } while (__any_sync(~0u, min(min(h[0][1], h[0][3]), min(h[1][1], h[1][3])) == 0) && ++gd < SPIN_LIMIT);
            const uint32_t kwin = __reduce_max_sync(~0u, max(max(h[0][0], h[0][2]), max(h[1][0], h[1][2])));
            const uint32_t tok = __reduce_min_sync(~0u, min(min(h[0][0] == kwin ? h[0][1] : 2048u, h[0][2] == kwin ? h[0][3] : 2048u), min(h[1][0] == kwin ? h[1][1] : 2048u, h[1][2] == kwin ? h[1][3] : 2048u)));
            if (lane == 0) {
                const uint32_t t = (tok - 1) & 2047, wi = (t & 1) * 64 + (t >> 5), wv[4] = {kwin, t, wi, wi * 320};
                sts4(sm + OFF_EP + EP_US + 32, wv); mbar_arrive(BAR(B_WIN));
            }
            if (lane < 8 && role < 20) stg4_rlx(&S->tab[role][lane], 0u, 0u, 0u, 0u);
            return;
        }
        const int at = tid - 320;
        const int kg = at < 40 ? 80 * j + 2 * at : max(fi - 88, 0) * 16 + 2 * (at & 7);
        const uint32_t w2 = *(const uint32_t*)(wr + kg);
        mbar_wait(BAR(B_WF + RWAIT), 0);
        if (RTB) mbar_wait(BAR(B_T0), 0);
        {
            uint4* p = &X->o[4 * 128 * 256] + role * RV + at;
#pragma unroll 1
            for (int r = 0; r < RV / 64; r++) {
                stg4_rlx(p, 0u, 0u, 0u, 0u);
                p += 64;
                __nanosleep(RSLEEP);
            }
        }
        bar_sync(5, 64);
        if (at == 0) { mbar_wait(BAR(B_TB), 0); }
        if (at == 0) asm volatile("red.release.gpu.global.add.u32 [%0], 1;" ::"l"(&S->cnt) : "memory");
        mbar_wait(BAR(B_RDY), 0);
        const uint32_t* const mp = (const uint32_t*)&S->tab[0][0] + ((kg >> 4) & 3) * 8 + (kg & 6) + ((kg >> 3) & 1);
        const int p = odd ? (at < 8 ? at + 32 : at - 8) : at, lm = min(lane, 9);
        const uint32_t a = sm + OFF_EP + (p & 3) * 48 + (p >> 2) * 4;
#pragma unroll 1
        for (int ph = 0; ph < 4; ph++) {
            uint32_t v, us;
            mbar_wait(BAR(ph < 2 ? TB_GO : TB_GO2), 0);
            while (true) {
                v = ldg1_rlx(mp + (ph < 2 ? 20 + ph + (kg >> 6) * 2 : 20 + ph * 10 + (kg >> 6)) * 288);
                us = ldg1_rlx(&S->tab[ph < 2 ? 20 + ph + lm * 2 : 20 + ph * 10 + lm][8]);
                if (!__any_sync(~0u, min(v, us) == 0) || ++gd > SPIN_LIMIT) break;
                __nanosleep(200);
            }
            if (at < 40) {
                sts1(a + ph * 192, v);
                if (ph == 1) {
                    const float u0 = blo(v) * blo(w2), u1 = bhi(v) * bhi(w2);
                    const uint32_t uh = pack2(u0, u1);
                    sts1(a + 768, 0x3f803f80u); sts1(a + 960, uh); sts1(a + 1152, pack2(u0 - blo(uh), u1 - bhi(uh)));
                }
            } else sts1(sm + OFF_EP + EP_GD + (at & 7) * 4, v);
            float t = lane < 10 ? __uint_as_float(us) : 0.f;
#pragma unroll
            for (int o = 1; o < 16; o <<= 1) t += __shfl_xor_sync(~0u, t, o);
            if (at == 0) sts1f(sm + OFF_EP + EP_US + 12 + ph * 4, t);
            __syncwarp();
            if (lane == 0 && ph) mbar_arrive(BAR(B_EP - 1 + ph));
        }
        STAMPT(20, 320);
    } else {
        asm volatile("setmaxnreg.inc.sync.aligned.u32 216;");
        asm volatile("barrier.cluster.wait.aligned;" ::: "memory");
        LANE_VARS
        const int tw = ti * 8 + warp;
        const uint32_t oo = tw * 4096 + j * 512 + lane * 16;
        const uint32_t pair = (uint32_t)(lane & 1) << 24;
        const uint32_t hi = lane >> 4, xa = sm + (warp * 16 + (lane & 15)) * 128 + ((hi ^ (lane & 7)) << 4);
        const uint32_t p8 = sm + OFF_P8 + warp * 2048, q8 = p8 - (warp ? 2048 : 4096), q9 = p8 - 2048 + (warp ? 16384 : 0);
        const uint32_t l16 = PIN(lane * 16), kt = PIN(hi * 16384 + (lane & 15) * 8), va = PIN(p8 + (lane & 7) * VP + (lane >> 3) * 16);
        const uint32_t vc = PIN(p8 + (lane & 7) * VP + fh * 16384 + hi * 16);
        const uint32_t vh = PIN((fh ? p8 : q9) + (lane & 7) * VP + hi * 16), kh = PIN((hi ? q9 : q8) + (lane & 15) * 8);
        const uint32_t mgt = PIN((2 * q > g ? 0xffffu : 0u) | (2 * q + 1 > g ? 0xffff0000u : 0u));
        uint32_t rr0, rr1, nn0, nn1;
        {
            float gA[2][4] = {}, gB[2][4] = {};
            uint32_t xb = sm + (warp * 16 + frow) * 128 + ((fh ^ (lane & 7)) << 4), one[16];
#pragma unroll
            for (int k = 0; k < 16; k++) one[k] = 0x3f803f80u + ((uint32_t)tid >> (12 + k));
#pragma unroll 1
            for (int c = 0; c < 10; c += 2) {
                mbar_wait(BAR(B_XF + c), 0); mbar_wait(BAR(B_XF + c + 1), 0);
                uint32_t a[8][4];
#pragma unroll
                for (int k = 0; k < 8; k++) ldsm4(a[k], (xb ^ ((k & 3) * 32)) + (k >> 2) * 16384);
                xb += 32768;
#pragma unroll
                for (int k = 0; k < 8; k++) {
                    uint32_t t[4];
#pragma unroll
                    for (int e = 0; e < 4; e++) asm volatile("mov.b32 %0, %1;" : "=r"(t[e]) : "r"(a[k][e]));
                    mma16(gA[k & 1], t[0], one[(k & 3) * 4], t[1], one[(k & 3) * 4 + 1], a[k][0], a[k][1]);
                    mma16(gB[k & 1], t[2], one[(k & 3) * 4 + 2], t[3], one[(k & 3) * 4 + 3], a[k][2], a[k][3]);
                }
            }
            const int src = (lane & ~3) | (g >> 1), e = g & 1;
            const float ss0 = __shfl_sync(~0u, e ? gA[0][1] + gA[1][1] : gA[0][0] + gA[1][0], src), ss1 = __shfl_sync(~0u, e ? gB[0][1] + gB[1][1] : gB[0][0] + gB[1][0], src);
            const float m0 = __shfl_sync(~0u, e ? gA[0][3] + gA[1][3] : gA[0][2] + gA[1][2], src) * (1.f / 640), m1 = __shfl_sync(~0u, e ? gB[0][3] + gB[1][3] : gB[0][2] + gB[1][2], src) * (1.f / 640);
            const float r0 = rbf(rsq(fmaxf(ss0 * (1.f / 640) - m0 * m0, 0.f) + 1e-5f)), r1 = rbf(rsq(fmaxf(ss1 * (1.f / 640) - m1 * m1, 0.f) + 1e-5f));
            rr0 = pack2(r0, r0); rr1 = pack2(r1, r1); nn0 = pack2(-m0 * r0, -m0 * r0); nn1 = pack2(-m1 * r1, -m1 * r1);
        }
        uint32_t xr[5][4];
#pragma unroll
        for (int s = 0; s < 5; s++) {
            const int ks = 5 * j + (odd ? (s == 4 ? 0 : s + 1) : s);
            ldsm4(xr[s], (xa ^ ((ks & 3) * 32)) + (ks >> 2) * 16384);
        }
        STAMP(0);
        mbar_wait(BAR(B_T0), 0);
        if (WGBAR) bar_sync(1, 256);
        float acc[120];
#pragma unroll
        for (int i = 0; i < 120; i++) asm volatile("" : "=f"(acc[i]));
        {
            uint32_t a[2][2][4], raw[2][4], tt[2][4];
            uint32_t tb = sm + OFF_TAB + q * 16, xp = xa;
            auto load = [&](int u) {
                ldsm4(raw[0], xp ^ (u * 64)); ldsm4(raw[1], xp ^ (u * 64 + 32));
                lds4(tt[0], tb + u * 64 + 1280); lds4(tt[1], tb + u * 64);
            };
            auto xform = [&](uint32_t (*dst)[4]) {
#pragma unroll
                for (int h = 0; h < 2; h++) {
                    dst[h][0] = hf2(hf2(raw[h][0], rr0, nn0), tt[0][2 * h], tt[1][2 * h]); dst[h][1] = hf2(hf2(raw[h][1], rr1, nn1), tt[0][2 * h], tt[1][2 * h]);
                    dst[h][2] = hf2(hf2(raw[h][2], rr0, nn0), tt[0][2 * h + 1], tt[1][2 * h + 1]); dst[h][3] = hf2(hf2(raw[h][3], rr1, nn1), tt[0][2 * h + 1], tt[1][2 * h + 1]);
                }
            };
            const uint64_t dm0 = al ? mkdesc(SM0, 2048, 1024, 1) : mkdesc(SM0, 1024, 512, 2), dt0 = mkdesc(SM0 + 12288, 512, 256, 3);
            load(0); xform(a[0]);
            STAMP(3);
#pragma unroll 1
            for (int i2 = 0; i2 < 10; i2++) {
#pragma unroll
                for (int u = 0; u < 2; u++) {
                    const int it = i2 * 2 + u;
                    const uint32_t bo = wbuf(it) >> 4;
                    mbar_wait(BAR(B_WF + it), 0);
                    if (LAG && warp < 4 && i2 * 2 + u == 20 - LAG) bar_sync(4, 256);
                    wg_fence();
#pragma unroll
                    for (int h = 0; h < 2; h++) { wgmma_rs_n192(acc, a[u][h], dm0 + bo + h * 384, (u | h) ? 1 : i2); wgmma_rs_n48(acc + 96, a[u][h], dt0 + bo + h * 96, (u | h) ? 1 : i2); }
                    wg_commit();
                    if (LAG && u == 1 && warp >= 4 && i2 == 9) asm volatile("bar.arrive 4, 256;" ::: "memory");
                    if (u == 1) { xp += 16384; tb += 128; }
                    if (u == 1 && (i2 & 1) && i2 < 9) mbar_wait(BAR(B_TB + (i2 >> 1)), 0);
                    load(u ^ 1);
                    wg_wait<1>();
                    if (lane < 2 && (u == 1 || i2 > 0)) mbar_arrive_cl(pair + BAR0(B_WE - 1 + it));
                    xform(a[u ^ 1]);
                }
            }
        }
        uint32_t own[5][4], ab[3][7][4], sv, tc, fz = 0;
        const char* op[7];
        auto ldo = [&](int s, uint32_t (*dst)[4]) {
#pragma unroll
            for (int w = 0; w < 7; w++) ldg4_rlx(dst[w], op[w] + (4 - s) * 524288);
        };
        {
            uint32_t Q[10][2], K[2][10], V[2][10];
            mbar_wait(BAR(B_RDY), 0);
            const bool pub = warp == 7 && (~ti & 7);
            uint4* const hp = pinp(&X->halo[(role - (ti & 8)) * 160 + lane]);
            sv = lds1(sm + OFF_EP + EP_US + 8); tc = (sv ^ 0x40000000u) - 0x20000000u;
            wg_wait<0>();
            STAMP(4); STAMPT(18, 128);
#define ACC_IDX(t, m) (odd_ ? (t >= 2 ? m * 32 + (t - 2) * 4 : 96 + m * 8 + t * 4) : (t < 8 ? m * 32 + t * 4 : 96 + m * 8 + (t - 8) * 4))
#define PACK1(odd_v) { constexpr bool odd_ = odd_v; _Pragma("unroll") for (int t = 0; t < 10; t++) { \
                K[1][t] = pack2(acc[ACC_IDX(t, 1) + 2], acc[ACC_IDX(t, 1) + 3]); V[1][t] = pack2(acc[ACC_IDX(t, 2) + 2], acc[ACC_IDX(t, 2) + 3]); \
                if (!PK) V[0][t] = pack2(acc[ACC_IDX(t, 2)], acc[ACC_IDX(t, 2) + 1]); } }
#define PACK2(odd_v) { constexpr bool odd_ = odd_v; _Pragma("unroll") for (int t = 0; t < 10; t++) { \
                if (PK) V[0][t] = pack2(acc[ACC_IDX(t, 2)], acc[ACC_IDX(t, 2) + 1]); \
                K[0][t] = pack2(acc[ACC_IDX(t, 1)], acc[ACC_IDX(t, 1) + 1]); \
                Q[t][0] = pack2(acc[ACC_IDX(t, 0)], acc[ACC_IDX(t, 0) + 1]); Q[t][1] = pack2(acc[ACC_IDX(t, 0) + 2], acc[ACC_IDX(t, 0) + 3]); } }
            if (odd) PACK1(true) else PACK1(false)
            if (pub) {
                K[1][0] = nz(K[1][0]); K[1][5] = nz(K[1][5]); K[1][2] = nz(K[1][2]); V[1][0] = nz(V[1][0]); V[1][4] = nz(V[1][4]);
                stg4_rlx(hp, K[1][0], K[1][1], K[1][3], K[1][4]); stg4_rlx(hp + 32, K[1][5], K[1][6], K[1][8], K[1][9]);
                stg4_rlx(hp + 96, V[1][0], V[1][1], V[1][2], V[1][3]); stg4_rlx(hp + 128, V[1][4], V[1][5], V[1][6], V[1][7]); stg4_rlx(hp + 64, K[1][2], K[1][7], V[1][8], V[1][9]);
            }
            uint32_t VT[5][4], KH[10];
            {
                const uint32_t k0[4] = {K[1][0], K[1][1], K[1][3], K[1][4]}, k1[4] = {K[1][5], K[1][6], K[1][8], K[1][9]};
                sts4(p8 + 16384 + 1408 + l16, k0); sts4(p8 + 1408 + l16, k1); sts2(p8 + 1920 + kt, K[1][2], K[1][7]);
                stsm4(va + 16384, V[1]); stsm4(va + 16384 + 64, V[1] + 4); stsm2(va + 16384 + 128, V[1][8], V[1][9]);
                if (!PK) { stsm4(va, V[0]); stsm4(va + 64, V[0] + 4); stsm2(va + 128, V[0][8], V[0][9]); }
            }
            __syncwarp();
            if (lane == 0) mbar_arrive(BAR(B_HL + 1 + warp));
            if (PK) {
                if (odd) PACK2(true) else PACK2(false)
                stsm4(va, V[0]); stsm4(va + 64, V[0] + 4); stsm2(va + 128, V[0][8], V[0][9]);
                __syncwarp();
            }
#pragma unroll
            for (int s = 0; s < 5; s++) ldsm4t(VT[s], vc + s * 32);
            if (!PK) { if (odd) PACK2(true) else PACK2(false) }
            float sb[4][4], sc[4][4];
            uint32_t qs[4][2];
#pragma unroll
            for (int h = 0; h < 4; h++) {
                const int ts = (h >> 1) * 5 + 2, ta = (h >> 1) * 5 + (h & 1) * 3;
                const bool mine = (q >> 1) == (h & 1);
                qs[h][0] = mine ? Q[ts][0] : 0u; qs[h][1] = mine ? Q[ts][1] : 0u;
                mma16c(sb[h], Q[ta][0], Q[ta][1], Q[ta + 1][0], Q[ta + 1][1], K[0][ta], K[0][ta + 1], 0.f, 0.f);
                mma16c(sc[h], Q[ta][0], Q[ta][1], Q[ta + 1][0], Q[ta + 1][1], K[1][ta], K[1][ta + 1], 0.f, 0.f);
                mma8(sb[h], qs[h][0], qs[h][1], K[0][ts]);
                mma8(sc[h], qs[h][0], qs[h][1], K[1][ts]);
            }
            const bool gt0 = mgt & 1, gt1 = (int)mgt < 0;
            auto half = [&](int e, float (*pv)[4], float (*cu)[4], uint32_t (*VT)[4]) {
                const float cs = 0.22360679774997896f * 1.4426950408889634f;
                uint32_t p[4];
                float t0[4], t1[4], m[4];
#pragma unroll
                for (int h = 0; h < 4; h++) { t0[h] = gt0 ? pv[h][2 * e] : cu[h][2 * e]; t1[h] = gt1 ? pv[h][2 * e + 1] : cu[h][2 * e + 1]; m[h] = fmaxf(t0[h], t1[h]); }
#pragma unroll
                for (int h = 0; h < 4; h++) m[h] = fmaxf(m[h], __shfl_xor_sync(~0u, m[h], 1));
#pragma unroll
                for (int h = 0; h < 4; h++) m[h] = fmaxf(m[h], __shfl_xor_sync(~0u, m[h], 2)) * -cs;
#pragma unroll
                for (int h = 0; h < 4; h++) p[h] = pack2(ex2(fmaf(t0[h], cs, m[h])), ex2(fmaf(t1[h], cs, m[h])));
#pragma unroll
                for (int pr = 0; pr < 2; pr++) {
                    const uint32_t a0 = p[2 * pr] & mgt, a1 = p[2 * pr + 1] & mgt, a2 = p[2 * pr] & ~mgt, a3 = p[2 * pr + 1] & ~mgt;
                    float l[4];
                    mma16c(l, a0, a1, a2, a3, 0x3f803f80u, 0x3f803f80u, 0.f, 0.f);
                    l[0] = rcp(l[0]); l[2] = rcp(l[2]);
#pragma unroll
                    for (int r = 0; r < 5; r++) {
                        const int t = pr * 5 + r;
                        float d[4];
                        mma16c(d, a0, a1, a2, a3, VT[t >> 1][(t & 1) * 2], VT[t >> 1][(t & 1) * 2 + 1], 0.f, 0.f);
                        const bool od = r == 2 ? (q & 2) : r > 2;
                        const float li = od ? l[2] : l[0];
                        own[t >> 1][(t & 1) * 2 + e] = pack2((od ? d[2] : d[0]) * li, (od ? d[3] : d[1]) * li);
                    }
                }
            };
            auto rest = [&](bool merged) {
                if (!merged) half(1, sb, sc, VT);
                mbar_wait(BAR(B_HL + warp), 0);
                uint32_t VH[5][4];
                float sa[4][4];
                lds4(KH, q9 + 1408 + l16); lds4(KH + 4, q8 + 1408 + l16); lds2(KH + 8, kh + 1920);
#pragma unroll
                for (int s = 0; s < 5; s++) ldsm4t(VH[s], vh + s * 32);
                STAMP(5); STAMPT(25, 64);
                if (SF & 2) fz |= clock32();
                const float ninf = (tw & 63) == 0 ? -INFINITY : 0.f;
#pragma unroll
                for (int h = 0; h < 4; h++) {
                    const int ta = (h >> 1) * 5 + (h & 1) * 3;
                    mma16c(sa[h], Q[ta][0], Q[ta][1], Q[ta + 1][0], Q[ta + 1][1], KH[2 * h], KH[2 * h + 1], ninf, ninf);
                    mma8(sa[h], qs[h][0], qs[h][1], KH[8 + (h >> 1)]);
                }
                if (merged) half(1, sb, sc, VT);
                half(0, sa, sb, VH);
            };
            if (MERGE == 0 || (MERGE == 2 && warp == 0) || (MERGE == 3 && (warp & 3) == 0)) rest(false); else rest(true);
#pragma unroll
            for (int w = 0; w < 7; w++) op[w] = (const char*)X->o + (oo ^ (w * 512 + 512));
#pragma unroll
            for (int s = 0; s < 5; s++) {
                if (s == EARLY_LD) { if (D_E) pause(D_E); ldo(0, ab[0]); }
                own[s][0] = s ? tagw(own[s][0], tc) : nz(own[s][0]); stg4_rlx((char*)X->o + oo + (4 - s) * 524288, own[s][0], own[s][1], own[s][2], own[s][3]);
            }
        }
        STAMP(6); STAMPT(21, 128); STAMPT(26, 64);
        if (SF & 4) fz |= clock32();
        float ac2[40];
#pragma unroll
        for (int i = 0; i < 40; i++) asm volatile("" : "=f"(ac2[i]));
        {
            const uint64_t d0 = mkdesc(SM0, 5120, 512, 2);
            mbar_wait(BAR(B_WO0), 0);
#pragma unroll
            for (int s = 1; s < 5; s++) own[s][0] -= tc;
            wg_fence();
#pragma unroll
            for (int s = 0; s < 5; s++) wgmma_rs_n80(ac2, own[s], d0 + (wobuf(0) >> 4) + s * 64, s);
            wg_commit();
            const uint32_t t6 = clock32();
            fz |= t6;
            if (D_O && EARLY_LD >= 5) pause_until(t6, D_O);
            if (EARLY_LD >= 5) ldo(0, ab[0]);
            if (!LATE1) ldo(1, ab[1]);
            mbar_wait(BAR(B_WO), 0);
#pragma unroll
            for (int s = 0; s < 5; s++) {
                uint32_t (*cur)[4] = ab[s % 3];
                if (s == 0) await7<0>(cur, op, fz, sv);
                else {
                    if (s == 1) await7<1>(cur, op, fz, sv); else if (s == 2) await7<2>(cur, op, fz, sv); else if (s == 3) await7<3>(cur, op, fz, sv); else await7<4>(cur, op, fz, sv);
#pragma unroll
                    for (int w = 0; w < 7; w++) cur[w][0] -= tc;
                }
                if (s == 0) { STAMP(7); STAMPT(1, 128); }
                wg_fence();
#pragma unroll
                for (int w = 1; w < 8; w++) wgmma_rs_n80(ac2, cur[w - 1], d0 + (wobuf(w) >> 4) + s * 64, 1);
                wg_commit();
                if (s < 3) { if (s) wg_wait<1>(); else fz |= clock32(); if (s == 0 && LATE1) ldo(1, ab[1]); if (s == 1 && LATE2) ldo(2, ab[2]); if (s || !LATE2) ldo(s + 2, ab[(s + 2) % 3]); }
                if (s == FD_AT && lane == 0) mbar_arrive(BAR(B_G2));
            }
        }
        mbar_wait(BAR(B_EP), 0);
        uint32_t tga[12], tst[12];
        const uint32_t ep = sm + OFF_EP + q * 48;
#pragma unroll
        for (int s = 0; s < 3; s++) { lds4(tga + 4 * s, ep + s * 16); lds4(tst + 4 * s, ep + 768 + min(g, 2) * 192 + s * 16); }
        uint4* const sp0 = pinp(&X->stats[j][tw * 16 + g]);
        const int prow = (ti & 7) * 128 + warp * 16;
        const uint4* const sp = pinp(&X->stats[hi * 4][tw * 16 + (lane & 15)]);
        const int dsrc = PIN((lane & ~3) | (g >> 1));
        wg_wait<0>();
        if (lane == 0) mbar_arrive(BAR(B_G4));
        STAMP(8); STAMPT(23, 128);
        {
            float gA[2][4] = {}, gB[2][4] = {}, sd[4] = {};
#pragma unroll
            for (int s = 0; s < 5; s++) {
#pragma unroll
                for (int e = 0; e < 4; e++) xr[s][e] = hf2(tga[2 * s + (e >> 1)], pack2(ac2[s * 8 + e * 2], ac2[s * 8 + e * 2 + 1]), xr[s][e]);
                mma16(sd, xr[s][0], xr[s][1], xr[s][2], xr[s][3], tst[2 * s], tst[2 * s + 1]);
                mma8(gA[0], xr[s][0], xr[s][1], xr[s][0]); mma8(gB[0], xr[s][0], xr[s][1], xr[s][1]);
                mma8(gA[1], xr[s][2], xr[s][3], xr[s][2]); mma8(gB[1], xr[s][2], xr[s][3], xr[s][3]);
            }
            const float l0 = __shfl_down_sync(~0u, sd[0], 1), l1 = __shfl_down_sync(~0u, sd[2], 1);
            const float q0 = __shfl_sync(~0u, fsel(g & 1, gA[0][1] + gA[1][1], gA[0][0] + gA[1][0]), dsrc), q1 = __shfl_sync(~0u, fsel(g & 1, gB[0][3] + gB[1][3], gB[0][2] + gB[1][2]), dsrc);
            stg4_if(q == 0, sp0, __float_as_uint(sd[0]), __float_as_uint(sd[1] + l0), __float_as_uint(q0), 1u);
            stg4_if(q == 0, sp0 + 8, __float_as_uint(sd[2]), __float_as_uint(sd[3] + l1), __float_as_uint(q1), 1u);
        }
        const uint32_t t9 = clock32();
        STAMP(9);
        uint32_t fg[5][4], fu[5][4], tcb[12], tsb[12];
        uint32_t st[4][4];
        auto ldfg = [&] {
        if (fi < 108) {
            mbar_wait(BAR(B_FG), 0);
#pragma unroll
            for (int s = 0; s < 5; s++) {
                const uint32_t off = sm + OFF_WG + (5 * warp + ((warp & 1) ? (s == 4 ? 0 : s + 1) : s)) * 1024 + frow * 64 + ((fh ^ ((lane >> 1) & 3)) << 4);
                ldsm4t(fg[s], off); ldsm4t(fu[s], off ^ 32);
            }
        }
        };
        if (FGPOS == 0) ldfg();
        if (D_ST) pause_until(t9, D_ST);
#pragma unroll
        for (int e = 0; e < 4; e++) ldg4_rlx(st[e], sp + e * 2056);
        if (FGPOS == 1) ldfg();
        mbar_wait(BAR(B_EP2), 0);
#pragma unroll
        for (int s = 0; s < 3; s++) { lds4(tcb + 4 * s, ep + 192 + s * 16); lds4(tsb + 4 * s, ep + 384 + s * 16); }
        int crow;
        {
            const float2 su = lds2f(sm + OFF_EP + EP_US + 16);
            int gd = 0;
            uint2* const rp = pinp((uint2*)&X->ra[(tw >> 4) * 8 + (lane & 7)][0] + (tw & 15));
            const int tk = PIN(warp == j && lane < 8 ? prow * 2 + (ti >> 3) + 1 : 0);
            float v[3];
            bool bad;
            while (true) {
                bad = __any_sync(~0u, (st[0][3] & st[1][3] & st[2][3] & st[3][3]) == 0);
#pragma unroll
                for (int e = 0; e < 3; e++) {
                    v[e] = (__uint_as_float(st[0][e]) + __uint_as_float(st[1][e])) + (__uint_as_float(st[2][e]) + __uint_as_float(st[3][e]));
                    v[e] += __shfl_xor_sync(~0u, v[e], 16);
                }
                if (!bad || ++gd > SPIN_LIMIT) break;
#pragma unroll
                for (int e = 0; e < 4; e++) ldg4_again(st[e], sp + e * 2056);
            }
            STAMP(10);
            const float m = v[0] * (1.f / 640), rs = rsq(fmaxf(fmaf(v[2], 1.f / 640, 1e-5f) - m * m, 1e-5f));
            const uint32_t key = fkey(fmaf(rs, fmaf(-m, su.x, v[1]), su.y)), kmax = __reduce_max_sync(~0u, key);
            crow = __ffs(__ballot_sync(~0u, key == kmax)) - 1;
            stg2_if(tk, rp, kmax, tk + 2 * crow);
            if (G3E && lane == 0) mbar_arrive(BAR(B_G3));
            const uint32_t rn = pack2(rs, -m * rbf(rs)), a0 = __shfl_sync(~0u, rn, g), a1 = __shfl_sync(~0u, rn, g + 8);
            rr0 = __byte_perm(a0, 0, 0x1010); nn0 = __byte_perm(a0, 0, 0x3232); rr1 = __byte_perm(a1, 0, 0x1010); nn1 = __byte_perm(a1, 0, 0x3232);
        }
        {
            const bool up = crow >= 8;
            const uint32_t rr = up ? rr1 : rr0, nn = up ? nn1 : nn0;
            if (g == (crow & 7)) {
                uint4* cp = &X->cand[j][tw * 20 + q];
#pragma unroll
                for (int s = 0; s < 5; s++) {
                    const uint32_t xa_ = up ? xr[s][1] : xr[s][0], xb_ = up ? xr[s][3] : xr[s][2];
                    stg4_rlx(cp + s * 4, nz(hf2(hf2(xa_, rr, nn), tcb[2 * s], tsb[2 * s])), hf2(hf2(xb_, rr, nn), tcb[2 * s + 1], tsb[2 * s + 1]), xa_, xb_);
                }
            }
        }
        if (!G3E && lane == 0) mbar_arrive(BAR(B_G3));
        STAMP(11);
        const uint32_t stg = sm + 5 * WST + warp * 2560;
        {
            mbar_wait(BAR(B_EP3), 0);
#pragma unroll
            for (int s = 0; s < 3; s++) lds4(tga + 4 * s, ep + 576 + s * 16);
#pragma unroll
            for (int s = 0; s < 5; s++) {
#pragma unroll
                for (int e = 0; e < 4; e++) { const int t = 2 * s + (e >> 1); xr[s][e] = hf2(tga[t], hf2(hf2(xr[s][e], (e & 1) ? rr1 : rr0, (e & 1) ? nn1 : nn0), tcb[t], tsb[t]), xr[s][e]); }
            }
            mbar_wait(BAR(B_G4), 0);
#pragma unroll
            for (int s = 0; s < 5; s++) stsm4(stg + (lane & 15) * 160 + (odd ? (s == 4 ? 0 : s + 1) : s) * 32 + hi * 16, xr[s]);
            asm volatile("fence.proxy.async.shared::cta;" ::: "memory");
            __syncwarp();
            if (OUTPOS == 0 && elect1()) tma3d_st(&mout, 80 * j, ti >> 3, prow + (~crow & 8), stg + (~crow & 8) * 160);
        }
        STAMP(12);
        const char* cp = (const char*)pinp(&X->cand[warp][q]);
        uint32_t* const ap0 = pinp((uint32_t*)&X->ra[fi >> 1][8 + (fi & 1) * 4] + (lane & 8) + (lane & 3) * 2 + ((lane >> 2) & 1));
        const uint32_t rw = PIN(sm + OFF_RED - 256 + (q * 4 + (g >> 1)) * 80 + warp * 8 + (g & 1) * 4), rd = PIN(sm + OFF_RED - 256 + (lane & 15) * 80);
        if (smem_u32(sm_raw) != sm) return;
        mbar_wait(BAR(B_WIN), 0);
        uint32_t wv[4]; int gd = 0;
        lds4(wv, sm + OFF_EP + EP_US + 32);
        const uint32_t kwin = wv[0];
        const int tokwin = wv[1], win = wv[2];
        auto out2 = [&] {
            if (OUTPOS == 1 && elect1()) tma3d_st(&mout, 80 * j, ti >> 3, prow + (~crow & 8), stg + (~crow & 8) * 160);
            if (win != tw) {
                if (elect1()) tma3d_st(&mout, 80 * j, ti >> 3, prow + (crow & 8), stg + (crow & 8) * 160);
            } else {
#pragma unroll 1
                for (int r = crow & 8; r <= (crow | 7); r++)
                    if (r != crow && lane < 20) { uint32_t v[2]; lds2(v, stg + r * 160 + lane * 8); *(uint2*)(out + (size_t)((prow + r) * 2 + (ti >> 3)) * 640 + 80 * j + lane * 4) = make_uint2(v[0], v[1]); }
            }
        };
        const uint32_t t13 = clock32();
        STAMP(13);
        if (OUTPOS2 == 0) out2();
        if (fi < 108) {
            uint32_t hb[5][2];
            float mine;
            bool bad;
            cp += wv[3];
            do {
#pragma unroll
                for (int s = 0; s < 5; s++) ldg2_rlx(hb[s], cp + s * 64);
                bad = __any_sync(~0u, min(min(min(hb[0][0], hb[1][0]), min(hb[2][0], hb[3][0])), hb[4][0]) == 0);
                float dg[2][4] = {}, du[2][4] = {};
#pragma unroll
                for (int s = 0; s < 5; s++) {
                    mma16(dg[s & 1], fg[s][0], fg[s][1], fg[s][2], fg[s][3], hb[s][0], hb[s][1]);
                    mma16(du[s & 1], fu[s][0], fu[s][1], fu[s][2], fu[s][3], hb[s][0], hb[s][1]);
                }
                mine = fsel(q & 2, fsel(q & 1, du[1][2], du[1][0]), fsel(q & 1, dg[1][2], dg[1][0])) + fsel(q & 2, fsel(q & 1, du[0][2], du[0][0]), fsel(q & 1, dg[0][2], dg[0][0]));
                sts1f(rw, mine);
                gd++;
            } while (bad && gd < SPIN_LIMIT);
            bar_sync(2, 256);
            if (warp == 0) {
                uint32_t v[4][4];
#pragma unroll
                for (int e = 0; e < 4; e++) lds4(v[e], rd + e * 16);
                float t[2];
#pragma unroll
                for (int e = 0; e < 2; e++)
                    t[e] = ((__uint_as_float(v[0][e]) + __uint_as_float(v[0][e + 2])) + (__uint_as_float(v[1][e]) + __uint_as_float(v[1][e + 2]))) +
                           ((__uint_as_float(v[2][e]) + __uint_as_float(v[2][e + 2])) + (__uint_as_float(v[3][e]) + __uint_as_float(v[3][e + 2])));
                uint32_t pr = pack2(t[0], t[1]);
                if (!(fi & 1)) pr = pack2(blo(pr) * sigm(blo(pr)), bhi(pr) * sigm(bhi(pr)));
                stg1_if(lane < 16, ap0, nz(pr));
            }
        }
        STAMP(14);
        if (OUTPOS2 == 1) { if (ODLY && fi < 88) pause(ODLY); out2(); }
        if (fi >= 88) {
            const int d = fi - 88, dj = d / 5, dm = d - dj * 5, sp = (dj & 1) ? (dm == 0 ? 4 : dm - 1) : dm;
            const int ks0 = min(warp * 14, 94);
            const uint32_t frag = frow * 32 + ((fh ^ ((lane >> 2) & 1)) << 4);
            uint32_t fd[14][4];
            mbar_wait(BAR(B_FD), 0);
#pragma unroll
            for (int s = 0; s < 14; s++) ldsm4t(fd[s], sm + OFF_WD + (ks0 + s) * 512 + frag);
            const float sf = sigm(rbf(__uint_as_float((kwin & 0x80000000u) ? kwin & 0x7fffffffu : ~kwin)));
            const uint32_t sg = PIN(pack2(sf, sf));
            const uint32_t gbd = lds1(sm + OFF_EP + EP_GD + (lane & 7) * 4);
            uint32_t* const op = (uint32_t*)(out + (size_t)tokwin * 640 + d * 16) + (lane & 7);
            uint32_t bsv[4], ag[4], au[4];
            const uint4* ap = &X->ra[(ks0 >> 1) + min(g, 6)][8 + q];
            const uint32_t keep = warp == 7 && g < 2 ? 0u : ~0u;
            const uint32_t as = PIN(sm + 7 * WST + warp * 512 + q * 16), aw = PIN(sm + 7 * WST + warp * 512 + g * 64 + (q & 1) * 32 + (q >> 1) * 8);
            const uint32_t yw = PIN(sm + OFF_TAB + ((q & 1) * 4 + (g >> 1)) * 80 + warp * 8 + (g & 1) * 4), yr = PIN(sm + OFF_TAB + (lane & 7) * 80);
            bool bad;
            if (D_A) pause_until(t13, D_A);
            do {
                pause(P_A);
                ldg4_rlx(ag, ap); ldg4_rlx(au, ap + 4); ldg4_rlx(bsv, &X->cand[dj][win * 20 + sp * 4 + q]);
                bad = __any_sync(~0u, min(min(min(min(ag[0], ag[1]), min(ag[2], ag[3])), min(min(au[0], au[1]), min(au[2], au[3]))), bsv[0]) == 0);
                sts2(aw, hm2(ag[0], au[0]) & keep, hm2(ag[1], au[1]) & keep); sts2(aw + 16, hm2(ag[2], au[2]) & keep, hm2(ag[3], au[3]) & keep);
                gd++;
            } while (bad && gd < SPIN_LIMIT);
            STAMP(15);
            __syncwarp();
            float dy[4][4] = {};
            uint32_t av[7][4];
#pragma unroll
            for (int s = 0; s < 7; s++) lds4(av[s], as + s * 64);
#pragma unroll
            for (int s = 0; s < 7; s++) {
                mma16(dy[(2 * s) & 3], fd[2 * s][0], fd[2 * s][1], fd[2 * s][2], fd[2 * s][3], av[s][0], av[s][1]);
                mma16(dy[(2 * s + 1) & 3], fd[2 * s + 1][0], fd[2 * s + 1][1], fd[2 * s + 1][2], fd[2 * s + 1][3], av[s][2], av[s][3]);
            }
            sts1f(yw, (fsel(q & 1, dy[2][2], dy[2][0]) + fsel(q & 1, dy[3][2], dy[3][0])) + (fsel(q & 1, dy[0][2], dy[0][0]) + fsel(q & 1, dy[1][2], dy[1][0])));
            bar_sync(2, 256);
            if (warp == 0) {
                uint32_t v[4][4];
#pragma unroll
                for (int e = 0; e < 4; e++) lds4(v[e], yr + e * 16);
                float t[2];
#pragma unroll
                for (int e = 0; e < 2; e++)
                    t[e] = ((__uint_as_float(v[0][e]) + __uint_as_float(v[0][e + 2])) + (__uint_as_float(v[1][e]) + __uint_as_float(v[1][e + 2]))) +
                           ((__uint_as_float(v[2][e]) + __uint_as_float(v[2][e + 2])) + (__uint_as_float(v[3][e]) + __uint_as_float(v[3][e + 2])));
                const uint32_t hh = (lane & 4) ? bsv[1] : bsv[0], xx = (lane & 4) ? bsv[3] : bsv[2];
                if (lane < 8) *op = hf2(gbd, hf2(hm2(pack2(t[0], t[1]), sg), 0x3f803f80u, hh), xx);
            }
        }
        asm volatile("cp.async.bulk.commit_group;\ncp.async.bulk.wait_group.read 0;" ::: "memory");
        STAMP(16);
    }
}

typedef CUresult (*EncFn)(CUtensorMap*, CUtensorMapDataType, cuuint32_t, void*, const cuuint64_t*, const cuuint64_t*, const cuuint32_t*, const cuuint32_t*,
                          CUtensorMapInterleave, CUtensorMapSwizzle, CUtensorMapL2promotion, CUtensorMapFloatOOBfill);
static void make_map(EncFn enc, CUtensorMap* m, const void* base, int rank, const cuuint64_t* dims, const cuuint64_t* strides, const cuuint32_t* box, CUtensorMapSwizzle sw) {
    const cuuint32_t es[5] = {1, 1, 1, 1, 1};
    enc(m, CU_TENSOR_MAP_DATA_TYPE_BFLOAT16, rank, (void*)base, dims, strides, box, es, CU_TENSOR_MAP_INTERLEAVE_NONE, sw, CU_TENSOR_MAP_L2_PROMOTION_NONE, CU_TENSOR_MAP_FLOAT_OOB_FILL_NONE);
}

extern "C" void kernel_launch(void* const* d_in, const int* in_sizes, int n_in, void* d_out, int out_size) {
    typedef const __nv_bfloat16* P;
    P x = (P)d_in[0], wqkv = (P)d_in[1], wo = (P)d_in[2], wr = (P)d_in[4], wg = (P)d_in[5], wu = (P)d_in[6], wd = (P)d_in[7], c = (P)d_in[8], wmod = (P)d_in[9];
    void* fn = nullptr; cudaDriverEntryPointQueryResult qr;
    cudaGetDriverEntryPoint("cuTensorMapEncodeTiled", &fn, cudaEnableDefault, &qr);
    EncFn enc = (EncFn)fn;
    CUtensorMap mx, mw, mt, mo, mg, mu, md, mm, mw2, mout, mo2;
    { cuuint64_t d[] = {640, 2, 1024}, s[] = {1280, 2560}; cuuint32_t b[] = {64, 1, 128}; make_map(enc, &mx, x, 3, d, s, b, CU_TENSOR_MAP_SWIZZLE_128B); }
    { cuuint64_t d[] = {32, 640, 20, 3}, s[] = {3840, 64, 1280}; cuuint32_t b[] = {32, 16, 2, 3}; make_map(enc, &mw, wqkv, 4, d, s, b, CU_TENSOR_MAP_SWIZZLE_64B); }
    { cuuint64_t d[] = {640, 640, 3}, s[] = {3840, 1280}; cuuint32_t b[] = {16, 16, 3}; make_map(enc, &mt, wqkv, 3, d, s, b, CU_TENSOR_MAP_SWIZZLE_32B); }
    { cuuint64_t d[] = {640, 640}, s[] = {1280}; cuuint32_t b[] = {32, 40}; make_map(enc, &mo, wo, 2, d, s, b, CU_TENSOR_MAP_SWIZZLE_64B);
      b[0] = 16; make_map(enc, &mo2, wo, 2, d, s, b, CU_TENSOR_MAP_SWIZZLE_64B); }
    { cuuint64_t d[] = {1728, 640}, s[] = {3456}; cuuint32_t b[] = {32, 160}; make_map(enc, &mg, wg, 2, d, s, b, CU_TENSOR_MAP_SWIZZLE_64B); make_map(enc, &mu, wu, 2, d, s, b, CU_TENSOR_MAP_SWIZZLE_64B); }
    { cuuint64_t d[] = {640, 216, 8}, s[] = {1280, 1280 * 216}; cuuint32_t b[] = {16, 216, 8}; make_map(enc, &md, wd, 3, d, s, b, CU_TENSOR_MAP_SWIZZLE_32B); }
    { cuuint64_t d[] = {3840, 640}, s[] = {7680}; cuuint32_t b[] = {64, 80}; make_map(enc, &mm, wmod, 2, d, s, b, CU_TENSOR_MAP_SWIZZLE_128B); }
    { cuuint64_t d[] = {64, 640, 10, 3}, s[] = {3840, 128, 1280}; cuuint32_t b[] = {64, 16, 1, 3}; make_map(enc, &mw2, wqkv, 4, d, s, b, CU_TENSOR_MAP_SWIZZLE_128B); }
    { cuuint64_t d[] = {640, 2, 1024}, s[] = {1280, 2560}; cuuint32_t b[] = {80, 1, 8}; make_map(enc, &mout, d_out, 3, d, s, b, CU_TENSOR_MAP_SWIZZLE_NONE); }
    void* sp = nullptr;
    cudaGetSymbolAddress(&sp, g_s);
    cudaFuncSetAttribute(fused_kernel, cudaFuncAttributeMaxDynamicSharedMemorySize, SMEM_BYTES);
    fused_kernel<<<132, 384, SMEM_BYTES>>>(x, wmod, c, (Scratch*)sp, wqkv, wo, (__nv_bfloat16*)d_out, wr, wg, wu, wd, mm, mx, mw, mt, mo, mg, mu, md, mw2, mout, mo2);
}
```

```cpp
#include <cuda_runtime.h>
#include <cuda_bf16.h>
#include <cuda.h>
#include <stdint.h>

#define SPIN_LIMIT (1 << 17)

constexpr int RV = 704;
struct __align__(4096) Exch {
    uint4 o[5 * 128 * 256];
    uint4 halo[112 * 160];
    uint4 stats[8][2056];
    uint4 cand[8][128 * 20 + 8];
    uint4 ra[64][24];
    uint4 pad[128 * RV - (128 * 256 + 112 * 160 + 8 * 2056 + 8 * (128 * 20 + 8) + 64 * 24)];
};
struct __align__(4096) Scratch {
    Exch x;
    uint4 tab[60][72];
    unsigned cnt;
};
__device__ Scratch g_s;
#define STAMP(n)
#define GSTAMP(n)
#define STAMPT(n, t)

constexpr uint32_t OFF_W = 163840, WST = 15360;
constexpr uint32_t OFF_WM = OFF_W + 2 * WST;
constexpr uint32_t OFF_FF = OFF_WM + 20480;
constexpr uint32_t OFF_P8 = 131072, VP = 176;
constexpr uint32_t OFF_WD = 129024, OFF_WG = 184320;
constexpr uint32_t OFF_TAB = 225280;
constexpr uint32_t OFF_RED = OFF_TAB + 2560;
constexpr uint32_t OFF_EP = OFF_TAB + 4096;
constexpr uint32_t EP_GD = 1344, EP_US = 1376;
constexpr uint32_t OFF_BAR = OFF_EP + 1488;
constexpr uint32_t OFF_PROF = OFF_BAR + 640;
constexpr uint32_t SMEM_BYTES = OFF_PROF + 128;
enum { B_XF = 0, B_WF = 10, B_WO0 = 30, B_WO, B_FG, B_FD, B_TB, B_HL = B_TB + 4, B_G0 = B_HL + 8, B_RDY, B_WIN, B_EP, B_EP2, B_EP3, B_G2, B_G3, B_G4, B_WE = 55, B_T0 = B_WE + 19 };
#define CPF 32
#define D_ST 400
#define D_REC 300
#define D_O 300
#define D_H 300
#define WO_MASK 0x1f5000
#define P_TAB 100
#define LAG 2
#define XWAIT 2
#define FD_AT 2
#define GU_MASK 0xaa00
#define TB_GO B_HL
#define TB_GO2 B_G2
#define TDELAY 3700
#define PFN 5
#define PF0 1
#define YSLEEP 300
#define MPF0 6
#define XDELAY 600
#define RSLEEP 40
#define HALO_GO B_G0
constexpr uint32_t SM0 = 1024;
#define BAR0(i) (SM0 + OFF_BAR + 8 * (i))
#define BAR(i) (sm + OFF_BAR + 8 * (i))

__device__ __forceinline__ uint32_t smem_u32(const void* p) { return (uint32_t)__cvta_generic_to_shared(p); }
__device__ __forceinline__ void mbar_init(uint32_t b, int cnt) { asm volatile("mbarrier.init.shared::cta.b64 [%0], %1;" ::"r"(b), "r"(cnt) : "memory"); }
__device__ __forceinline__ void mbar_expect_tx(uint32_t b, uint32_t bytes) { asm volatile("mbarrier.arrive.expect_tx.shared::cta.b64 _, [%0], %1;" ::"r"(b), "r"(bytes) : "memory"); }
__device__ __forceinline__ void mbar_arrive(uint32_t b) { asm volatile("mbarrier.arrive.shared::cta.b64 _, [%0];" ::"r"(b) : "memory"); }
__device__ __forceinline__ bool mbar_try(uint32_t b, uint32_t par) {
    uint32_t ok;
    asm volatile("{.reg .pred p; mbarrier.try_wait.parity.shared::cta.b64 p, [%1], %2; selp.u32 %0, 1, 0, p;}" : "=r"(ok) : "r"(b), "r"(par) : "memory");
    return ok;
}
__device__ __forceinline__ void mbar_wait(uint32_t b, uint32_t par) {
    asm volatile("{.reg .pred p;\nW: mbarrier.try_wait.parity.shared::cta.b64 p, [%0], %1;\n@!p bra W;}" ::"r"(b), "r"(par) : "memory");
}
__device__ __forceinline__ void bar_sync(int id, int n) { asm volatile("bar.sync %0, %1;" ::"r"(id), "r"(n) : "memory"); }
__device__ __forceinline__ void tma2d(uint32_t dst, const CUtensorMap* m, int c0, int c1, uint32_t bar) {
    asm volatile("cp.async.bulk.tensor.2d.shared::cluster.global.mbarrier::complete_tx::bytes [%0], [%1, {%3, %4}], [%2];" ::"r"(dst), "l"(m), "r"(bar), "r"(c0), "r"(c1) : "memory");
}
__device__ __forceinline__ void tma3d(uint32_t dst, const CUtensorMap* m, int c0, int c1, int c2, uint32_t bar) {
    asm volatile("cp.async.bulk.tensor.3d.shared::cluster.global.mbarrier::complete_tx::bytes [%0], [%1, {%3, %4, %5}], [%2];" ::"r"(dst), "l"(m), "r"(bar), "r"(c0), "r"(c1), "r"(c2) : "memory");
}
__device__ __forceinline__ void l2_prefetch(const void* p, uint32_t bytes) { asm volatile("cp.async.bulk.prefetch.L2.global [%0], %1;" ::"l"(p), "r"(bytes) : "memory"); }
__device__ __forceinline__ void wg_fence() { asm volatile("wgmma.fence.sync.aligned;" ::: "memory"); }
__device__ __forceinline__ void wg_commit() { asm volatile("wgmma.commit_group.sync.aligned;" ::: "memory"); }
template <int N> __device__ __forceinline__ void wg_wait() { asm volatile("wgmma.wait_group.sync.aligned %0;" ::"n"(N) : "memory"); }
__device__ __forceinline__ void ldsm4(uint32_t* r, uint32_t addr) { asm volatile("ldmatrix.sync.aligned.m8n8.x4.shared.b16 {%0,%1,%2,%3}, [%4];" : "=r"(r[0]), "=r"(r[1]), "=r"(r[2]), "=r"(r[3]) : "r"(addr) : "memory"); }
__device__ __forceinline__ void ldsm4t(uint32_t* r, uint32_t addr) { asm volatile("ldmatrix.sync.aligned.m8n8.x4.trans.shared.b16 {%0,%1,%2,%3}, [%4];" : "=r"(r[0]), "=r"(r[1]), "=r"(r[2]), "=r"(r[3]) : "r"(addr) : "memory"); }
__device__ __forceinline__ void stsm4(uint32_t addr, const uint32_t* r) { asm volatile("stmatrix.sync.aligned.m8n8.x4.shared.b16 [%4], {%0,%1,%2,%3};" ::"r"(r[0]), "r"(r[1]), "r"(r[2]), "r"(r[3]), "r"(addr) : "memory"); }
__device__ __forceinline__ void lds4(uint32_t* r, uint32_t addr) { asm volatile("ld.shared.v4.u32 {%0,%1,%2,%3}, [%4];" : "=r"(r[0]), "=r"(r[1]), "=r"(r[2]), "=r"(r[3]) : "r"(addr) : "memory"); }
__device__ __forceinline__ void sts4(uint32_t addr, const uint32_t* r) { asm volatile("st.shared.v4.u32 [%4], {%0,%1,%2,%3};" ::"r"(r[0]), "r"(r[1]), "r"(r[2]), "r"(r[3]), "r"(addr) : "memory"); }
__device__ __forceinline__ float2 lds2f(uint32_t addr) { float2 v; asm volatile("ld.shared.v2.f32 {%0,%1}, [%2];" : "=f"(v.x), "=f"(v.y) : "r"(addr) : "memory"); return v; }
__device__ __forceinline__ void sts1f(uint32_t addr, float v) { asm volatile("st.shared.f32 [%0], %1;" ::"r"(addr), "f"(v) : "memory"); }
__device__ __forceinline__ void sts1(uint32_t addr, uint32_t v) { asm volatile("st.shared.u32 [%0], %1;" ::"r"(addr), "r"(v) : "memory"); }
__device__ __forceinline__ void ldg4_rlx(uint32_t* r, const void* p) { asm volatile("{.reg .b128 t; ld.relaxed.gpu.global.b128 t, [%4]; mov.b128 {%0,%1,%2,%3}, t;}" : "=r"(r[0]), "=r"(r[1]), "=r"(r[2]), "=r"(r[3]) : "l"(p) : "memory"); }
__device__ __forceinline__ void ldg2_rlx(uint32_t* r, const void* p) { asm volatile("{.reg .b64 t; ld.relaxed.gpu.global.b64 t, [%2]; mov.b64 {%0,%1}, t;}" : "=r"(r[0]), "=r"(r[1]) : "l"(p) : "memory"); }
__device__ __forceinline__ uint32_t ldg1_rlx(const void* p) { uint32_t v; asm volatile("ld.relaxed.gpu.global.u32 %0, [%1];" : "=r"(v) : "l"(p) : "memory"); return v; }
__device__ __forceinline__ void stg4_rlx(void* p, uint32_t a, uint32_t b, uint32_t c, uint32_t d) { asm volatile("{.reg .b128 t; mov.b128 t, {%1,%2,%3,%4}; st.relaxed.gpu.global.b128 [%0], t;}" ::"l"(p), "r"(a), "r"(b), "r"(c), "r"(d) : "memory"); }
__device__ __forceinline__ void stg1_rlx(void* p, uint32_t a) { asm volatile("st.relaxed.gpu.global.u32 [%0], %1;" ::"l"(p), "r"(a) : "memory"); }
__device__ __forceinline__ uint64_t mkdesc(uint32_t addr, uint32_t lbo, uint32_t sbo, uint32_t sw) { return (uint64_t)((addr & 0x3FFFF) >> 4) | ((uint64_t)(lbo >> 4) << 16) | ((uint64_t)(sbo >> 4) << 32) | ((uint64_t)sw << 62); }
__device__ __forceinline__ uint32_t pack2(float lo, float hi) { uint32_t r; asm("cvt.rn.bf16x2.f32 %0, %1, %2;" : "=r"(r) : "f"(hi), "f"(lo)); return r; }
__device__ __forceinline__ float blo(uint32_t v) { return __uint_as_float(v << 16); }
__device__ __forceinline__ float bhi(uint32_t v) { return __uint_as_float(v & 0xffff0000u); }
__device__ __forceinline__ float rbf(float x) { return blo(pack2(x, 0.f)); }
__device__ __forceinline__ uint32_t hf2(uint32_t a, uint32_t b, uint32_t c) { uint32_t r; asm("fma.rn.bf16x2 %0, %1, %2, %3;" : "=r"(r) : "r"(a), "r"(b), "r"(c)); return r; }
__device__ __forceinline__ float ex2(float x) { float r; asm("ex2.approx.ftz.f32 %0, %1;" : "=f"(r) : "f"(x)); return r; }
__device__ __forceinline__ void mma16(float* d, uint32_t a0, uint32_t a1, uint32_t a2, uint32_t a3, uint32_t b0, uint32_t b1) {
    asm("mma.sync.aligned.m16n8k16.row.col.f32.bf16.bf16.f32 {%0,%1,%2,%3}, {%4,%5,%6,%7}, {%8,%9}, {%0,%1,%2,%3};"
                 : "+f"(d[0]), "+f"(d[1]), "+f"(d[2]), "+f"(d[3]) : "r"(a0), "r"(a1), "r"(a2), "r"(a3), "r"(b0), "r"(b1));
}
__device__ __forceinline__ void mma8(float* d, uint32_t a0, uint32_t a1, uint32_t b0) {
    asm("mma.sync.aligned.m16n8k8.row.col.f32.bf16.bf16.f32 {%0,%1,%2,%3}, {%4,%5}, {%6}, {%0,%1,%2,%3};"
                 : "+f"(d[0]), "+f"(d[1]), "+f"(d[2]), "+f"(d[3]) : "r"(a0), "r"(a1), "r"(b0));
}
__device__ __forceinline__ uint32_t fkey(float f) { const uint32_t u = __float_as_uint(f); return u ^ (((int)u >> 31) | 0x80000000u); }
__device__ __forceinline__ float rcp(float x) { float r; asm("rcp.approx.ftz.f32 %0, %1;" : "=f"(r) : "f"(x)); return r; }
__device__ __forceinline__ float sigm(float x) { return rcp(1.f + ex2(x * -1.4426950408889634f)); }
__device__ __forceinline__ void mma16c(float* d, uint32_t a0, uint32_t a1, uint32_t a2, uint32_t a3, uint32_t b0, uint32_t b1, float c0, float c1) {
    asm("mma.sync.aligned.m16n8k16.row.col.f32.bf16.bf16.f32 {%0,%1,%2,%3}, {%4,%5,%6,%7}, {%8,%9}, {%10,%11,%12,%12};"
                 : "=f"(d[0]), "=f"(d[1]), "=f"(d[2]), "=f"(d[3]) : "r"(a0), "r"(a1), "r"(a2), "r"(a3), "r"(b0), "r"(b1), "f"(c0), "f"(c1), "f"(0.f));
}
__device__ __forceinline__ void stsm2(uint32_t addr, uint32_t a, uint32_t b) { asm volatile("stmatrix.sync.aligned.m8n8.x2.shared.b16 [%2], {%0,%1};" ::"r"(a), "r"(b), "r"(addr) : "memory"); }
__device__ __forceinline__ void lds2(uint32_t* r, uint32_t addr) { asm volatile("ld.shared.v2.u32 {%0,%1}, [%2];" : "=r"(r[0]), "=r"(r[1]) : "r"(addr) : "memory"); }
__device__ __forceinline__ void sts2(uint32_t addr, uint32_t a, uint32_t b) { asm volatile("st.shared.v2.u32 [%2], {%0,%1};" ::"r"(a), "r"(b), "r"(addr) : "memory"); }
__device__ __forceinline__ uint32_t lds1(uint32_t addr) { uint32_t v; asm volatile("ld.shared.u32 %0, [%1];" : "=r"(v) : "r"(addr) : "memory"); return v; }
__device__ __forceinline__ bool elect1() { uint32_t p; asm volatile("{.reg .pred P; elect.sync _|P, 0xffffffff; selp.u32 %0, 1, 0, P;}" : "=r"(p)); return p; }
__device__ __forceinline__ void tma2d_mc(uint32_t dst, const CUtensorMap* m, int c0, int c1, uint32_t bar) {
    asm volatile("cp.async.bulk.tensor.2d.shared::cluster.global.mbarrier::complete_tx::bytes.multicast::cluster [%0], [%1, {%3, %4}], [%2], %5;" ::"r"(dst), "l"(m), "r"(bar), "r"(c0), "r"(c1), "h"((unsigned short)3) : "memory");
}
__device__ __forceinline__ void tma3d_mc(uint32_t dst, const CUtensorMap* m, int c0, int c1, int c2, uint32_t bar) {
    asm volatile("cp.async.bulk.tensor.3d.shared::cluster.global.mbarrier::complete_tx::bytes.multicast::cluster [%0], [%1, {%3, %4, %5}], [%2], %6;" ::"r"(dst), "l"(m), "r"(bar), "r"(c0), "r"(c1), "r"(c2), "h"((unsigned short)3) : "memory");
}
__device__ __forceinline__ void tma4d_mc(uint32_t dst, const CUtensorMap* m, int c0, int c1, int c2, int c3, uint32_t bar) {
    asm volatile("cp.async.bulk.tensor.4d.shared::cluster.global.mbarrier::complete_tx::bytes.multicast::cluster [%0], [%1, {%3, %4, %5, %6}], [%2], %7;" ::"r"(dst), "l"(m), "r"(bar), "r"(c0), "r"(c1), "r"(c2), "r"(c3), "h"((unsigned short)3) : "memory");
}
__device__ __forceinline__ void mbar_arrive_cl(uint32_t b) { asm volatile("mbarrier.arrive.shared::cluster.b64 _, [%0];" ::"r"(b) : "memory"); }
__device__ __forceinline__ uint32_t hm2(uint32_t a, uint32_t b) { uint32_t r; asm("mul.rn.bf16x2 %0, %1, %2;" : "=r"(r) : "r"(a), "r"(b)); return r; }
__device__ __forceinline__ uint32_t clock32() { uint32_t c; asm volatile("mov.u32 %0, %clock;" : "=r"(c)); return c; }
__device__ __forceinline__ float rsq(float x) { float r; asm("rsqrt.approx.ftz.f32 %0, %1;" : "=f"(r) : "f"(x)); return r; }
__device__ __forceinline__ void pause_until(uint32_t t0, uint32_t n) {
    asm volatile("{.reg .pred p; .reg .u32 t;\nP: mov.u32 t, %clock; sub.u32 t, t, %0; setp.lt.u32 p, t, %1;\n@p bra.uni P;}" ::"r"(t0), "r"(n) : "memory");
}
__device__ __forceinline__ void pause(uint32_t n) { if (n) { const uint32_t t = clock32(); while (clock32() - t < n) {} } }
__device__ __forceinline__ uint32_t wbuf(int it) {
    const uint32_t v = it < 4 ? it + 8 : (uint32_t)(0x8302418302b1a908ull >> (4 * it - 16)) & 15;
    return v * WST + (v >> 3) * (OFF_W - 8 * WST);
}
__device__ __forceinline__ uint32_t wobuf(int w) { return ((0x30241765u >> (4 * w)) & 7) * WST; }
__device__ __forceinline__ uint32_t inc(uint32_t v) { uint32_t r; asm volatile("{.reg .u32 t; or.b32 t, %1, 255; add.u32 %0, t, 1;}" : "=r"(r) : "r"(v)); return r; }
__device__ __forceinline__ uint32_t ldg1_acq(const void* p) { uint32_t v; asm volatile("ld.acquire.gpu.global.u32 %0, [%1];" : "=r"(v) : "l"(p) : "memory"); return v; }
__device__ __forceinline__ void tma3d_st(const CUtensorMap* m, int c0, int c1, int c2, uint32_t src) {
    asm volatile("cp.async.bulk.tensor.3d.global.shared::cta.bulk_group [%0, {%2, %3, %4}], [%1];" ::"l"(m), "r"(src), "r"(c0), "r"(c1), "r"(c2) : "memory");
}
__device__ __forceinline__ uint32_t nz(uint32_t v) { uint32_t r; asm("max.u32 %0, %1, 1;" : "=r"(r) : "r"(v)); return r; }
__device__ __forceinline__ uint32_t tagw(uint32_t w, uint32_t tc) { return ((w & 0x8000ffffu) | min(max(w & 0x7fff0000u, 0x20000000u), 0x5fff0000u)) + tc; }
template <int S_> __device__ __forceinline__ void await7(uint32_t (*r)[4], const char* const* p, uint32_t fz, uint32_t stale) {
    if (S_ == 0) asm volatile("{.reg .b128 t; .reg .pred p; .reg .u32 m, k, n;\nmov.u32 n, %clock; or.b32 n, n, %37; shr.u32 n, n, 31;\nL:\n"
        "min.u32 m, %0, %4; min.u32 m, m, %8; min.u32 m, m, %12; min.u32 m, m, %16; min.u32 m, m, %20; min.u32 m, m, %24;\n"
        "setp.eq.u32 p, m, 0; vote.sync.any.pred p, p, 0xffffffff; add.u32 n, n, 1; setp.lt.and.u32 p, n, %36, p;\n@!p bra.uni D;\n"
        "setp.eq.u32 p, %0, 0; mov.b128 t, {%0,%1,%2,%3}; @p ld.relaxed.gpu.global.b128 t, [%28+%35]; mov.b128 {%0,%1,%2,%3}, t;\n"
        "setp.eq.u32 p, %4, 0; mov.b128 t, {%4,%5,%6,%7}; @p ld.relaxed.gpu.global.b128 t, [%29+%35]; mov.b128 {%4,%5,%6,%7}, t;\n"
        "setp.eq.u32 p, %8, 0; mov.b128 t, {%8,%9,%10,%11}; @p ld.relaxed.gpu.global.b128 t, [%30+%35]; mov.b128 {%8,%9,%10,%11}, t;\n"
        "setp.eq.u32 p, %12, 0; mov.b128 t, {%12,%13,%14,%15}; @p ld.relaxed.gpu.global.b128 t, [%31+%35]; mov.b128 {%12,%13,%14,%15}, t;\n"
        "setp.eq.u32 p, %16, 0; mov.b128 t, {%16,%17,%18,%19}; @p ld.relaxed.gpu.global.b128 t, [%32+%35]; mov.b128 {%16,%17,%18,%19}, t;\n"
        "setp.eq.u32 p, %20, 0; mov.b128 t, {%20,%21,%22,%23}; @p ld.relaxed.gpu.global.b128 t, [%33+%35]; mov.b128 {%20,%21,%22,%23}, t;\n"
        "setp.eq.u32 p, %24, 0; mov.b128 t, {%24,%25,%26,%27}; @p ld.relaxed.gpu.global.b128 t, [%34+%35]; mov.b128 {%24,%25,%26,%27}, t;\n"
        "bra.uni L;\nD:}"
        : "+r"(r[0][0]), "+r"(r[0][1]), "+r"(r[0][2]), "+r"(r[0][3]), "+r"(r[1][0]), "+r"(r[1][1]), "+r"(r[1][2]), "+r"(r[1][3]), "+r"(r[2][0]), "+r"(r[2][1]), "+r"(r[2][2]), "+r"(r[2][3]), "+r"(r[3][0]), "+r"(r[3][1]), "+r"(r[3][2]), "+r"(r[3][3]), "+r"(r[4][0]), "+r"(r[4][1]), "+r"(r[4][2]), "+r"(r[4][3]), "+r"(r[5][0]), "+r"(r[5][1]), "+r"(r[5][2]), "+r"(r[5][3]), "+r"(r[6][0]), "+r"(r[6][1]), "+r"(r[6][2]), "+r"(r[6][3])
        : "l"(p[0]), "l"(p[1]), "l"(p[2]), "l"(p[3]), "l"(p[4]), "l"(p[5]), "l"(p[6]), "n"((4 - S_) * 524288), "n"(SPIN_LIMIT), "r"(fz), "r"(stale) : "memory");
    else asm volatile("{.reg .b128 t; .reg .pred p; .reg .u32 m, k, n;\nmov.u32 n, %clock; or.b32 n, n, %37; shr.u32 n, n, 31;\nL:\n"
        "xor.b32 m, %0, %38; xor.b32 k, %4, %38; and.b32 m, m, k; xor.b32 k, %8, %38; and.b32 m, m, k; xor.b32 k, %12, %38; and.b32 m, m, k; xor.b32 k, %16, %38; and.b32 m, m, k;\n"
        "xor.b32 k, %20, %38; and.b32 m, m, k; xor.b32 k, %24, %38; and.b32 m, m, k; and.b32 m, m, 0x40000000;\n"
        "setp.eq.u32 p, m, 0; vote.sync.any.pred p, p, 0xffffffff; add.u32 n, n, 1; setp.lt.and.u32 p, n, %36, p;\n@!p bra.uni D;\n"
        "xor.b32 k, %0, %38; and.b32 k, k, 0x40000000; setp.eq.u32 p, k, 0; mov.b128 t, {%0,%1,%2,%3}; @p ld.relaxed.gpu.global.b128 t, [%28+%35]; mov.b128 {%0,%1,%2,%3}, t;\n"
        "xor.b32 k, %4, %38; and.b32 k, k, 0x40000000; setp.eq.u32 p, k, 0; mov.b128 t, {%4,%5,%6,%7}; @p ld.relaxed.gpu.global.b128 t, [%29+%35]; mov.b128 {%4,%5,%6,%7}, t;\n"
        "xor.b32 k, %8, %38; and.b32 k, k, 0x40000000; setp.eq.u32 p, k, 0; mov.b128 t, {%8,%9,%10,%11}; @p ld.relaxed.gpu.global.b128 t, [%30+%35]; mov.b128 {%8,%9,%10,%11}, t;\n"
        "xor.b32 k, %12, %38; and.b32 k, k, 0x40000000; setp.eq.u32 p, k, 0; mov.b128 t, {%12,%13,%14,%15}; @p ld.relaxed.gpu.global.b128 t, [%31+%35]; mov.b128 {%12,%13,%14,%15}, t;\n"
        "xor.b32 k, %16, %38; and.b32 k, k, 0x40000000; setp.eq.u32 p, k, 0; mov.b128 t, {%16,%17,%18,%19}; @p ld.relaxed.gpu.global.b128 t, [%32+%35]; mov.b128 {%16,%17,%18,%19}, t;\n"
        "xor.b32 k, %20, %38; and.b32 k, k, 0x40000000; setp.eq.u32 p, k, 0; mov.b128 t, {%20,%21,%22,%23}; @p ld.relaxed.gpu.global.b128 t, [%33+%35]; mov.b128 {%20,%21,%22,%23}, t;\n"
        "xor.b32 k, %24, %38; and.b32 k, k, 0x40000000; setp.eq.u32 p, k, 0; mov.b128 t, {%24,%25,%26,%27}; @p ld.relaxed.gpu.global.b128 t, [%34+%35]; mov.b128 {%24,%25,%26,%27}, t;\n"
        "bra.uni L;\nD:}"
        : "+r"(r[0][0]), "+r"(r[0][1]), "+r"(r[0][2]), "+r"(r[0][3]), "+r"(r[1][0]), "+r"(r[1][1]), "+r"(r[1][2]), "+r"(r[1][3]), "+r"(r[2][0]), "+r"(r[2][1]), "+r"(r[2][2]), "+r"(r[2][3]), "+r"(r[3][0]), "+r"(r[3][1]), "+r"(r[3][2]), "+r"(r[3][3]), "+r"(r[4][0]), "+r"(r[4][1]), "+r"(r[4][2]), "+r"(r[4][3]), "+r"(r[5][0]), "+r"(r[5][1]), "+r"(r[5][2]), "+r"(r[5][3]), "+r"(r[6][0]), "+r"(r[6][1]), "+r"(r[6][2]), "+r"(r[6][3])
        : "l"(p[0]), "l"(p[1]), "l"(p[2]), "l"(p[3]), "l"(p[4]), "l"(p[5]), "l"(p[6]), "n"((4 - S_) * 524288), "n"(SPIN_LIMIT), "r"(fz), "r"(stale) : "memory");
}
template <class T> __device__ __forceinline__ T* pinp(T* p) { return (T*)__shfl_xor_sync(~0u, (unsigned long long)p, 0); }
__device__ __forceinline__ float fsel(bool c, float a, float b) { float r; asm("{.reg .pred p; setp.ne.u32 p, %3, 0; selp.f32 %0, %1, %2, p;}" : "=f"(r) : "f"(a), "f"(b), "r"((int)c)); return r; }
__device__ __forceinline__ void stg4_if(bool c, void* p, uint32_t a, uint32_t b, uint32_t d, uint32_t e) {
    asm volatile("{.reg .b128 t; .reg .pred p; setp.ne.u32 p, %5, 0; mov.b128 t, {%1,%2,%3,%4}; @p st.relaxed.gpu.global.b128 [%0], t;}" ::"l"(p), "r"(a), "r"(b), "r"(d), "r"(e), "r"((int)c) : "memory");
}
__device__ __forceinline__ void stg1_if(bool c, void* p, uint32_t a) {
    asm volatile("{.reg .pred p; setp.ne.u32 p, %2, 0; @p st.relaxed.gpu.global.u32 [%0], %1;}" ::"l"(p), "r"(a), "r"((int)c) : "memory");
}
__device__ __forceinline__ void ldg4_again(uint32_t* r, const void* p) {
    asm volatile("{.reg .b128 t; .reg .pred p; setp.eq.u32 p, %3, 0; mov.b128 t, {%0,%1,%2,%3}; @p ld.relaxed.gpu.global.b128 t, [%4]; mov.b128 {%0,%1,%2,%3}, t;}"
                 : "+r"(r[0]), "+r"(r[1]), "+r"(r[2]), "+r"(r[3]) : "l"(p) : "memory");
}
__device__ __forceinline__ void wgmma_rs_n192(float* d, const uint32_t* a, uint64_t bdesc, int accum) {
    asm volatile("{.reg .pred p; setp.ne.b32 p, %101, 0; wgmma.mma_async.sync.aligned.m64n192k16.f32.bf16.bf16 {%0,%1,%2,%3,%4,%5,%6,%7,%8,%9,%10,%11,%12,%13,%14,%15,%16,%17,%18,%19,%20,%21,%22,%23,%24,%25,%26,%27,%28,%29,%30,%31,%32,%33,%34,%35,%36,%37,%38,%39,%40,%41,%42,%43,%44,%45,%46,%47,%48,%49,%50,%51,%52,%53,%54,%55,%56,%57,%58,%59,%60,%61,%62,%63,%64,%65,%66,%67,%68,%69,%70,%71,%72,%73,%74,%75,%76,%77,%78,%79,%80,%81,%82,%83,%84,%85,%86,%87,%88,%89,%90,%91,%92,%93,%94,%95}, {%96,%97,%98,%99}, %100, p, 1, 1, 1;}"
        : "+f"(d[0]),"+f"(d[1]),"+f"(d[2]),"+f"(d[3]),"+f"(d[4]),"+f"(d[5]),"+f"(d[6]),"+f"(d[7]),"+f"(d[8]),"+f"(d[9]),"+f"(d[10]),"+f"(d[11]),"+f"(d[12]),"+f"(d[13]),"+f"(d[14]),"+f"(d[15]),"+f"(d[16]),"+f"(d[17]),"+f"(d[18]),"+f"(d[19]),"+f"(d[20]),"+f"(d[21]),"+f"(d[22]),"+f"(d[23]),"+f"(d[24]),"+f"(d[25]),"+f"(d[26]),"+f"(d[27]),"+f"(d[28]),"+f"(d[29]),"+f"(d[30]),"+f"(d[31]),"+f"(d[32]),"+f"(d[33]),"+f"(d[34]),"+f"(d[35]),"+f"(d[36]),"+f"(d[37]),"+f"(d[38]),"+f"(d[39]),"+f"(d[40]),"+f"(d[41]),"+f"(d[42]),"+f"(d[43]),"+f"(d[44]),"+f"(d[45]),"+f"(d[46]),"+f"(d[47]),"+f"(d[48]),"+f"(d[49]),"+f"(d[50]),"+f"(d[51]),"+f"(d[52]),"+f"(d[53]),"+f"(d[54]),"+f"(d[55]),"+f"(d[56]),"+f"(d[57]),"+f"(d[58]),"+f"(d[59]),"+f"(d[60]),"+f"(d[61]),"+f"(d[62]),"+f"(d[63]),"+f"(d[64]),"+f"(d[65]),"+f"(d[66]),"+f"(d[67]),"+f"(d[68]),"+f"(d[69]),"+f"(d[70]),"+f"(d[71]),"+f"(d[72]),"+f"(d[73]),"+f"(d[74]),"+f"(d[75]),"+f"(d[76]),"+f"(d[77]),"+f"(d[78]),"+f"(d[79]),"+f"(d[80]),"+f"(d[81]),"+f"(d[82]),"+f"(d[83]),"+f"(d[84]),"+f"(d[85]),"+f"(d[86]),"+f"(d[87]),"+f"(d[88]),"+f"(d[89]),"+f"(d[90]),"+f"(d[91]),"+f"(d[92]),"+f"(d[93]),"+f"(d[94]),"+f"(d[95])
        : "r"(a[0]), "r"(a[1]), "r"(a[2]), "r"(a[3]), "l"(bdesc), "r"(accum));
}
__device__ __forceinline__ void wgmma_rs_n48(float* d, const uint32_t* a, uint64_t bdesc, int accum) {
    asm volatile("{.reg .pred p; setp.ne.b32 p, %29, 0; wgmma.mma_async.sync.aligned.m64n48k16.f32.bf16.bf16 {%0,%1,%2,%3,%4,%5,%6,%7,%8,%9,%10,%11,%12,%13,%14,%15,%16,%17,%18,%19,%20,%21,%22,%23}, {%24,%25,%26,%27}, %28, p, 1, 1, 1;}"
        : "+f"(d[0]),"+f"(d[1]),"+f"(d[2]),"+f"(d[3]),"+f"(d[4]),"+f"(d[5]),"+f"(d[6]),"+f"(d[7]),"+f"(d[8]),"+f"(d[9]),"+f"(d[10]),"+f"(d[11]),"+f"(d[12]),"+f"(d[13]),"+f"(d[14]),"+f"(d[15]),"+f"(d[16]),"+f"(d[17]),"+f"(d[18]),"+f"(d[19]),"+f"(d[20]),"+f"(d[21]),"+f"(d[22]),"+f"(d[23])
        : "r"(a[0]), "r"(a[1]), "r"(a[2]), "r"(a[3]), "l"(bdesc), "r"(accum));
}
__device__ __forceinline__ void wgmma_rs_n80(float* d, const uint32_t* a, uint64_t bdesc, int accum) {
    asm volatile("{.reg .pred p; setp.ne.b32 p, %45, 0; wgmma.mma_async.sync.aligned.m64n80k16.f32.bf16.bf16 {%0,%1,%2,%3,%4,%5,%6,%7,%8,%9,%10,%11,%12,%13,%14,%15,%16,%17,%18,%19,%20,%21,%22,%23,%24,%25,%26,%27,%28,%29,%30,%31,%32,%33,%34,%35,%36,%37,%38,%39}, {%40,%41,%42,%43}, %44, p, 1, 1, 1;}"
        : "+f"(d[0]),"+f"(d[1]),"+f"(d[2]),"+f"(d[3]),"+f"(d[4]),"+f"(d[5]),"+f"(d[6]),"+f"(d[7]),"+f"(d[8]),"+f"(d[9]),"+f"(d[10]),"+f"(d[11]),"+f"(d[12]),"+f"(d[13]),"+f"(d[14]),"+f"(d[15]),"+f"(d[16]),"+f"(d[17]),"+f"(d[18]),"+f"(d[19]),"+f"(d[20]),"+f"(d[21]),"+f"(d[22]),"+f"(d[23]),"+f"(d[24]),"+f"(d[25]),"+f"(d[26]),"+f"(d[27]),"+f"(d[28]),"+f"(d[29]),"+f"(d[30]),"+f"(d[31]),"+f"(d[32]),"+f"(d[33]),"+f"(d[34]),"+f"(d[35]),"+f"(d[36]),"+f"(d[37]),"+f"(d[38]),"+f"(d[39])
        : "r"(a[0]), "r"(a[1]), "r"(a[2]), "r"(a[3]), "l"(bdesc), "r"(accum));
}

__global__ void __cluster_dims__(2, 1, 1) __launch_bounds__(384, 1)
fused_kernel(const __nv_bfloat16* __restrict__ wmod, const __nv_bfloat16* __restrict__ cvec, Scratch* __restrict__ S,
             const __nv_bfloat16* __restrict__ wqkv, const __nv_bfloat16* __restrict__ wo, __nv_bfloat16* __restrict__ out,
             const __nv_bfloat16* __restrict__ wr, const __nv_bfloat16* __restrict__ wg, const __nv_bfloat16* __restrict__ wu,
             const __nv_bfloat16* __restrict__ wd,
             const __grid_constant__ CUtensorMap mm, const __grid_constant__ CUtensorMap mx, const __grid_constant__ CUtensorMap mw,
             const __grid_constant__ CUtensorMap mt, const __grid_constant__ CUtensorMap mo, const __grid_constant__ CUtensorMap mg,
             const __grid_constant__ CUtensorMap mu, const __grid_constant__ CUtensorMap md,
             const __grid_constant__ CUtensorMap mw2, const __grid_constant__ CUtensorMap mout,
             const __grid_constant__ CUtensorMap mo2) {
    extern __shared__ __align__(1024) char sm_raw[];
    const int bid = blockIdx.x;
    const uint32_t sm = ((bid & 1) << 24) + SM0;
    STAMP(30);
    const uint32_t t_start = clock32();
    if (bid < CPF && threadIdx.x == 0)
        asm volatile("cp.async.bulk.prefetch.tensor.2d.L2.global [%0, {%1, %2}];" ::"l"(&mm), "r"((bid & 1) * 640 + (bid >> 4) * 64), "r"(((bid >> 1) & 7) * 80) : "memory");
    const int cl = bid >> 1, rank = bid & 1, c7 = ((cl - 36) * 37) >> 8;
    const int grp = cl < 4 ? 0 : (cl < 36 ? (cl - 4) & 7 : cl - 35 - 7 * c7);
    const int ti = grp * 2 + rank;
    auto ldx = [&](int c) { mbar_expect_tx(BAR(B_XF + c), 16384); tma3d(sm + c * 16384, &mx, c * 64, ti >> 3, (ti & 7) * 128, BAR(B_XF + c)); };
    if (threadIdx.x == 256 && bid < 128) {
        mbar_init(BAR(B_XF), 1); mbar_init(BAR(B_XF + 1), 1);
        pause_until(t_start, XDELAY);
        ldx(0); ldx(1);
        STAMPT(22, 256);
#pragma unroll
        for (int i = 2; i < 10; i++) mbar_init(BAR(B_XF + i), 1);
        mbar_init(BAR(B_T0), 1);
        asm volatile("fence.mbarrier_init.release.cluster;" ::: "memory");
        ldx(2); ldx(3); ldx(4);
    }
    const int warp = __shfl_sync(~0u, threadIdx.x >> 5, 0);

#define PIN(v) __shfl_xor_sync(~0u, (v), 0)
#define LANE_VARS const int tid = PIN(threadIdx.x), lane = tid & 31, g = lane >> 2, q = lane & 3; \
    const uint32_t frow = (lane & 7) + (lane >> 4) * 8, fh = (lane >> 3) & 1;
    if (bid >= 128) {
        LANE_VARS
        const int h = bid - 128;
        if (warp >= 8) {
            if (warp == 8) return;
            const int t = tid - 288;
            if (t < 90) stg4_rlx(&S->tab[(5 + t / 9) * 4 + h][t % 9], 0u, 0u, 0u, 0u);
            __syncwarp();
            asm volatile("bar.arrive 1, 352;" ::: "memory");
            bar_sync(2, 96);
            if (t == 0) asm volatile("red.release.gpu.global.add.u32 [%0], 32;" ::"l"(&S->cnt) : "memory");
            return;
        }
        const uint32_t slot = sm + warp * 20480, bar = BAR(warp * 2);
        auto column = [&](int job) {
            const int n = job * 4 + h;
            return job < 10 ? ((h & 1) ? (job < 5 ? 10 : 30) : (job < 5 ? 0 : 10)) + (n >> 1) : (n < 50 ? n - 10 : n);
        };
        auto load = [&](int job) {
            mbar_expect_tx(bar + (job & 1) * 8, 10240);
            tma2d(slot + (job & 1) * 10240, &mm, column(job) * 64, warp * 80, bar + (job & 1) * 8);
        };
        if (elect1()) { mbar_init(bar, 1); mbar_init(bar + 8, 1); load(0); }
        __syncwarp();
        uint32_t b[10];
#pragma unroll
        for (int s = 0; s < 10; s++) b[s] = ldg1_rlx((const uint32_t*)cvec + warp * 40 + s * 4 + q);
        if (lane < 8 && warp < 5) stg4_rlx(&S->tab[warp * 4 + h][lane], 0u, 0u, 0u, 0u);
#pragma unroll
        for (int s = 0; s < 10; s++) b[s] = pack2(blo(b[s]) * sigm(blo(b[s])), bhi(b[s]) * sigm(bhi(b[s])));
        const uint32_t fa = slot + frow * 128 + ((fh ^ (lane & 7)) << 4);
        const int c0 = (lane >> 3) * 16 + (lane & 1) * 8 + (lane & 6);
#pragma unroll 1
        for (int job = 0; job < 15; job++) {
            uint32_t w2 = 0;
            if (job >= 5) w2 = ldg1_rlx(wr + (column(job) % 10) * 64 + c0);

            mbar_wait(bar + (job & 1) * 8, (job >> 1) & 1);
            if (job == 0) { if (elect1()) load(1); __syncwarp(); }
            float d[4][4] = {};
#pragma unroll
            for (int s = 0; s < 5; s++) {
#pragma unroll
                for (int m = 0; m < 4; m++) { uint32_t a[4]; ldsm4t(a, (fa ^ (m * 32)) + (job & 1) * 10240 + s * 2048); mma16(d[m], a[0], a[1], a[2], a[3], b[2 * s], b[2 * s + 1]); }
            }
            const uint32_t red = sm + OFF_W + (job & 1) * 2048;
            sts1f(red + (warp * 64 + q * 8 + g) * 4, q == 0 ? d[0][0] : (q == 1 ? d[0][2] : (q == 2 ? d[1][0] : d[1][2])));
            sts1f(red + (warp * 64 + 32 + q * 8 + g) * 4, q == 0 ? d[2][0] : (q == 1 ? d[2][2] : (q == 2 ? d[3][0] : d[3][2])));
            __syncwarp();
            if (job < 13 && elect1()) load(job + 2);
            __syncwarp();
            bar_sync(0, 256);
            if (job == 5) bar_sync(1, 352);
            if (warp == (job & 7)) {
                float y0 = 0.f, y1 = 0.f;
#pragma unroll
                for (int w = 0; w < 8; w++) { const float2 v = lds2f(red + (w * 64 + c0) * 4); y0 += v.x; y1 += v.y; }
                const uint32_t t = hf2(pack2(y0, y1), 0x3f803f80u, ((h & 1) && job < 10) ? 0x3f803f80u : 0x80008000u);
                uint32_t* const p = (uint32_t*)&S->tab[job * 4 + h][0];
                stg1_rlx(p + lane, nz(t));
                float dot = fmaf(blo(t), blo(w2), bhi(t) * bhi(w2));
#pragma unroll
                for (int o = 16; o; o >>= 1) dot += __shfl_xor_sync(~0u, dot, o);
                if (lane == 0) stg1_rlx(p + 32, dot == 0.f ? 0x80000000u : __float_as_uint(dot));
            }
            if (job == 0) STAMP(27);
            if (job == 8) STAMP(28);
        }
        STAMP(17);
        return;
    }
    uint32_t ep0;
    if (__builtin_expect(warp == 8, 1)) {
        asm volatile("barrier.cluster.arrive.relaxed.aligned;" ::: "memory");
        if (elect1()) {
#pragma unroll 1
            for (int c = 5; c < 10; c++) ldx(c);
        }
        __syncwarp();
    } else {
        if (warp < 8) {
            if (elect1()) {
#pragma unroll
                for (int i = 0; i < 8; i++) { const int b = B_WF + warp * 8 + i; mbar_init(BAR(b), b >= B_WE ? 16 : (b >= B_G2 ? 8 : (b >= B_EP ? 2 : (b == B_WO ? 7 : 1)))); }
                asm volatile("fence.mbarrier_init.release.cluster;" ::: "memory");
            }
            __syncwarp();
        }
        if (warp == 9) ep0 = ldg1_rlx(&S->cnt);
        asm volatile("barrier.cluster.arrive.relaxed.aligned;" ::: "memory");
    }
    const int sl = cl < 4 ? 4 + cl : (cl < 36 ? (cl - 4) >> 3 : 4 + c7);
    const int j = sl ^ (((sl + 2) >> 2) & 1), role = ti * 8 + j, odd = j & 1;
    const int fi = j * 16 + ti;
    const int al = ((j + 1) & 2) == 0;
    Exch* const X = &S->x;
    if (warp >= 8) {
        asm volatile("setmaxnreg.dec.sync.aligned.u32 72;");
        if (warp == 8) {
            asm volatile("barrier.cluster.wait.aligned;" ::: "memory");
            if (!elect1()) return;
            const int col_main = 80 * j + 16 * odd, col_tail = 80 * j + (odd ? 0 : 64);
            auto load_w = [&](int it) {
                const uint32_t b = BAR(B_WF + it), dst = sm + wbuf(it) + rank * 6144;
                mbar_expect_tx(b, WST);
                tma4d_mc(dst, al ? &mw2 : &mw, 0, it * 32 + rank * 16, col_main >> (5 + al), 0, b);
                tma3d_mc(dst + 12288 - rank * 4608, &mt, col_tail, it * 32 + rank * 16, 0, b);
            };
            int it = 0, wn = 0, gn = 0;
#pragma unroll 1
            for (int r = -2; r < 19; r++) {
                if (r == -1) mbar_wait(BAR(B_XF + XWAIT), 0);
                if (r >= 0) mbar_wait(BAR(B_WE + r), 0);
                const int lim = min(r < 2 ? (r == 1 ? 7 : 2 * r + 6) : r + 7, 20);
#pragma unroll 1
                for (; it < lim; it++) load_w(it);
                if (r == -1 || r == 0) l2_prefetch(wqkv + (size_t)(384 + r * 256 + role * 2) * 1920, 2 * 3840);
                if (r == 0) l2_prefetch(wo + role * 3200, 6400);
                if (r >= MPF0 && r < MPF0 + 10) l2_prefetch(wmod + (size_t)(role * 5 + ((r - MPF0) >> 1)) * 3840 + 1920 + (r & 1) * 1280, 1280);
                if (((GU_MASK >> (r + 2)) & 1) && fi < 108) { if (gn == 0) mbar_expect_tx(BAR(B_FG), 40960); tma2d(sm + OFF_WG + gn * 10240, (fi & 1) ? &mu : &mg, (fi >> 1) * 32, gn * 160, BAR(B_FG)); gn++; }
#pragma unroll 1
                for (int n = ((WO_MASK >> (r + 2)) & 1) + (r == 14); n > 0; n--) {
                    const int row = (j ^ wn) * 80 + rank * 40;
                    const uint32_t b = BAR(wn ? B_WO : B_WO0), dst = sm + wobuf(wn) + rank * 2560;
                    mbar_expect_tx(b, 12800);
                    tma2d_mc(dst, &mo, col_main, row, b); tma2d_mc(dst + 5120, &mo, col_main + 32, row, b); tma2d_mc(dst + 10240, &mo2, col_tail, row, b);
                    wn++;
                }
                if (r >= PF0 && r < PF0 + 3 * PFN) { const int m = (r - PF0) / PFN; l2_prefetch((m == 0 ? wg : (m == 1 ? wu : wd)) + role * 8640 + (r - PF0 - m * PFN) * (8640 / PFN), 17280 / PFN); }
            }
            STAMPT(24, 256);
            if (fi >= 88) { mbar_wait(BAR(B_G2), 0); mbar_expect_tx(BAR(B_FD), 55296); tma3d(sm + OFF_WD, &md, (fi - 88) * 16, 0, 0, BAR(B_FD)); }
            return;
        }
        asm volatile("barrier.cluster.wait.aligned;" ::: "memory");
        const int tid = threadIdx.x, lane = tid & 31, fh = (lane >> 3) & 1;
        int gd = 0;
        if (warp == 9) {
            {
                uint32_t ta = sm + OFF_TAB + fh * 1280 + (lane >> 4) * 128 + (lane & 4) * 16 + (lane & 1) * 32 + (lane & 2) * 4;
                const uint4* tp = &S->tab[lane >> 3][lane & 7];
                pause_until(t_start, TDELAY);
#pragma unroll 1
                for (int e = 0; e < 5; e++) {
                    uint32_t w[4];
                    if (e > 1) mbar_wait(BAR(B_WE + 4 * e - 8), 0);
                    while (true) {
                        ldg4_rlx(w, tp);
                        if (!__any_sync(~0u, min(min(w[0], w[1]), min(w[2], w[3])) == 0) || ++gd > SPIN_LIMIT) break;
                        pause(P_TAB);
                    }
                    sts2(ta, w[0], w[1]); sts2(ta + 16, w[2], w[3]);
                    __syncwarp();
                    if (e == 0) { STAMPT(2, 288); if (lane == 0) sts1(sm + OFF_EP + EP_US + 8, ep0 << 22 & 0x40000000u); }
                    if (lane == 0) mbar_arrive(BAR(e ? B_TB - 1 + e : B_T0));
                    ta += 256; tp += 288;
                }
            }
            uint32_t h[5][4];
            while (ldg1_acq(&S->cnt) != inc(ep0) && ++gd < SPIN_LIMIT) __nanosleep(YSLEEP);
            __syncwarp();
            if (lane == 0) mbar_arrive(BAR(B_RDY));
            mbar_wait(BAR(HALO_GO), 0);
            pause(D_H);
            if ((ti & 7) == 0) {
#pragma unroll
                for (int s = 0; s < 20; s++) h[s >> 2][s & 3] = 0;
            } else {
                do {
#pragma unroll
                    for (int s = 0; s < 5; s++) ldg4_rlx(h[s], &X->halo[(role - 8 - (ti & 8)) * 160 + s * 32 + lane]);
                } while (__any_sync(~0u, min(min(min(h[0][0], h[1][0]), min(h[2][0], h[3][0])), h[4][0]) == 0) && ++gd < SPIN_LIMIT);
            }
            const uint32_t p8 = sm + OFF_P8 - 4096, va = p8 + 2048 + (lane & 7) * VP + (lane >> 3) * 16;
            sts4(p8 + 2048 + 1408 + lane * 16, h[0]); sts4(p8 + 1408 + lane * 16, h[1]); sts2(p8 + (lane >> 4) * 2048 + 1920 + (lane & 15) * 8, h[2][0], h[2][1]);
            stsm4(va, h[3]); stsm4(va + 64, h[4]); stsm2(va + 128, h[2][2], h[2][3]);
            __syncwarp();
            if (lane == 0) mbar_arrive(BAR(B_HL));
            STAMPT(19, 288);
            uint2* const rp = pinp((uint2*)&X->ra[(lane & 7) * 8][0] + ti);
            const uint2* const rq = pinp((const uint2*)&X->ra[grp * 8][0] + (lane & 15));
            mbar_wait(BAR(B_G3), 0);
            if (j == (ti & 7)) {
                lds2(h[0], sm + OFF_EP + EP_US + 48 + (lane & 7) * 8);
                const uint32_t km = __reduce_max_sync(~0u, h[0][0]), tk = __reduce_min_sync(~0u, h[0][0] == km ? h[0][1] : ~0u);
                if (lane < 8) asm volatile("red.relaxed.gpu.global.max.u64 [%0], %1;" ::"l"(rp), "l"((unsigned long long)tk << 32 | km) : "memory");
            }
            pause(D_REC);
            do { ldg2_rlx(h[0], rq); } while (__any_sync(~0u, h[0][1] == 0) && ++gd < SPIN_LIMIT);
            const uint32_t kwin = __reduce_max_sync(~0u, h[0][0]), tok = __reduce_min_sync(~0u, h[0][0] == kwin ? h[0][1] : ~0u);
            if (lane == 0) {
                const uint32_t t = (tok - 1) & 2047, wi = (t & 1) * 64 + (t >> 5), wv[4] = {kwin, t, wi, wi * 320};
                sts4(sm + OFF_EP + EP_US + 32, wv); mbar_arrive(BAR(B_WIN));
            }
            if (lane < 8 && role < 20) stg4_rlx(&S->tab[role][lane], 0u, 0u, 0u, 0u);
            return;
        }
        const int at = tid - 320;
        const int kg = at < 40 ? 80 * j + 2 * at : max(fi - 88, 0) * 16 + 2 * (at & 7);
        const uint32_t w2 = *(const uint32_t*)(wr + kg);
        mbar_wait(BAR(B_T0), 0);
        {
            uint4* p = &X->o[4 * 128 * 256] + role * RV + at;
#pragma unroll 1
            for (int r = 0; r < RV / 64; r++) {
                stg4_rlx(p, 0u, 0u, 0u, 0u);
                p += 64;
                __nanosleep(RSLEEP);
            }
        }
        bar_sync(5, 64);
        if (at == 0) { mbar_wait(BAR(B_TB), 0); }
        if (at == 0) asm volatile("red.release.gpu.global.add.u32 [%0], 1;" ::"l"(&S->cnt) : "memory");
        mbar_wait(BAR(B_RDY), 0);
        const uint32_t* const mp = (const uint32_t*)&S->tab[0][0] + ((kg >> 4) & 3) * 8 + (kg & 6) + ((kg >> 3) & 1);
        const int p = odd ? (at < 8 ? at + 32 : at - 8) : at, lm = min(lane, 9);
        const uint32_t a = sm + OFF_EP + (p & 3) * 48 + (p >> 2) * 4;
#pragma unroll 1
        for (int ph = 0; ph < 4; ph++) {
            uint32_t v, us;
            mbar_wait(BAR(ph < 2 ? TB_GO : TB_GO2), 0);
            while (true) {
                v = ldg1_rlx(mp + (ph < 2 ? 20 + ph + (kg >> 6) * 2 : 20 + ph * 10 + (kg >> 6)) * 288);
                us = ldg1_rlx(&S->tab[ph < 2 ? 20 + ph + lm * 2 : 20 + ph * 10 + lm][8]);
                if (!__any_sync(~0u, min(v, us) == 0) || ++gd > SPIN_LIMIT) break;
                __nanosleep(200);
            }
            if (at < 40) {
                sts1(a + ph * 192, v);
                if (ph == 1) {
                    const float u0 = blo(v) * blo(w2), u1 = bhi(v) * bhi(w2);
                    const uint32_t uh = pack2(u0, u1);
                    sts1(a + 768, 0x3f803f80u); sts1(a + 960, uh); sts1(a + 1152, pack2(u0 - blo(uh), u1 - bhi(uh)));
                }
            } else sts1(sm + OFF_EP + EP_GD + (at & 7) * 4, v);
            float t = lane < 10 ? __uint_as_float(us) : 0.f;
#pragma unroll
            for (int o = 1; o < 16; o <<= 1) t += __shfl_xor_sync(~0u, t, o);
            if (at == 0) sts1f(sm + OFF_EP + EP_US + 12 + ph * 4, t);
            __syncwarp();
            if (lane == 0 && ph) mbar_arrive(BAR(B_EP - 1 + ph));
        }
        STAMPT(20, 320);
    } else {
        asm volatile("setmaxnreg.inc.sync.aligned.u32 216;");
        asm volatile("barrier.cluster.wait.aligned;" ::: "memory");
        LANE_VARS
        const int tw = ti * 8 + warp;
        const uint32_t oo = tw * 4096 + j * 512 + lane * 16;
        const uint32_t pair = (uint32_t)(lane & 1) << 24;
        const uint32_t hi = lane >> 4, xa = sm + (warp * 16 + (lane & 15)) * 128 + ((hi ^ (lane & 7)) << 4);
        const uint32_t p8 = sm + OFF_P8 + warp * 2048, q8 = p8 - (warp ? 2048 : 4096), q9 = p8 - 2048 + (warp ? 16384 : 0);
        const uint32_t l16 = PIN(lane * 16), kt = PIN(hi * 16384 + (lane & 15) * 8), va = PIN(p8 + (lane & 7) * VP + (lane >> 3) * 16);
        const uint32_t vc = PIN(p8 + (lane & 7) * VP + fh * 16384 + hi * 16);
        const uint32_t vh = PIN((fh ? p8 : q9) + (lane & 7) * VP + hi * 16), kh = PIN((hi ? q9 : q8) + (lane & 15) * 8);
        const uint32_t mgt = PIN((2 * q > g ? 0xffffu : 0u) | (2 * q + 1 > g ? 0xffff0000u : 0u));
        uint32_t rr0, rr1, nn0, nn1;
        {
            float gA[2][4] = {}, gB[2][4] = {};
            uint32_t xb = sm + (warp * 16 + frow) * 128 + ((fh ^ (lane & 7)) << 4), one[16];
#pragma unroll
            for (int k = 0; k < 16; k++) one[k] = 0x3f803f80u + ((uint32_t)tid >> (12 + k));
#pragma unroll 1
            for (int c = 0; c < 10; c += 2) {
                mbar_wait(BAR(B_XF + c), 0); mbar_wait(BAR(B_XF + c + 1), 0);
                uint32_t a[8][4];
#pragma unroll
                for (int k = 0; k < 8; k++) ldsm4(a[k], (xb ^ ((k & 3) * 32)) + (k >> 2) * 16384);
                xb += 32768;
#pragma unroll
                for (int k = 0; k < 8; k++) {
                    uint32_t t[4];
#pragma unroll
                    for (int e = 0; e < 4; e++) asm volatile("mov.b32 %0, %1;" : "=r"(t[e]) : "r"(a[k][e]));
                    mma16(gA[k & 1], t[0], one[(k & 3) * 4], t[1], one[(k & 3) * 4 + 1], a[k][0], a[k][1]);
                    mma16(gB[k & 1], t[2], one[(k & 3) * 4 + 2], t[3], one[(k & 3) * 4 + 3], a[k][2], a[k][3]);
                }
            }
            const int src = (lane & ~3) | (g >> 1), e = g & 1;
            const float ss0 = __shfl_sync(~0u, e ? gA[0][1] + gA[1][1] : gA[0][0] + gA[1][0], src), ss1 = __shfl_sync(~0u, e ? gB[0][1] + gB[1][1] : gB[0][0] + gB[1][0], src);
            const float m0 = __shfl_sync(~0u, e ? gA[0][3] + gA[1][3] : gA[0][2] + gA[1][2], src) * (1.f / 640), m1 = __shfl_sync(~0u, e ? gB[0][3] + gB[1][3] : gB[0][2] + gB[1][2], src) * (1.f / 640);
            const float r0 = rbf(rsq(fmaxf(ss0 * (1.f / 640) - m0 * m0, 0.f) + 1e-5f)), r1 = rbf(rsq(fmaxf(ss1 * (1.f / 640) - m1 * m1, 0.f) + 1e-5f));
            rr0 = pack2(r0, r0); rr1 = pack2(r1, r1); nn0 = pack2(-m0 * r0, -m0 * r0); nn1 = pack2(-m1 * r1, -m1 * r1);
        }
        uint32_t xr[5][4];
#pragma unroll
        for (int s = 0; s < 5; s++) {
            const int ks = 5 * j + (odd ? (s == 4 ? 0 : s + 1) : s);
            ldsm4(xr[s], (xa ^ ((ks & 3) * 32)) + (ks >> 2) * 16384);
        }
        STAMP(0);
        mbar_wait(BAR(B_T0), 0);
        float acc[120];
#pragma unroll
        for (int i = 0; i < 120; i++) asm volatile("" : "=f"(acc[i]));
        {
            uint32_t a[2][2][4], raw[2][4], tt[2][4];
            uint32_t tb = sm + OFF_TAB + q * 16, xp = xa;
            auto load = [&](int u) {
                ldsm4(raw[0], xp ^ (u * 64)); ldsm4(raw[1], xp ^ (u * 64 + 32));
                lds4(tt[0], tb + u * 64 + 1280); lds4(tt[1], tb + u * 64);
            };
            auto xform = [&](uint32_t (*dst)[4]) {
#pragma unroll
                for (int h = 0; h < 2; h++) {
                    dst[h][0] = hf2(hf2(raw[h][0], rr0, nn0), tt[0][2 * h], tt[1][2 * h]); dst[h][1] = hf2(hf2(raw[h][1], rr1, nn1), tt[0][2 * h], tt[1][2 * h]);
                    dst[h][2] = hf2(hf2(raw[h][2], rr0, nn0), tt[0][2 * h + 1], tt[1][2 * h + 1]); dst[h][3] = hf2(hf2(raw[h][3], rr1, nn1), tt[0][2 * h + 1], tt[1][2 * h + 1]);
                }
            };
            const uint64_t dm0 = al ? mkdesc(SM0, 2048, 1024, 1) : mkdesc(SM0, 1024, 512, 2), dt0 = mkdesc(SM0 + 12288, 512, 256, 3);
            load(0); xform(a[0]);
            STAMP(3);
#pragma unroll 1
            for (int i2 = 0; i2 < 10; i2++) {
#pragma unroll
                for (int u = 0; u < 2; u++) {
                    const int it = i2 * 2 + u;
                    const uint32_t bo = wbuf(it) >> 4;
                    mbar_wait(BAR(B_WF + it), 0);
                    if (LAG && warp < 4 && i2 * 2 + u == 20 - LAG) bar_sync(4, 256);
                    wg_fence();
#pragma unroll
                    for (int h = 0; h < 2; h++) { wgmma_rs_n192(acc, a[u][h], dm0 + bo + h * 384, (u | h) ? 1 : i2); wgmma_rs_n48(acc + 96, a[u][h], dt0 + bo + h * 96, (u | h) ? 1 : i2); }
                    wg_commit();
                    if (LAG && u == 1 && warp >= 4 && i2 == 9) asm volatile("bar.arrive 4, 256;" ::: "memory");
                    if (u == 1) { xp += 16384; tb += 128; }
                    if (u == 1 && (i2 & 1) && i2 < 9) mbar_wait(BAR(B_TB + (i2 >> 1)), 0);
                    load(u ^ 1);
                    wg_wait<1>();
                    if (lane < 2 && (u == 1 || i2 > 0)) mbar_arrive_cl(pair + BAR0(B_WE - 1 + it));
                    xform(a[u ^ 1]);
                }
            }
        }
        uint32_t own[5][4], ab[3][7][4], sv, tc, fz = 0;
        const char* op[7];
        auto ldo = [&](int s, uint32_t (*dst)[4]) {
#pragma unroll
            for (int w = 0; w < 7; w++) ldg4_rlx(dst[w], op[w] + (4 - s) * 524288);
        };
        {
            uint32_t Q[10][2], K[2][10], V[2][10];
            mbar_wait(BAR(B_RDY), 0);
            const bool pub = warp == 7 && (~ti & 7);
            uint4* const hp = pinp(&X->halo[(role - (ti & 8)) * 160 + lane]);
            sv = lds1(sm + OFF_EP + EP_US + 8); tc = (sv ^ 0x40000000u) - 0x20000000u;
            wg_wait<0>();
            STAMP(4); STAMPT(18, 128);
#define ACC_IDX(t, m) (odd_ ? (t >= 2 ? m * 32 + (t - 2) * 4 : 96 + m * 8 + t * 4) : (t < 8 ? m * 32 + t * 4 : 96 + m * 8 + (t - 8) * 4))
#define PACK1(odd_v) { constexpr bool odd_ = odd_v; _Pragma("unroll") for (int t = 0; t < 10; t++) { \
                K[1][t] = pack2(acc[ACC_IDX(t, 1) + 2], acc[ACC_IDX(t, 1) + 3]); V[1][t] = pack2(acc[ACC_IDX(t, 2) + 2], acc[ACC_IDX(t, 2) + 3]); } }
#define PACK2(odd_v) { constexpr bool odd_ = odd_v; _Pragma("unroll") for (int t = 0; t < 10; t++) { \
                V[0][t] = pack2(acc[ACC_IDX(t, 2)], acc[ACC_IDX(t, 2) + 1]); \
                K[0][t] = pack2(acc[ACC_IDX(t, 1)], acc[ACC_IDX(t, 1) + 1]); \
                Q[t][0] = pack2(acc[ACC_IDX(t, 0)], acc[ACC_IDX(t, 0) + 1]); Q[t][1] = pack2(acc[ACC_IDX(t, 0) + 2], acc[ACC_IDX(t, 0) + 3]); } }
            if (odd) PACK1(true) else PACK1(false)
            if (pub) {
                K[1][0] = nz(K[1][0]); K[1][5] = nz(K[1][5]); K[1][2] = nz(K[1][2]); V[1][0] = nz(V[1][0]); V[1][4] = nz(V[1][4]);
                stg4_rlx(hp, K[1][0], K[1][1], K[1][3], K[1][4]); stg4_rlx(hp + 32, K[1][5], K[1][6], K[1][8], K[1][9]);
                stg4_rlx(hp + 96, V[1][0], V[1][1], V[1][2], V[1][3]); stg4_rlx(hp + 128, V[1][4], V[1][5], V[1][6], V[1][7]); stg4_rlx(hp + 64, K[1][2], K[1][7], V[1][8], V[1][9]);
            }
            uint32_t VT[5][4], KH[10];
            {
                const uint32_t k0[4] = {K[1][0], K[1][1], K[1][3], K[1][4]}, k1[4] = {K[1][5], K[1][6], K[1][8], K[1][9]};
                sts4(p8 + 16384 + 1408 + l16, k0); sts4(p8 + 1408 + l16, k1); sts2(p8 + 1920 + kt, K[1][2], K[1][7]);
                stsm4(va + 16384, V[1]); stsm4(va + 16384 + 64, V[1] + 4); stsm2(va + 16384 + 128, V[1][8], V[1][9]);
            }
            __syncwarp();
            if (lane == 0) mbar_arrive(BAR(B_HL + 1 + warp));
            if (odd) PACK2(true) else PACK2(false)
            stsm4(va, V[0]); stsm4(va + 64, V[0] + 4); stsm2(va + 128, V[0][8], V[0][9]);
            __syncwarp();
#pragma unroll
            for (int s = 0; s < 5; s++) ldsm4t(VT[s], vc + s * 32);
            float sb[4][4], sc[4][4];
            uint32_t qs[4][2];
#pragma unroll
            for (int h = 0; h < 4; h++) {
                const int ts = (h >> 1) * 5 + 2, ta = (h >> 1) * 5 + (h & 1) * 3;
                const bool mine = (q >> 1) == (h & 1);
                qs[h][0] = mine ? Q[ts][0] : 0u; qs[h][1] = mine ? Q[ts][1] : 0u;
                mma16c(sb[h], Q[ta][0], Q[ta][1], Q[ta + 1][0], Q[ta + 1][1], K[0][ta], K[0][ta + 1], 0.f, 0.f);
                mma16c(sc[h], Q[ta][0], Q[ta][1], Q[ta + 1][0], Q[ta + 1][1], K[1][ta], K[1][ta + 1], 0.f, 0.f);
                mma8(sb[h], qs[h][0], qs[h][1], K[0][ts]);
                mma8(sc[h], qs[h][0], qs[h][1], K[1][ts]);
            }
            const bool gt0 = mgt & 1, gt1 = (int)mgt < 0;
            auto half = [&](int e, float (*pv)[4], float (*cu)[4], uint32_t (*VT)[4]) {
                const float cs = 0.22360679774997896f * 1.4426950408889634f;
                uint32_t p[4];
                float t0[4], t1[4], m[4];
#pragma unroll
                for (int h = 0; h < 4; h++) { t0[h] = gt0 ? pv[h][2 * e] : cu[h][2 * e]; t1[h] = gt1 ? pv[h][2 * e + 1] : cu[h][2 * e + 1]; m[h] = fmaxf(t0[h], t1[h]); }
#pragma unroll
                for (int h = 0; h < 4; h++) m[h] = fmaxf(m[h], __shfl_xor_sync(~0u, m[h], 1));
#pragma unroll
                for (int h = 0; h < 4; h++) m[h] = fmaxf(m[h], __shfl_xor_sync(~0u, m[h], 2)) * -cs;
#pragma unroll
                for (int h = 0; h < 4; h++) p[h] = pack2(ex2(fmaf(t0[h], cs, m[h])), ex2(fmaf(t1[h], cs, m[h])));
#pragma unroll
                for (int pr = 0; pr < 2; pr++) {
                    const uint32_t a0 = p[2 * pr] & mgt, a1 = p[2 * pr + 1] & mgt, a2 = p[2 * pr] & ~mgt, a3 = p[2 * pr + 1] & ~mgt;
                    float l[4];
                    mma16c(l, a0, a1, a2, a3, 0x3f803f80u, 0x3f803f80u, 0.f, 0.f);
                    l[0] = rcp(l[0]); l[2] = rcp(l[2]);
#pragma unroll
                    for (int r = 0; r < 5; r++) {
                        const int t = pr * 5 + r;
                        float d[4];
                        mma16c(d, a0, a1, a2, a3, VT[t >> 1][(t & 1) * 2], VT[t >> 1][(t & 1) * 2 + 1], 0.f, 0.f);
                        const bool od = r == 2 ? (q & 2) : r > 2;
                        const float li = od ? l[2] : l[0];
                        own[t >> 1][(t & 1) * 2 + e] = pack2((od ? d[2] : d[0]) * li, (od ? d[3] : d[1]) * li);
                    }
                }
            };
            mbar_wait(BAR(B_HL + warp), 0);
            uint32_t VH[5][4];
            float sa[4][4];
            lds4(KH, q9 + 1408 + l16); lds4(KH + 4, q8 + 1408 + l16); lds2(KH + 8, kh + 1920);
#pragma unroll
            for (int s = 0; s < 5; s++) ldsm4t(VH[s], vh + s * 32);
            STAMP(5); STAMPT(25, 64);
            fz |= clock32();
            const float ninf = (tw & 63) == 0 ? -INFINITY : 0.f;
#pragma unroll
            for (int h = 0; h < 4; h++) {
                const int ta = (h >> 1) * 5 + (h & 1) * 3;
                mma16c(sa[h], Q[ta][0], Q[ta][1], Q[ta + 1][0], Q[ta + 1][1], KH[2 * h], KH[2 * h + 1], ninf, ninf);
                mma8(sa[h], qs[h][0], qs[h][1], KH[8 + (h >> 1)]);
            }
            half(1, sb, sc, VT);
            half(0, sa, sb, VH);
#pragma unroll
            for (int w = 0; w < 7; w++) op[w] = (const char*)X->o + (oo ^ (w * 512 + 512));
#pragma unroll
            for (int s = 0; s < 5; s++) {
                own[s][0] = s ? tagw(own[s][0], tc) : nz(own[s][0]); stg4_rlx((char*)X->o + oo + (4 - s) * 524288, own[s][0], own[s][1], own[s][2], own[s][3]);
            }
        }
        STAMP(6); STAMPT(21, 128); STAMPT(26, 64);
        float ac2[40];
#pragma unroll
        for (int i = 0; i < 40; i++) asm volatile("" : "=f"(ac2[i]));
        {
            const uint64_t d0 = mkdesc(SM0, 5120, 512, 2);
            mbar_wait(BAR(B_WO0), 0);
#pragma unroll
            for (int s = 1; s < 5; s++) own[s][0] -= tc;
            wg_fence();
#pragma unroll
            for (int s = 0; s < 5; s++) wgmma_rs_n80(ac2, own[s], d0 + (wobuf(0) >> 4) + s * 64, s);
            wg_commit();
            const uint32_t t6 = clock32();
            fz |= t6;
            pause_until(t6, D_O);
            ldo(0, ab[0]);
            mbar_wait(BAR(B_WO), 0);
#pragma unroll
            for (int s = 0; s < 5; s++) {
                uint32_t (*cur)[4] = ab[s % 3];
                if (s == 0) await7<0>(cur, op, fz, sv);
                else {
                    if (s == 1) await7<1>(cur, op, fz, sv); else if (s == 2) await7<2>(cur, op, fz, sv); else if (s == 3) await7<3>(cur, op, fz, sv); else await7<4>(cur, op, fz, sv);
#pragma unroll
                    for (int w = 0; w < 7; w++) cur[w][0] -= tc;
                }
                if (s == 0) { STAMP(7); STAMPT(1, 128); }
                wg_fence();
#pragma unroll
                for (int w = 1; w < 8; w++) wgmma_rs_n80(ac2, cur[w - 1], d0 + (wobuf(w) >> 4) + s * 64, 1);
                wg_commit();
                if (s < 3) { if (s) wg_wait<1>(); else fz |= clock32(); if (s == 0) ldo(1, ab[1]); ldo(s + 2, ab[(s + 2) % 3]); }
                if (s == FD_AT && lane == 0) mbar_arrive(BAR(B_G2));
            }
        }
        mbar_wait(BAR(B_EP), 0);
        uint32_t tga[12], tst[12];
        const uint32_t ep = sm + OFF_EP + q * 48;
#pragma unroll
        for (int s = 0; s < 3; s++) { lds4(tga + 4 * s, ep + s * 16); lds4(tst + 4 * s, ep + 768 + min(g, 2) * 192 + s * 16); }
        uint4* const sp0 = pinp(&X->stats[j][tw * 16 + g]);
        const int prow = (ti & 7) * 128 + warp * 16;
        const uint4* const sp = pinp(&X->stats[hi * 4][tw * 16 + (lane & 15)]);
        const int dsrc = PIN((lane & ~3) | (g >> 1));
        wg_wait<0>();
        if (lane == 0) mbar_arrive(BAR(B_G4));
        STAMP(8); STAMPT(23, 128);
        {
            float gA[2][4] = {}, gB[2][4] = {}, sd[4] = {};
#pragma unroll
            for (int s = 0; s < 5; s++) {
#pragma unroll
                for (int e = 0; e < 4; e++) xr[s][e] = hf2(tga[2 * s + (e >> 1)], pack2(ac2[s * 8 + e * 2], ac2[s * 8 + e * 2 + 1]), xr[s][e]);
                mma16(sd, xr[s][0], xr[s][1], xr[s][2], xr[s][3], tst[2 * s], tst[2 * s + 1]);
                mma8(gA[0], xr[s][0], xr[s][1], xr[s][0]); mma8(gB[0], xr[s][0], xr[s][1], xr[s][1]);
                mma8(gA[1], xr[s][2], xr[s][3], xr[s][2]); mma8(gB[1], xr[s][2], xr[s][3], xr[s][3]);
            }
            const float l0 = __shfl_down_sync(~0u, sd[0], 1), l1 = __shfl_down_sync(~0u, sd[2], 1);
            const float q0 = __shfl_sync(~0u, fsel(g & 1, gA[0][1] + gA[1][1], gA[0][0] + gA[1][0]), dsrc), q1 = __shfl_sync(~0u, fsel(g & 1, gB[0][3] + gB[1][3], gB[0][2] + gB[1][2]), dsrc);
            stg4_if(q == 0, sp0, __float_as_uint(sd[0]), __float_as_uint(sd[1] + l0), __float_as_uint(q0), 1u);
            stg4_if(q == 0, sp0 + 8, __float_as_uint(sd[2]), __float_as_uint(sd[3] + l1), __float_as_uint(q1), 1u);
        }
        const uint32_t t9 = clock32();
        STAMP(9);
        uint32_t fg[5][4], fu[5][4], tcb[12], tsb[12];
        uint32_t st[4][4];
        if (fi < 108) {
            mbar_wait(BAR(B_FG), 0);
#pragma unroll
            for (int s = 0; s < 5; s++) {
                const uint32_t off = sm + OFF_WG + (5 * warp + ((warp & 1) ? (s == 4 ? 0 : s + 1) : s)) * 1024 + frow * 64 + ((fh ^ ((lane >> 1) & 3)) << 4);
                ldsm4t(fg[s], off); ldsm4t(fu[s], off ^ 32);
            }
        }
        pause_until(t9, D_ST);
#pragma unroll
        for (int e = 0; e < 4; e++) ldg4_rlx(st[e], sp + e * 2056);
        mbar_wait(BAR(B_EP2), 0);
#pragma unroll
        for (int s = 0; s < 3; s++) { lds4(tcb + 4 * s, ep + 192 + s * 16); lds4(tsb + 4 * s, ep + 384 + s * 16); }
        int crow;
        {
            const float2 su = lds2f(sm + OFF_EP + EP_US + 16);
            int gd = 0;
            const int tk = PIN(prow * 2 + (ti >> 3) + 1);
            float v[3];
            bool bad;
            while (true) {
                bad = __any_sync(~0u, (st[0][3] & st[1][3] & st[2][3] & st[3][3]) == 0);
#pragma unroll
                for (int e = 0; e < 3; e++) {
                    v[e] = (__uint_as_float(st[0][e]) + __uint_as_float(st[1][e])) + (__uint_as_float(st[2][e]) + __uint_as_float(st[3][e]));
                    v[e] += __shfl_xor_sync(~0u, v[e], 16);
                }
                if (!bad || ++gd > SPIN_LIMIT) break;
#pragma unroll
                for (int e = 0; e < 4; e++) ldg4_again(st[e], sp + e * 2056);
            }
            STAMP(10);
            const float m = v[0] * (1.f / 640), rs = rsq(fmaxf(fmaf(v[2], 1.f / 640, 1e-5f) - m * m, 1e-5f));
            const uint32_t key = fkey(fmaf(rs, fmaf(-m, su.x, v[1]), su.y)), kmax = __reduce_max_sync(~0u, key);
            crow = __ffs(__ballot_sync(~0u, key == kmax)) - 1;
            if (lane == 0) { sts2(sm + OFF_EP + EP_US + 48 + warp * 8, kmax, tk + 2 * crow); mbar_arrive(BAR(B_G3)); }
            const uint32_t rn = pack2(rs, -m * rbf(rs)), a0 = __shfl_sync(~0u, rn, g), a1 = __shfl_sync(~0u, rn, g + 8);
            rr0 = __byte_perm(a0, 0, 0x1010); nn0 = __byte_perm(a0, 0, 0x3232); rr1 = __byte_perm(a1, 0, 0x1010); nn1 = __byte_perm(a1, 0, 0x3232);
        }
        {
            const bool up = crow >= 8;
            const uint32_t rr = up ? rr1 : rr0, nn = up ? nn1 : nn0;
            if (g == (crow & 7)) {
                uint4* cp = &X->cand[j][tw * 20 + q];
#pragma unroll
                for (int s = 0; s < 5; s++) {
                    const uint32_t xa_ = up ? xr[s][1] : xr[s][0], xb_ = up ? xr[s][3] : xr[s][2];
                    stg4_rlx(cp + s * 4, nz(hf2(hf2(xa_, rr, nn), tcb[2 * s], tsb[2 * s])), hf2(hf2(xb_, rr, nn), tcb[2 * s + 1], tsb[2 * s + 1]), xa_, xb_);
                }
            }
        }
        STAMP(11);
        const uint32_t stg = sm + 5 * WST + warp * 2560;
        {
            mbar_wait(BAR(B_EP3), 0);
#pragma unroll
            for (int s = 0; s < 3; s++) lds4(tga + 4 * s, ep + 576 + s * 16);
#pragma unroll
            for (int s = 0; s < 5; s++) {
#pragma unroll
                for (int e = 0; e < 4; e++) { const int t = 2 * s + (e >> 1); xr[s][e] = hf2(tga[t], hf2(hf2(xr[s][e], (e & 1) ? rr1 : rr0, (e & 1) ? nn1 : nn0), tcb[t], tsb[t]), xr[s][e]); }
            }
            mbar_wait(BAR(B_G4), 0);
#pragma unroll
            for (int s = 0; s < 5; s++) stsm4(stg + (lane & 15) * 160 + (odd ? (s == 4 ? 0 : s + 1) : s) * 32 + hi * 16, xr[s]);
            asm volatile("fence.proxy.async.shared::cta;" ::: "memory");
            __syncwarp();
            if (elect1()) tma3d_st(&mout, 80 * j, ti >> 3, prow + (~crow & 8), stg + (~crow & 8) * 160);
        }
        STAMP(12);
        const char* cp = (const char*)pinp(&X->cand[warp][q]);
        uint32_t* const ap0 = pinp((uint32_t*)&X->ra[fi >> 1][8 + (fi & 1) * 4] + (lane & 8) + (lane & 3) * 2 + ((lane >> 2) & 1));
        const uint32_t rw = PIN(sm + OFF_RED - 256 + (q * 4 + (g >> 1)) * 80 + warp * 8 + (g & 1) * 4), rd = PIN(sm + OFF_RED - 256 + (lane & 15) * 80);
        if (smem_u32(sm_raw) != sm) return;
        uint32_t wv[4]; int gd = 0;
        mbar_wait(BAR(B_WIN), 0);
        lds4(wv, sm + OFF_EP + EP_US + 32);
        const uint32_t kwin = wv[0];
        const int tokwin = wv[1], win = wv[2];
        STAMP(13);
        if (fi < 108) {
            uint32_t hb[5][2];
            float mine;
            bool bad;
            cp += wv[3];
            do {
#pragma unroll
                for (int s = 0; s < 5; s++) ldg2_rlx(hb[s], cp + s * 64);
                bad = __any_sync(~0u, min(min(min(hb[0][0], hb[1][0]), min(hb[2][0], hb[3][0])), hb[4][0]) == 0);
                float dg[2][4] = {}, du[2][4] = {};
#pragma unroll
                for (int s = 0; s < 5; s++) {
                    mma16(dg[s & 1], fg[s][0], fg[s][1], fg[s][2], fg[s][3], hb[s][0], hb[s][1]);
                    mma16(du[s & 1], fu[s][0], fu[s][1], fu[s][2], fu[s][3], hb[s][0], hb[s][1]);
                }
                mine = fsel(q & 2, fsel(q & 1, du[1][2], du[1][0]), fsel(q & 1, dg[1][2], dg[1][0])) + fsel(q & 2, fsel(q & 1, du[0][2], du[0][0]), fsel(q & 1, dg[0][2], dg[0][0]));
                sts1f(rw, mine);
                gd++;
            } while (bad && gd < SPIN_LIMIT);
            bar_sync(2, 256);
            if (warp == 0) {
                uint32_t v[4][4];
#pragma unroll
                for (int e = 0; e < 4; e++) lds4(v[e], rd + e * 16);
                float t[2];
#pragma unroll
                for (int e = 0; e < 2; e++)
                    t[e] = ((__uint_as_float(v[0][e]) + __uint_as_float(v[0][e + 2])) + (__uint_as_float(v[1][e]) + __uint_as_float(v[1][e + 2]))) +
                           ((__uint_as_float(v[2][e]) + __uint_as_float(v[2][e + 2])) + (__uint_as_float(v[3][e]) + __uint_as_float(v[3][e + 2])));
                uint32_t pr = pack2(t[0], t[1]);
                if (!(fi & 1)) pr = pack2(blo(pr) * sigm(blo(pr)), bhi(pr) * sigm(bhi(pr)));
                stg1_if(lane < 16, ap0, nz(pr));
            }
        }
        STAMP(14);
        if (win != tw) {
            if (elect1()) tma3d_st(&mout, 80 * j, ti >> 3, prow + (crow & 8), stg + (crow & 8) * 160);
        } else {
#pragma unroll 1
            for (int r = crow & 8; r <= (crow | 7); r++)
                if (r != crow && lane < 20) { uint32_t v[2]; lds2(v, stg + r * 160 + lane * 8); *(uint2*)(out + (size_t)((prow + r) * 2 + (ti >> 3)) * 640 + 80 * j + lane * 4) = make_uint2(v[0], v[1]); }
        }
        if (fi >= 88) {
            const int d = fi - 88, dj = d / 5, dm = d - dj * 5, sp = (dj & 1) ? (dm == 0 ? 4 : dm - 1) : dm;
            const int ks0 = min(warp * 14, 94);
            const uint32_t frag = frow * 32 + ((fh ^ ((lane >> 2) & 1)) << 4);
            uint32_t fd[14][4];
            mbar_wait(BAR(B_FD), 0);
#pragma unroll
            for (int s = 0; s < 14; s++) ldsm4t(fd[s], sm + OFF_WD + (ks0 + s) * 512 + frag);
            const float sf = sigm(rbf(__uint_as_float((kwin & 0x80000000u) ? kwin & 0x7fffffffu : ~kwin)));
            const uint32_t sg = PIN(pack2(sf, sf));
            const uint32_t gbd = lds1(sm + OFF_EP + EP_GD + (lane & 7) * 4);
            uint32_t* const op = (uint32_t*)(out + (size_t)tokwin * 640 + d * 16) + (lane & 7);
            uint32_t bsv[4], ag[4], au[4];
            const uint4* ap = &X->ra[(ks0 >> 1) + min(g, 6)][8 + q];
            const uint32_t keep = warp == 7 && g < 2 ? 0u : ~0u;
            const uint32_t as = PIN(sm + 7 * WST + warp * 512 + q * 16), aw = PIN(sm + 7 * WST + warp * 512 + g * 64 + (q & 1) * 32 + (q >> 1) * 8);
            const uint32_t yw = PIN(sm + OFF_TAB + ((q & 1) * 4 + (g >> 1)) * 80 + warp * 8 + (g & 1) * 4), yr = PIN(sm + OFF_TAB + (lane & 7) * 80);
            bool bad;
            do {
                ldg4_rlx(ag, ap); ldg4_rlx(au, ap + 4); ldg4_rlx(bsv, &X->cand[dj][win * 20 + sp * 4 + q]);
                bad = __any_sync(~0u, min(min(min(min(ag[0], ag[1]), min(ag[2], ag[3])), min(min(au[0], au[1]), min(au[2], au[3]))), bsv[0]) == 0);
                sts2(aw, hm2(ag[0], au[0]) & keep, hm2(ag[1], au[1]) & keep); sts2(aw + 16, hm2(ag[2], au[2]) & keep, hm2(ag[3], au[3]) & keep);
                gd++;
            } while (bad && gd < SPIN_LIMIT);
            STAMP(15);
            __syncwarp();
            float dy[4][4] = {};
            uint32_t av[7][4];
#pragma unroll
            for (int s = 0; s < 7; s++) lds4(av[s], as + s * 64);
#pragma unroll
            for (int s = 0; s < 7; s++) {
                mma16(dy[(2 * s) & 3], fd[2 * s][0], fd[2 * s][1], fd[2 * s][2], fd[2 * s][3], av[s][0], av[s][1]);
                mma16(dy[(2 * s + 1) & 3], fd[2 * s + 1][0], fd[2 * s + 1][1], fd[2 * s + 1][2], fd[2 * s + 1][3], av[s][2], av[s][3]);
            }
            sts1f(yw, (fsel(q & 1, dy[2][2], dy[2][0]) + fsel(q & 1, dy[3][2], dy[3][0])) + (fsel(q & 1, dy[0][2], dy[0][0]) + fsel(q & 1, dy[1][2], dy[1][0])));
            bar_sync(2, 256);
            if (warp == 0) {
                uint32_t v[4][4];
#pragma unroll
                for (int e = 0; e < 4; e++) lds4(v[e], yr + e * 16);
                float t[2];
#pragma unroll
                for (int e = 0; e < 2; e++)
                    t[e] = ((__uint_as_float(v[0][e]) + __uint_as_float(v[0][e + 2])) + (__uint_as_float(v[1][e]) + __uint_as_float(v[1][e + 2]))) +
                           ((__uint_as_float(v[2][e]) + __uint_as_float(v[2][e + 2])) + (__uint_as_float(v[3][e]) + __uint_as_float(v[3][e + 2])));
                const uint32_t hh = (lane & 4) ? bsv[1] : bsv[0], xx = (lane & 4) ? bsv[3] : bsv[2];
                if (lane < 8) *op = hf2(gbd, hf2(hm2(pack2(t[0], t[1]), sg), 0x3f803f80u, hh), xx);
            }
        }
        asm volatile("cp.async.bulk.commit_group;\ncp.async.bulk.wait_group.read 0;" ::: "memory");
        STAMP(16);
    }
}

typedef CUresult (*EncFn)(CUtensorMap*, CUtensorMapDataType, cuuint32_t, void*, const cuuint64_t*, const cuuint64_t*, const cuuint32_t*, const cuuint32_t*,
                          CUtensorMapInterleave, CUtensorMapSwizzle, CUtensorMapL2promotion, CUtensorMapFloatOOBfill);
static void make_map(EncFn enc, CUtensorMap* m, const void* base, int rank, const cuuint64_t* dims, const cuuint64_t* strides, const cuuint32_t* box, CUtensorMapSwizzle sw) {
    const cuuint32_t es[5] = {1, 1, 1, 1, 1};
    enc(m, CU_TENSOR_MAP_DATA_TYPE_BFLOAT16, rank, (void*)base, dims, strides, box, es, CU_TENSOR_MAP_INTERLEAVE_NONE, sw, CU_TENSOR_MAP_L2_PROMOTION_NONE, CU_TENSOR_MAP_FLOAT_OOB_FILL_NONE);
}

extern "C" void kernel_launch(void* const* d_in, const int* in_sizes, int n_in, void* d_out, int out_size) {
    typedef const __nv_bfloat16* P;
    P x = (P)d_in[0], wqkv = (P)d_in[1], wo = (P)d_in[2], wr = (P)d_in[4], wg = (P)d_in[5], wu = (P)d_in[6], wd = (P)d_in[7], c = (P)d_in[8], wmod = (P)d_in[9];
    void* fn = nullptr; cudaDriverEntryPointQueryResult qr;
    cudaGetDriverEntryPoint("cuTensorMapEncodeTiled", &fn, cudaEnableDefault, &qr);
    EncFn enc = (EncFn)fn;
    CUtensorMap mx, mw, mt, mo, mg, mu, md, mm, mw2, mout, mo2;
    { cuuint64_t d[] = {640, 2, 1024}, s[] = {1280, 2560}; cuuint32_t b[] = {64, 1, 128}; make_map(enc, &mx, x, 3, d, s, b, CU_TENSOR_MAP_SWIZZLE_128B); }
    { cuuint64_t d[] = {32, 640, 20, 3}, s[] = {3840, 64, 1280}; cuuint32_t b[] = {32, 16, 2, 3}; make_map(enc, &mw, wqkv, 4, d, s, b, CU_TENSOR_MAP_SWIZZLE_64B); }
    { cuuint64_t d[] = {640, 640, 3}, s[] = {3840, 1280}; cuuint32_t b[] = {16, 16, 3}; make_map(enc, &mt, wqkv, 3, d, s, b, CU_TENSOR_MAP_SWIZZLE_32B); }
    { cuuint64_t d[] = {640, 640}, s[] = {1280}; cuuint32_t b[] = {32, 40}; make_map(enc, &mo, wo, 2, d, s, b, CU_TENSOR_MAP_SWIZZLE_64B);
      b[0] = 16; make_map(enc, &mo2, wo, 2, d, s, b, CU_TENSOR_MAP_SWIZZLE_64B); }
    { cuuint64_t d[] = {1728, 640}, s[] = {3456}; cuuint32_t b[] = {32, 160}; make_map(enc, &mg, wg, 2, d, s, b, CU_TENSOR_MAP_SWIZZLE_64B); make_map(enc, &mu, wu, 2, d, s, b, CU_TENSOR_MAP_SWIZZLE_64B); }
    { cuuint64_t d[] = {640, 216, 8}, s[] = {1280, 1280 * 216}; cuuint32_t b[] = {16, 216, 8}; make_map(enc, &md, wd, 3, d, s, b, CU_TENSOR_MAP_SWIZZLE_32B); }
    { cuuint64_t d[] = {3840, 640}, s[] = {7680}; cuuint32_t b[] = {64, 80}; make_map(enc, &mm, wmod, 2, d, s, b, CU_TENSOR_MAP_SWIZZLE_128B); }
    { cuuint64_t d[] = {64, 640, 10, 3}, s[] = {3840, 128, 1280}; cuuint32_t b[] = {64, 16, 1, 3}; make_map(enc, &mw2, wqkv, 4, d, s, b, CU_TENSOR_MAP_SWIZZLE_128B); }
    { cuuint64_t d[] = {640, 2, 1024}, s[] = {1280, 2560}; cuuint32_t b[] = {80, 1, 8}; make_map(enc, &mout, d_out, 3, d, s, b, CU_TENSOR_MAP_SWIZZLE_NONE); }
    void* sp = nullptr;
    cudaGetSymbolAddress(&sp, g_s);
    cudaFuncSetAttribute(fused_kernel, cudaFuncAttributeMaxDynamicSharedMemorySize, SMEM_BYTES);
    fused_kernel<<<132, 384, SMEM_BYTES>>>(wmod, c, (Scratch*)sp, wqkv, wo, (__nv_bfloat16*)d_out, wr, wg, wu, wd, mm, mx, mw, mt, mo, mg, mu, md, mw2, mout, mo2);
}
```

```cpp
#include <cuda_runtime.h>
#include <cuda_bf16.h>
#include <cuda.h>
#include <stdint.h>

#define SPIN_LIMIT (1 << 17)

constexpr int RV = 704;
struct __align__(4096) Exch {
    uint4 o[5 * 128 * 256];
    uint4 halo[112 * 160];
    uint4 stats[8][2056];
    uint4 cand[8][128 * 20 + 8];
    uint4 ra[64][24];
    uint4 pad[128 * RV - (128 * 256 + 112 * 160 + 8 * 2056 + 8 * (128 * 20 + 8) + 64 * 24)];
};
struct __align__(4096) Scratch {
    Exch x;
    uint4 tab[60][72];
    unsigned cnt;
};
__device__ Scratch g_s;
#define STAMP(n)
#define GSTAMP(n)
#define STAMPT(n, t)

constexpr uint32_t OFF_W = 163840, WST = 15360;
constexpr uint32_t OFF_WM = OFF_W + 2 * WST;
constexpr uint32_t OFF_FF = OFF_WM + 20480;
constexpr uint32_t OFF_P8 = 131072, VP = 176;
constexpr uint32_t OFF_WD = 129024, OFF_WG = 184320;
constexpr uint32_t OFF_TAB = 225280;
constexpr uint32_t OFF_RED = OFF_TAB + 2560;
constexpr uint32_t OFF_EP = OFF_TAB + 4096;
constexpr uint32_t EP_GD = 1344, EP_US = 1376;
constexpr uint32_t OFF_BAR = OFF_EP + 1488;
constexpr uint32_t OFF_PROF = OFF_BAR + 640;
constexpr uint32_t SMEM_BYTES = OFF_PROF + 128;
enum { B_XF = 0, B_WF = 10, B_WO0 = 30, B_WO, B_FG, B_FD, B_TB, B_HL = B_TB + 4, B_G0 = B_HL + 8, B_RDY, B_WIN, B_EP, B_EP2, B_EP3, B_G2, B_G3, B_G4, B_WE = 55, B_T0 = B_WE + 19 };
#define SPLIT 1
#define ELD 4
#define D_2 0
#define CPF 32
#define D_ST 400
#define D_REC 300
#define D_O 300
#define D_H 300
#define WO_MASK 0x1f5000
#define P_TAB 100
#define LAG 2
#define XWAIT 2
#define FD_AT 2
#define GU_MASK 0xaa00
#define TB_GO B_HL
#define TB_GO2 B_G2
#define TDELAY 3700
#define PFN 5
#define PF0 1
#define YSLEEP 300
#define MPF0 6
#define XDELAY 600
#define RSLEEP 40
#define HALO_GO B_G0
constexpr uint32_t SM0 = 1024;
#define BAR0(i) (SM0 + OFF_BAR + 8 * (i))
#define BAR(i) (sm + OFF_BAR + 8 * (i))

__device__ __forceinline__ uint32_t smem_u32(const void* p) { return (uint32_t)__cvta_generic_to_shared(p); }
__device__ __forceinline__ void mbar_init(uint32_t b, int cnt) { asm volatile("mbarrier.init.shared::cta.b64 [%0], %1;" ::"r"(b), "r"(cnt) : "memory"); }
__device__ __forceinline__ void mbar_expect_tx(uint32_t b, uint32_t bytes) { asm volatile("mbarrier.arrive.expect_tx.shared::cta.b64 _, [%0], %1;" ::"r"(b), "r"(bytes) : "memory"); }
__device__ __forceinline__ void mbar_arrive(uint32_t b) { asm volatile("mbarrier.arrive.shared::cta.b64 _, [%0];" ::"r"(b) : "memory"); }
__device__ __forceinline__ bool mbar_try(uint32_t b, uint32_t par) {
    uint32_t ok;
    asm volatile("{.reg .pred p; mbarrier.try_wait.parity.shared::cta.b64 p, [%1], %2; selp.u32 %0, 1, 0, p;}" : "=r"(ok) : "r"(b), "r"(par) : "memory");
    return ok;
}
__device__ __forceinline__ void mbar_wait(uint32_t b, uint32_t par) {
    asm volatile("{.reg .pred p;\nW: mbarrier.try_wait.parity.shared::cta.b64 p, [%0], %1;\n@!p bra W;}" ::"r"(b), "r"(par) : "memory");
}
__device__ __forceinline__ void bar_sync(int id, int n) { asm volatile("bar.sync %0, %1;" ::"r"(id), "r"(n) : "memory"); }
__device__ __forceinline__ void tma2d(uint32_t dst, const CUtensorMap* m, int c0, int c1, uint32_t bar) {
    asm volatile("cp.async.bulk.tensor.2d.shared::cluster.global.mbarrier::complete_tx::bytes [%0], [%1, {%3, %4}], [%2];" ::"r"(dst), "l"(m), "r"(bar), "r"(c0), "r"(c1) : "memory");
}
__device__ __forceinline__ void tma3d(uint32_t dst, const CUtensorMap* m, int c0, int c1, int c2, uint32_t bar) {
    asm volatile("cp.async.bulk.tensor.3d.shared::cluster.global.mbarrier::complete_tx::bytes [%0], [%1, {%3, %4, %5}], [%2];" ::"r"(dst), "l"(m), "r"(bar), "r"(c0), "r"(c1), "r"(c2) : "memory");
}
__device__ __forceinline__ void l2_prefetch(const void* p, uint32_t bytes) { asm volatile("cp.async.bulk.prefetch.L2.global [%0], %1;" ::"l"(p), "r"(bytes) : "memory"); }
__device__ __forceinline__ void wg_fence() { asm volatile("wgmma.fence.sync.aligned;" ::: "memory"); }
__device__ __forceinline__ void wg_commit() { asm volatile("wgmma.commit_group.sync.aligned;" ::: "memory"); }
template <int N> __device__ __forceinline__ void wg_wait() { asm volatile("wgmma.wait_group.sync.aligned %0;" ::"n"(N) : "memory"); }
__device__ __forceinline__ void ldsm4(uint32_t* r, uint32_t addr) { asm volatile("ldmatrix.sync.aligned.m8n8.x4.shared.b16 {%0,%1,%2,%3}, [%4];" : "=r"(r[0]), "=r"(r[1]), "=r"(r[2]), "=r"(r[3]) : "r"(addr) : "memory"); }
__device__ __forceinline__ void ldsm4t(uint32_t* r, uint32_t addr) { asm volatile("ldmatrix.sync.aligned.m8n8.x4.trans.shared.b16 {%0,%1,%2,%3}, [%4];" : "=r"(r[0]), "=r"(r[1]), "=r"(r[2]), "=r"(r[3]) : "r"(addr) : "memory"); }
__device__ __forceinline__ void stsm4(uint32_t addr, const uint32_t* r) { asm volatile("stmatrix.sync.aligned.m8n8.x4.shared.b16 [%4], {%0,%1,%2,%3};" ::"r"(r[0]), "r"(r[1]), "r"(r[2]), "r"(r[3]), "r"(addr) : "memory"); }
__device__ __forceinline__ void lds4(uint32_t* r, uint32_t addr) { asm volatile("ld.shared.v4.u32 {%0,%1,%2,%3}, [%4];" : "=r"(r[0]), "=r"(r[1]), "=r"(r[2]), "=r"(r[3]) : "r"(addr) : "memory"); }
__device__ __forceinline__ void sts4(uint32_t addr, const uint32_t* r) { asm volatile("st.shared.v4.u32 [%4], {%0,%1,%2,%3};" ::"r"(r[0]), "r"(r[1]), "r"(r[2]), "r"(r[3]), "r"(addr) : "memory"); }
__device__ __forceinline__ float2 lds2f(uint32_t addr) { float2 v; asm volatile("ld.shared.v2.f32 {%0,%1}, [%2];" : "=f"(v.x), "=f"(v.y) : "r"(addr) : "memory"); return v; }
__device__ __forceinline__ void sts1f(uint32_t addr, float v) { asm volatile("st.shared.f32 [%0], %1;" ::"r"(addr), "f"(v) : "memory"); }
__device__ __forceinline__ void sts1(uint32_t addr, uint32_t v) { asm volatile("st.shared.u32 [%0], %1;" ::"r"(addr), "r"(v) : "memory"); }
__device__ __forceinline__ void ldg4_rlx(uint32_t* r, const void* p) { asm volatile("{.reg .b128 t; ld.relaxed.gpu.global.b128 t, [%4]; mov.b128 {%0,%1,%2,%3}, t;}" : "=r"(r[0]), "=r"(r[1]), "=r"(r[2]), "=r"(r[3]) : "l"(p) : "memory"); }
__device__ __forceinline__ void ldg2_rlx(uint32_t* r, const void* p) { asm volatile("{.reg .b64 t; ld.relaxed.gpu.global.b64 t, [%2]; mov.b64 {%0,%1}, t;}" : "=r"(r[0]), "=r"(r[1]) : "l"(p) : "memory"); }
__device__ __forceinline__ uint32_t ldg1_rlx(const void* p) { uint32_t v; asm volatile("ld.relaxed.gpu.global.u32 %0, [%1];" : "=r"(v) : "l"(p) : "memory"); return v; }
__device__ __forceinline__ void stg4_rlx(void* p, uint32_t a, uint32_t b, uint32_t c, uint32_t d) { asm volatile("{.reg .b128 t; mov.b128 t, {%1,%2,%3,%4}; st.relaxed.gpu.global.b128 [%0], t;}" ::"l"(p), "r"(a), "r"(b), "r"(c), "r"(d) : "memory"); }
__device__ __forceinline__ void stg1_rlx(void* p, uint32_t a) { asm volatile("st.relaxed.gpu.global.u32 [%0], %1;" ::"l"(p), "r"(a) : "memory"); }
__device__ __forceinline__ uint64_t mkdesc(uint32_t addr, uint32_t lbo, uint32_t sbo, uint32_t sw) { return (uint64_t)((addr & 0x3FFFF) >> 4) | ((uint64_t)(lbo >> 4) << 16) | ((uint64_t)(sbo >> 4) << 32) | ((uint64_t)sw << 62); }
__device__ __forceinline__ uint32_t pack2(float lo, float hi) { uint32_t r; asm("cvt.rn.bf16x2.f32 %0, %1, %2;" : "=r"(r) : "f"(hi), "f"(lo)); return r; }
__device__ __forceinline__ float blo(uint32_t v) { return __uint_as_float(v << 16); }
__device__ __forceinline__ float bhi(uint32_t v) { return __uint_as_float(v & 0xffff0000u); }
__device__ __forceinline__ float rbf(float x) { return blo(pack2(x, 0.f)); }
__device__ __forceinline__ uint32_t hf2(uint32_t a, uint32_t b, uint32_t c) { uint32_t r; asm("fma.rn.bf16x2 %0, %1, %2, %3;" : "=r"(r) : "r"(a), "r"(b), "r"(c)); return r; }
__device__ __forceinline__ float ex2(float x) { float r; asm("ex2.approx.ftz.f32 %0, %1;" : "=f"(r) : "f"(x)); return r; }
__device__ __forceinline__ void mma16(float* d, uint32_t a0, uint32_t a1, uint32_t a2, uint32_t a3, uint32_t b0, uint32_t b1) {
    asm("mma.sync.aligned.m16n8k16.row.col.f32.bf16.bf16.f32 {%0,%1,%2,%3}, {%4,%5,%6,%7}, {%8,%9}, {%0,%1,%2,%3};"
                 : "+f"(d[0]), "+f"(d[1]), "+f"(d[2]), "+f"(d[3]) : "r"(a0), "r"(a1), "r"(a2), "r"(a3), "r"(b0), "r"(b1));
}
__device__ __forceinline__ void mma8(float* d, uint32_t a0, uint32_t a1, uint32_t b0) {
    asm("mma.sync.aligned.m16n8k8.row.col.f32.bf16.bf16.f32 {%0,%1,%2,%3}, {%4,%5}, {%6}, {%0,%1,%2,%3};"
                 : "+f"(d[0]), "+f"(d[1]), "+f"(d[2]), "+f"(d[3]) : "r"(a0), "r"(a1), "r"(b0));
}
__device__ __forceinline__ uint32_t fkey(float f) { const uint32_t u = __float_as_uint(f); return u ^ (((int)u >> 31) | 0x80000000u); }
__device__ __forceinline__ float rcp(float x) { float r; asm("rcp.approx.ftz.f32 %0, %1;" : "=f"(r) : "f"(x)); return r; }
__device__ __forceinline__ float sigm(float x) { return rcp(1.f + ex2(x * -1.4426950408889634f)); }
__device__ __forceinline__ void mma16c(float* d, uint32_t a0, uint32_t a1, uint32_t a2, uint32_t a3, uint32_t b0, uint32_t b1, float c0, float c1) {
    asm("mma.sync.aligned.m16n8k16.row.col.f32.bf16.bf16.f32 {%0,%1,%2,%3}, {%4,%5,%6,%7}, {%8,%9}, {%10,%11,%12,%12};"
                 : "=f"(d[0]), "=f"(d[1]), "=f"(d[2]), "=f"(d[3]) : "r"(a0), "r"(a1), "r"(a2), "r"(a3), "r"(b0), "r"(b1), "f"(c0), "f"(c1), "f"(0.f));
}
__device__ __forceinline__ void stsm2(uint32_t addr, uint32_t a, uint32_t b) { asm volatile("stmatrix.sync.aligned.m8n8.x2.shared.b16 [%2], {%0,%1};" ::"r"(a), "r"(b), "r"(addr) : "memory"); }
__device__ __forceinline__ void lds2(uint32_t* r, uint32_t addr) { asm volatile("ld.shared.v2.u32 {%0,%1}, [%2];" : "=r"(r[0]), "=r"(r[1]) : "r"(addr) : "memory"); }
__device__ __forceinline__ void sts2(uint32_t addr, uint32_t a, uint32_t b) { asm volatile("st.shared.v2.u32 [%2], {%0,%1};" ::"r"(a), "r"(b), "r"(addr) : "memory"); }
__device__ __forceinline__ uint32_t lds1(uint32_t addr) { uint32_t v; asm volatile("ld.shared.u32 %0, [%1];" : "=r"(v) : "r"(addr) : "memory"); return v; }
__device__ __forceinline__ bool elect1() { uint32_t p; asm volatile("{.reg .pred P; elect.sync _|P, 0xffffffff; selp.u32 %0, 1, 0, P;}" : "=r"(p)); return p; }
__device__ __forceinline__ void tma2d_mc(uint32_t dst, const CUtensorMap* m, int c0, int c1, uint32_t bar) {
    asm volatile("cp.async.bulk.tensor.2d.shared::cluster.global.mbarrier::complete_tx::bytes.multicast::cluster [%0], [%1, {%3, %4}], [%2], %5;" ::"r"(dst), "l"(m), "r"(bar), "r"(c0), "r"(c1), "h"((unsigned short)3) : "memory");
}
__device__ __forceinline__ void tma3d_mc(uint32_t dst, const CUtensorMap* m, int c0, int c1, int c2, uint32_t bar) {
    asm volatile("cp.async.bulk.tensor.3d.shared::cluster.global.mbarrier::complete_tx::bytes.multicast::cluster [%0], [%1, {%3, %4, %5}], [%2], %6;" ::"r"(dst), "l"(m), "r"(bar), "r"(c0), "r"(c1), "r"(c2), "h"((unsigned short)3) : "memory");
}
__device__ __forceinline__ void tma4d_mc(uint32_t dst, const CUtensorMap* m, int c0, int c1, int c2, int c3, uint32_t bar) {
    asm volatile("cp.async.bulk.tensor.4d.shared::cluster.global.mbarrier::complete_tx::bytes.multicast::cluster [%0], [%1, {%3, %4, %5, %6}], [%2], %7;" ::"r"(dst), "l"(m), "r"(bar), "r"(c0), "r"(c1), "r"(c2), "r"(c3), "h"((unsigned short)3) : "memory");
}
__device__ __forceinline__ void mbar_arrive_cl(uint32_t b) { asm volatile("mbarrier.arrive.shared::cluster.b64 _, [%0];" ::"r"(b) : "memory"); }
__device__ __forceinline__ uint32_t hm2(uint32_t a, uint32_t b) { uint32_t r; asm("mul.rn.bf16x2 %0, %1, %2;" : "=r"(r) : "r"(a), "r"(b)); return r; }
__device__ __forceinline__ uint32_t clock32() { uint32_t c; asm volatile("mov.u32 %0, %clock;" : "=r"(c)); return c; }
__device__ __forceinline__ float rsq(float x) { float r; asm("rsqrt.approx.ftz.f32 %0, %1;" : "=f"(r) : "f"(x)); return r; }
__device__ __forceinline__ void pause_until(uint32_t t0, uint32_t n) {
    asm volatile("{.reg .pred p; .reg .u32 t;\nP: mov.u32 t, %clock; sub.u32 t, t, %0; setp.lt.u32 p, t, %1;\n@p bra.uni P;}" ::"r"(t0), "r"(n) : "memory");
}
__device__ __forceinline__ void pause(uint32_t n) { if (n) { const uint32_t t = clock32(); while (clock32() - t < n) {} } }
__device__ __forceinline__ uint32_t wbuf(int it) {
    const uint32_t v = it < 4 ? it + 8 : (uint32_t)(0x8302418302b1a908ull >> (4 * it - 16)) & 15;
    return v * WST + (v >> 3) * (OFF_W - 8 * WST);
}
__device__ __forceinline__ uint32_t wobuf(int w) { return ((0x30241765u >> (4 * w)) & 7) * WST; }
__device__ __forceinline__ uint32_t inc(uint32_t v) { uint32_t r; asm volatile("{.reg .u32 t; or.b32 t, %1, 255; add.u32 %0, t, 1;}" : "=r"(r) : "r"(v)); return r; }
__device__ __forceinline__ uint32_t ldg1_acq(const void* p) { uint32_t v; asm volatile("ld.acquire.gpu.global.u32 %0, [%1];" : "=r"(v) : "l"(p) : "memory"); return v; }
__device__ __forceinline__ void tma3d_st(const CUtensorMap* m, int c0, int c1, int c2, uint32_t src) {
    asm volatile("cp.async.bulk.tensor.3d.global.shared::cta.bulk_group [%0, {%2, %3, %4}], [%1];" ::"l"(m), "r"(src), "r"(c0), "r"(c1), "r"(c2) : "memory");
}
__device__ __forceinline__ uint32_t nz(uint32_t v) { uint32_t r; asm("max.u32 %0, %1, 1;" : "=r"(r) : "r"(v)); return r; }
__device__ __forceinline__ uint32_t tagw(uint32_t w, uint32_t tc) { return ((w & 0x8000ffffu) | min(max(w & 0x7fff0000u, 0x20000000u), 0x5fff0000u)) + tc; }
template <int S_> __device__ __forceinline__ void await7(uint32_t (*r)[4], const char* const* p, uint32_t fz, uint32_t stale) {
    if (S_ == 0) asm volatile("{.reg .b128 t; .reg .pred p; .reg .u32 m, k, n;\nmov.u32 n, %clock; or.b32 n, n, %37; shr.u32 n, n, 31;\nL:\n"
        "min.u32 m, %0, %4; min.u32 m, m, %8; min.u32 m, m, %12; min.u32 m, m, %16; min.u32 m, m, %20; min.u32 m, m, %24;\n"
        "setp.eq.u32 p, m, 0; vote.sync.any.pred p, p, 0xffffffff; add.u32 n, n, 1; setp.lt.and.u32 p, n, %36, p;\n@!p bra.uni D;\n"
        "setp.eq.u32 p, %0, 0; mov.b128 t, {%0,%1,%2,%3}; @p ld.relaxed.gpu.global.b128 t, [%28+%35]; mov.b128 {%0,%1,%2,%3}, t;\n"
        "setp.eq.u32 p, %4, 0; mov.b128 t, {%4,%5,%6,%7}; @p ld.relaxed.gpu.global.b128 t, [%29+%35]; mov.b128 {%4,%5,%6,%7}, t;\n"
        "setp.eq.u32 p, %8, 0; mov.b128 t, {%8,%9,%10,%11}; @p ld.relaxed.gpu.global.b128 t, [%30+%35]; mov.b128 {%8,%9,%10,%11}, t;\n"
        "setp.eq.u32 p, %12, 0; mov.b128 t, {%12,%13,%14,%15}; @p ld.relaxed.gpu.global.b128 t, [%31+%35]; mov.b128 {%12,%13,%14,%15}, t;\n"
        "setp.eq.u32 p, %16, 0; mov.b128 t, {%16,%17,%18,%19}; @p ld.relaxed.gpu.global.b128 t, [%32+%35]; mov.b128 {%16,%17,%18,%19}, t;\n"
        "setp.eq.u32 p, %20, 0; mov.b128 t, {%20,%21,%22,%23}; @p ld.relaxed.gpu.global.b128 t, [%33+%35]; mov.b128 {%20,%21,%22,%23}, t;\n"
        "setp.eq.u32 p, %24, 0; mov.b128 t, {%24,%25,%26,%27}; @p ld.relaxed.gpu.global.b128 t, [%34+%35]; mov.b128 {%24,%25,%26,%27}, t;\n"
        "bra.uni L;\nD:}"
        : "+r"(r[0][0]), "+r"(r[0][1]), "+r"(r[0][2]), "+r"(r[0][3]), "+r"(r[1][0]), "+r"(r[1][1]), "+r"(r[1][2]), "+r"(r[1][3]), "+r"(r[2][0]), "+r"(r[2][1]), "+r"(r[2][2]), "+r"(r[2][3]), "+r"(r[3][0]), "+r"(r[3][1]), "+r"(r[3][2]), "+r"(r[3][3]), "+r"(r[4][0]), "+r"(r[4][1]), "+r"(r[4][2]), "+r"(r[4][3]), "+r"(r[5][0]), "+r"(r[5][1]), "+r"(r[5][2]), "+r"(r[5][3]), "+r"(r[6][0]), "+r"(r[6][1]), "+r"(r[6][2]), "+r"(r[6][3])
        : "l"(p[0]), "l"(p[1]), "l"(p[2]), "l"(p[3]), "l"(p[4]), "l"(p[5]), "l"(p[6]), "n"((4 - S_) * 524288), "n"(SPIN_LIMIT), "r"(fz), "r"(stale) : "memory");
    else asm volatile("{.reg .b128 t; .reg .pred p; .reg .u32 m, k, n;\nmov.u32 n, %clock; or.b32 n, n, %37; shr.u32 n, n, 31;\nL:\n"
        "xor.b32 m, %0, %38; xor.b32 k, %4, %38; and.b32 m, m, k; xor.b32 k, %8, %38; and.b32 m, m, k; xor.b32 k, %12, %38; and.b32 m, m, k; xor.b32 k, %16, %38; and.b32 m, m, k;\n"
        "xor.b32 k, %20, %38; and.b32 m, m, k; xor.b32 k, %24, %38; and.b32 m, m, k; and.b32 m, m, 0x40000000;\n"
        "setp.eq.u32 p, m, 0; vote.sync.any.pred p, p, 0xffffffff; add.u32 n, n, 1; setp.lt.and.u32 p, n, %36, p;\n@!p bra.uni D;\n"
        "xor.b32 k, %0, %38; and.b32 k, k, 0x40000000; setp.eq.u32 p, k, 0; mov.b128 t, {%0,%1,%2,%3}; @p ld.relaxed.gpu.global.b128 t, [%28+%35]; mov.b128 {%0,%1,%2,%3}, t;\n"
        "xor.b32 k, %4, %38; and.b32 k, k, 0x40000000; setp.eq.u32 p, k, 0; mov.b128 t, {%4,%5,%6,%7}; @p ld.relaxed.gpu.global.b128 t, [%29+%35]; mov.b128 {%4,%5,%6,%7}, t;\n"
        "xor.b32 k, %8, %38; and.b32 k, k, 0x40000000; setp.eq.u32 p, k, 0; mov.b128 t, {%8,%9,%10,%11}; @p ld.relaxed.gpu.global.b128 t, [%30+%35]; mov.b128 {%8,%9,%10,%11}, t;\n"
        "xor.b32 k, %12, %38; and.b32 k, k, 0x40000000; setp.eq.u32 p, k, 0; mov.b128 t, {%12,%13,%14,%15}; @p ld.relaxed.gpu.global.b128 t, [%31+%35]; mov.b128 {%12,%13,%14,%15}, t;\n"
        "xor.b32 k, %16, %38; and.b32 k, k, 0x40000000; setp.eq.u32 p, k, 0; mov.b128 t, {%16,%17,%18,%19}; @p ld.relaxed.gpu.global.b128 t, [%32+%35]; mov.b128 {%16,%17,%18,%19}, t;\n"
        "xor.b32 k, %20, %38; and.b32 k, k, 0x40000000; setp.eq.u32 p, k, 0; mov.b128 t, {%20,%21,%22,%23}; @p ld.relaxed.gpu.global.b128 t, [%33+%35]; mov.b128 {%20,%21,%22,%23}, t;\n"
        "xor.b32 k, %24, %38; and.b32 k, k, 0x40000000; setp.eq.u32 p, k, 0; mov.b128 t, {%24,%25,%26,%27}; @p ld.relaxed.gpu.global.b128 t, [%34+%35]; mov.b128 {%24,%25,%26,%27}, t;\n"
        "bra.uni L;\nD:}"
        : "+r"(r[0][0]), "+r"(r[0][1]), "+r"(r[0][2]), "+r"(r[0][3]), "+r"(r[1][0]), "+r"(r[1][1]), "+r"(r[1][2]), "+r"(r[1][3]), "+r"(r[2][0]), "+r"(r[2][1]), "+r"(r[2][2]), "+r"(r[2][3]), "+r"(r[3][0]), "+r"(r[3][1]), "+r"(r[3][2]), "+r"(r[3][3]), "+r"(r[4][0]), "+r"(r[4][1]), "+r"(r[4][2]), "+r"(r[4][3]), "+r"(r[5][0]), "+r"(r[5][1]), "+r"(r[5][2]), "+r"(r[5][3]), "+r"(r[6][0]), "+r"(r[6][1]), "+r"(r[6][2]), "+r"(r[6][3])
        : "l"(p[0]), "l"(p[1]), "l"(p[2]), "l"(p[3]), "l"(p[4]), "l"(p[5]), "l"(p[6]), "n"((4 - S_) * 524288), "n"(SPIN_LIMIT), "r"(fz), "r"(stale) : "memory");
}
template <class T> __device__ __forceinline__ T* pinp(T* p) { return (T*)__shfl_xor_sync(~0u, (unsigned long long)p, 0); }
__device__ __forceinline__ float fsel(bool c, float a, float b) { float r; asm("{.reg .pred p; setp.ne.u32 p, %3, 0; selp.f32 %0, %1, %2, p;}" : "=f"(r) : "f"(a), "f"(b), "r"((int)c)); return r; }
__device__ __forceinline__ void stg4_if(bool c, void* p, uint32_t a, uint32_t b, uint32_t d, uint32_t e) {
    asm volatile("{.reg .b128 t; .reg .pred p; setp.ne.u32 p, %5, 0; mov.b128 t, {%1,%2,%3,%4}; @p st.relaxed.gpu.global.b128 [%0], t;}" ::"l"(p), "r"(a), "r"(b), "r"(d), "r"(e), "r"((int)c) : "memory");
}
__device__ __forceinline__ void stg1_if(bool c, void* p, uint32_t a) {
    asm volatile("{.reg .pred p; setp.ne.u32 p, %2, 0; @p st.relaxed.gpu.global.u32 [%0], %1;}" ::"l"(p), "r"(a), "r"((int)c) : "memory");
}
__device__ __forceinline__ void ldg4_again(uint32_t* r, const void* p) {
    asm volatile("{.reg .b128 t; .reg .pred p; setp.eq.u32 p, %3, 0; mov.b128 t, {%0,%1,%2,%3}; @p ld.relaxed.gpu.global.b128 t, [%4]; mov.b128 {%0,%1,%2,%3}, t;}"
                 : "+r"(r[0]), "+r"(r[1]), "+r"(r[2]), "+r"(r[3]) : "l"(p) : "memory");
}
__device__ __forceinline__ void wgmma_rs_n192(float* d, const uint32_t* a, uint64_t bdesc, int accum) {
    asm volatile("{.reg .pred p; setp.ne.b32 p, %101, 0; wgmma.mma_async.sync.aligned.m64n192k16.f32.bf16.bf16 {%0,%1,%2,%3,%4,%5,%6,%7,%8,%9,%10,%11,%12,%13,%14,%15,%16,%17,%18,%19,%20,%21,%22,%23,%24,%25,%26,%27,%28,%29,%30,%31,%32,%33,%34,%35,%36,%37,%38,%39,%40,%41,%42,%43,%44,%45,%46,%47,%48,%49,%50,%51,%52,%53,%54,%55,%56,%57,%58,%59,%60,%61,%62,%63,%64,%65,%66,%67,%68,%69,%70,%71,%72,%73,%74,%75,%76,%77,%78,%79,%80,%81,%82,%83,%84,%85,%86,%87,%88,%89,%90,%91,%92,%93,%94,%95}, {%96,%97,%98,%99}, %100, p, 1, 1, 1;}"
        : "+f"(d[0]),"+f"(d[1]),"+f"(d[2]),"+f"(d[3]),"+f"(d[4]),"+f"(d[5]),"+f"(d[6]),"+f"(d[7]),"+f"(d[8]),"+f"(d[9]),"+f"(d[10]),"+f"(d[11]),"+f"(d[12]),"+f"(d[13]),"+f"(d[14]),"+f"(d[15]),"+f"(d[16]),"+f"(d[17]),"+f"(d[18]),"+f"(d[19]),"+f"(d[20]),"+f"(d[21]),"+f"(d[22]),"+f"(d[23]),"+f"(d[24]),"+f"(d[25]),"+f"(d[26]),"+f"(d[27]),"+f"(d[28]),"+f"(d[29]),"+f"(d[30]),"+f"(d[31]),"+f"(d[32]),"+f"(d[33]),"+f"(d[34]),"+f"(d[35]),"+f"(d[36]),"+f"(d[37]),"+f"(d[38]),"+f"(d[39]),"+f"(d[40]),"+f"(d[41]),"+f"(d[42]),"+f"(d[43]),"+f"(d[44]),"+f"(d[45]),"+f"(d[46]),"+f"(d[47]),"+f"(d[48]),"+f"(d[49]),"+f"(d[50]),"+f"(d[51]),"+f"(d[52]),"+f"(d[53]),"+f"(d[54]),"+f"(d[55]),"+f"(d[56]),"+f"(d[57]),"+f"(d[58]),"+f"(d[59]),"+f"(d[60]),"+f"(d[61]),"+f"(d[62]),"+f"(d[63]),"+f"(d[64]),"+f"(d[65]),"+f"(d[66]),"+f"(d[67]),"+f"(d[68]),"+f"(d[69]),"+f"(d[70]),"+f"(d[71]),"+f"(d[72]),"+f"(d[73]),"+f"(d[74]),"+f"(d[75]),"+f"(d[76]),"+f"(d[77]),"+f"(d[78]),"+f"(d[79]),"+f"(d[80]),"+f"(d[81]),"+f"(d[82]),"+f"(d[83]),"+f"(d[84]),"+f"(d[85]),"+f"(d[86]),"+f"(d[87]),"+f"(d[88]),"+f"(d[89]),"+f"(d[90]),"+f"(d[91]),"+f"(d[92]),"+f"(d[93]),"+f"(d[94]),"+f"(d[95])
        : "r"(a[0]), "r"(a[1]), "r"(a[2]), "r"(a[3]), "l"(bdesc), "r"(accum));
}
__device__ __forceinline__ void wgmma_rs_n48(float* d, const uint32_t* a, uint64_t bdesc, int accum) {
    asm volatile("{.reg .pred p; setp.ne.b32 p, %29, 0; wgmma.mma_async.sync.aligned.m64n48k16.f32.bf16.bf16 {%0,%1,%2,%3,%4,%5,%6,%7,%8,%9,%10,%11,%12,%13,%14,%15,%16,%17,%18,%19,%20,%21,%22,%23}, {%24,%25,%26,%27}, %28, p, 1, 1, 1;}"
        : "+f"(d[0]),"+f"(d[1]),"+f"(d[2]),"+f"(d[3]),"+f"(d[4]),"+f"(d[5]),"+f"(d[6]),"+f"(d[7]),"+f"(d[8]),"+f"(d[9]),"+f"(d[10]),"+f"(d[11]),"+f"(d[12]),"+f"(d[13]),"+f"(d[14]),"+f"(d[15]),"+f"(d[16]),"+f"(d[17]),"+f"(d[18]),"+f"(d[19]),"+f"(d[20]),"+f"(d[21]),"+f"(d[22]),"+f"(d[23])
        : "r"(a[0]), "r"(a[1]), "r"(a[2]), "r"(a[3]), "l"(bdesc), "r"(accum));
}
__device__ __forceinline__ void wgmma_rs_n80(float* d, const uint32_t* a, uint64_t bdesc, int accum) {
    asm volatile("{.reg .pred p; setp.ne.b32 p, %45, 0; wgmma.mma_async.sync.aligned.m64n80k16.f32.bf16.bf16 {%0,%1,%2,%3,%4,%5,%6,%7,%8,%9,%10,%11,%12,%13,%14,%15,%16,%17,%18,%19,%20,%21,%22,%23,%24,%25,%26,%27,%28,%29,%30,%31,%32,%33,%34,%35,%36,%37,%38,%39}, {%40,%41,%42,%43}, %44, p, 1, 1, 1;}"
        : "+f"(d[0]),"+f"(d[1]),"+f"(d[2]),"+f"(d[3]),"+f"(d[4]),"+f"(d[5]),"+f"(d[6]),"+f"(d[7]),"+f"(d[8]),"+f"(d[9]),"+f"(d[10]),"+f"(d[11]),"+f"(d[12]),"+f"(d[13]),"+f"(d[14]),"+f"(d[15]),"+f"(d[16]),"+f"(d[17]),"+f"(d[18]),"+f"(d[19]),"+f"(d[20]),"+f"(d[21]),"+f"(d[22]),"+f"(d[23]),"+f"(d[24]),"+f"(d[25]),"+f"(d[26]),"+f"(d[27]),"+f"(d[28]),"+f"(d[29]),"+f"(d[30]),"+f"(d[31]),"+f"(d[32]),"+f"(d[33]),"+f"(d[34]),"+f"(d[35]),"+f"(d[36]),"+f"(d[37]),"+f"(d[38]),"+f"(d[39])
        : "r"(a[0]), "r"(a[1]), "r"(a[2]), "r"(a[3]), "l"(bdesc), "r"(accum));
}

__global__ void __cluster_dims__(2, 1, 1) __launch_bounds__(384, 1)
fused_kernel(const __nv_bfloat16* __restrict__ wmod, const __nv_bfloat16* __restrict__ cvec, Scratch* __restrict__ S,
             const __nv_bfloat16* __restrict__ wqkv, const __nv_bfloat16* __restrict__ wo, __nv_bfloat16* __restrict__ out,
             const __nv_bfloat16* __restrict__ wr, const __nv_bfloat16* __restrict__ wg, const __nv_bfloat16* __restrict__ wu,
             const __nv_bfloat16* __restrict__ wd,
             const __grid_constant__ CUtensorMap mm, const __grid_constant__ CUtensorMap mx, const __grid_constant__ CUtensorMap mw,
             const __grid_constant__ CUtensorMap mt, const __grid_constant__ CUtensorMap mo, const __grid_constant__ CUtensorMap mg,
             const __grid_constant__ CUtensorMap mu, const __grid_constant__ CUtensorMap md,
             const __grid_constant__ CUtensorMap mw2, const __grid_constant__ CUtensorMap mout,
             const __grid_constant__ CUtensorMap mo2) {
    extern __shared__ __align__(1024) char sm_raw[];
    const int bid = blockIdx.x;
    const uint32_t sm = ((bid & 1) << 24) + SM0;
    STAMP(30);
    const uint32_t t_start = clock32();
    if (bid < CPF && threadIdx.x == 0)
        asm volatile("cp.async.bulk.prefetch.tensor.2d.L2.global [%0, {%1, %2}];" ::"l"(&mm), "r"((bid & 1) * 640 + (bid >> 4) * 64), "r"(((bid >> 1) & 7) * 80) : "memory");
    const int cl = bid >> 1, rank = bid & 1, c7 = ((cl - 36) * 37) >> 8;
    const int grp = cl < 4 ? 0 : (cl < 36 ? (cl - 4) & 7 : cl - 35 - 7 * c7);
    const int ti = grp * 2 + rank;
    auto ldx = [&](int c) { mbar_expect_tx(BAR(B_XF + c), 16384); tma3d(sm + c * 16384, &mx, c * 64, ti >> 3, (ti & 7) * 128, BAR(B_XF + c)); };
    if (threadIdx.x == 256 && bid < 128) {
        mbar_init(BAR(B_XF), 1); mbar_init(BAR(B_XF + 1), 1);
        pause_until(t_start, XDELAY);
        ldx(0); ldx(1);
        STAMPT(22, 256);
#pragma unroll
        for (int i = 2; i < 10; i++) mbar_init(BAR(B_XF + i), 1);
        mbar_init(BAR(B_T0), 1);
        asm volatile("fence.mbarrier_init.release.cluster;" ::: "memory");
        ldx(2); ldx(3); ldx(4);
    }
    const int warp = __shfl_sync(~0u, threadIdx.x >> 5, 0);

#define PIN(v) __shfl_xor_sync(~0u, (v), 0)
#define LANE_VARS const int tid = PIN(threadIdx.x), lane = tid & 31, g = lane >> 2, q = lane & 3; \
    const uint32_t frow = (lane & 7) + (lane >> 4) * 8, fh = (lane >> 3) & 1;
    if (bid >= 128) {
        LANE_VARS
        const int h = bid - 128;
        if (warp >= 8) {
            if (warp == 8) return;
            const int t = tid - 288;
            if (t < 90) stg4_rlx(&S->tab[(5 + t / 9) * 4 + h][t % 9], 0u, 0u, 0u, 0u);
            __syncwarp();
            asm volatile("bar.arrive 1, 352;" ::: "memory");
            bar_sync(2, 96);
            if (t == 0) asm volatile("red.release.gpu.global.add.u32 [%0], 32;" ::"l"(&S->cnt) : "memory");
            return;
        }
        const uint32_t slot = sm + warp * 20480, bar = BAR(warp * 2);
        auto column = [&](int job) {
            const int n = job * 4 + h;
            return job < 10 ? ((h & 1) ? (job < 5 ? 10 : 30) : (job < 5 ? 0 : 10)) + (n >> 1) : (n < 50 ? n - 10 : n);
        };
        auto load = [&](int job) {
            mbar_expect_tx(bar + (job & 1) * 8, 10240);
            tma2d(slot + (job & 1) * 10240, &mm, column(job) * 64, warp * 80, bar + (job & 1) * 8);
        };
        if (elect1()) { mbar_init(bar, 1); mbar_init(bar + 8, 1); load(0); }
        __syncwarp();
        uint32_t b[10];
#pragma unroll
        for (int s = 0; s < 10; s++) b[s] = ldg1_rlx((const uint32_t*)cvec + warp * 40 + s * 4 + q);
        if (lane < 8 && warp < 5) stg4_rlx(&S->tab[warp * 4 + h][lane], 0u, 0u, 0u, 0u);
#pragma unroll
        for (int s = 0; s < 10; s++) b[s] = pack2(blo(b[s]) * sigm(blo(b[s])), bhi(b[s]) * sigm(bhi(b[s])));
        const uint32_t fa = slot + frow * 128 + ((fh ^ (lane & 7)) << 4);
        const int c0 = (lane >> 3) * 16 + (lane & 1) * 8 + (lane & 6);
#pragma unroll 1
        for (int job = 0; job < 15; job++) {
            uint32_t w2 = 0;
            if (job >= 5) w2 = ldg1_rlx(wr + (column(job) % 10) * 64 + c0);

            mbar_wait(bar + (job & 1) * 8, (job >> 1) & 1);
            if (job == 0) { if (elect1()) load(1); __syncwarp(); }
            float d[4][4] = {};
#pragma unroll
            for (int s = 0; s < 5; s++) {
#pragma unroll
                for (int m = 0; m < 4; m++) { uint32_t a[4]; ldsm4t(a, (fa ^ (m * 32)) + (job & 1) * 10240 + s * 2048); mma16(d[m], a[0], a[1], a[2], a[3], b[2 * s], b[2 * s + 1]); }
            }
            const uint32_t red = sm + OFF_W + (job & 1) * 2048;
            sts1f(red + (warp * 64 + q * 8 + g) * 4, q == 0 ? d[0][0] : (q == 1 ? d[0][2] : (q == 2 ? d[1][0] : d[1][2])));
            sts1f(red + (warp * 64 + 32 + q * 8 + g) * 4, q == 0 ? d[2][0] : (q == 1 ? d[2][2] : (q == 2 ? d[3][0] : d[3][2])));
            __syncwarp();
            if (job < 13 && elect1()) load(job + 2);
            __syncwarp();
            bar_sync(0, 256);
            if (job == 5) bar_sync(1, 352);
            if (warp == (job & 7)) {
                float y0 = 0.f, y1 = 0.f;
#pragma unroll
                for (int w = 0; w < 8; w++) { const float2 v = lds2f(red + (w * 64 + c0) * 4); y0 += v.x; y1 += v.y; }
                const uint32_t t = hf2(pack2(y0, y1), 0x3f803f80u, ((h & 1) && job < 10) ? 0x3f803f80u : 0x80008000u);
                uint32_t* const p = (uint32_t*)&S->tab[job * 4 + h][0];
                stg1_rlx(p + lane, nz(t));
                float dot = fmaf(blo(t), blo(w2), bhi(t) * bhi(w2));
#pragma unroll
                for (int o = 16; o; o >>= 1) dot += __shfl_xor_sync(~0u, dot, o);
                if (lane == 0) stg1_rlx(p + 32, dot == 0.f ? 0x80000000u : __float_as_uint(dot));
            }
            if (job == 0) STAMP(27);
            if (job == 8) STAMP(28);
        }
        STAMP(17);
        return;
    }
    uint32_t ep0;
    if (__builtin_expect(warp == 8, 1)) {
        asm volatile("barrier.cluster.arrive.relaxed.aligned;" ::: "memory");
        if (elect1()) {
#pragma unroll 1
            for (int c = 5; c < 10; c++) ldx(c);
        }
        __syncwarp();
    } else {
        if (warp < 8) {
            if (elect1()) {
#pragma unroll
                for (int i = 0; i < 8; i++) { const int b = B_WF + warp * 8 + i; mbar_init(BAR(b), b >= B_WE ? 16 : (b >= B_G2 ? 8 : (b >= B_EP ? 2 : (b == B_WO ? 7 : 1)))); }
                asm volatile("fence.mbarrier_init.release.cluster;" ::: "memory");
            }
            __syncwarp();
        }
        if (warp == 9) ep0 = ldg1_rlx(&S->cnt);
        asm volatile("barrier.cluster.arrive.relaxed.aligned;" ::: "memory");
    }
    const int sl = cl < 4 ? 4 + cl : (cl < 36 ? (cl - 4) >> 3 : 4 + c7);
    const int j = sl ^ (((sl + 2) >> 2) & 1), role = ti * 8 + j, odd = j & 1;
    const int fi = j * 16 + ti;
    const int al = ((j + 1) & 2) == 0;
    Exch* const X = &S->x;
    if (warp >= 8) {
        asm volatile("setmaxnreg.dec.sync.aligned.u32 72;");
        if (warp == 8) {
            asm volatile("barrier.cluster.wait.aligned;" ::: "memory");
            if (!elect1()) return;
            const int col_main = 80 * j + 16 * odd, col_tail = 80 * j + (odd ? 0 : 64);
            auto load_w = [&](int it) {
                const uint32_t b = BAR(B_WF + it), dst = sm + wbuf(it) + rank * 6144;
                mbar_expect_tx(b, WST);
                tma4d_mc(dst, al ? &mw2 : &mw, 0, it * 32 + rank * 16, col_main >> (5 + al), 0, b);
                tma3d_mc(dst + 12288 - rank * 4608, &mt, col_tail, it * 32 + rank * 16, 0, b);
            };
            int it = 0, wn = 0, gn = 0;
#pragma unroll 1
            for (int r = -2; r < 19; r++) {
                if (r == -1) mbar_wait(BAR(B_XF + XWAIT), 0);
                if (r >= 0) mbar_wait(BAR(B_WE + r), 0);
                const int lim = min(r < 2 ? (r == 1 ? 7 : 2 * r + 6) : r + 7, 20);
#pragma unroll 1
                for (; it < lim; it++) load_w(it);
                if (r == -1 || r == 0) l2_prefetch(wqkv + (size_t)(384 + r * 256 + role * 2) * 1920, 2 * 3840);
                if (r == 0) l2_prefetch(wo + role * 3200, 6400);
                if (r >= MPF0 && r < MPF0 + 10) l2_prefetch(wmod + (size_t)(role * 5 + ((r - MPF0) >> 1)) * 3840 + 1920 + (r & 1) * 1280, 1280);
                if (((GU_MASK >> (r + 2)) & 1) && fi < 108) { if (gn == 0) mbar_expect_tx(BAR(B_FG), 40960); tma2d(sm + OFF_WG + gn * 10240, (fi & 1) ? &mu : &mg, (fi >> 1) * 32, gn * 160, BAR(B_FG)); gn++; }
#pragma unroll 1
                for (int n = ((WO_MASK >> (r + 2)) & 1) + (r == 14); n > 0; n--) {
                    const int row = (j ^ wn) * 80 + rank * 40;
                    const uint32_t b = BAR(wn ? B_WO : B_WO0), dst = sm + wobuf(wn) + rank * 2560;
                    mbar_expect_tx(b, 12800);
                    tma2d_mc(dst, &mo, col_main, row, b); tma2d_mc(dst + 5120, &mo, col_main + 32, row, b); tma2d_mc(dst + 10240, &mo2, col_tail, row, b);
                    wn++;
                }
                if (r >= PF0 && r < PF0 + 3 * PFN) { const int m = (r - PF0) / PFN; l2_prefetch((m == 0 ? wg : (m == 1 ? wu : wd)) + role * 8640 + (r - PF0 - m * PFN) * (8640 / PFN), 17280 / PFN); }
            }
            STAMPT(24, 256);
            if (fi >= 88) { mbar_wait(BAR(B_G2), 0); mbar_expect_tx(BAR(B_FD), 55296); tma3d(sm + OFF_WD, &md, (fi - 88) * 16, 0, 0, BAR(B_FD)); }
            return;
        }
        asm volatile("barrier.cluster.wait.aligned;" ::: "memory");
        const int tid = threadIdx.x, lane = tid & 31, fh = (lane >> 3) & 1;
        int gd = 0;
        if (warp == 9) {
            {
                uint32_t ta = sm + OFF_TAB + fh * 1280 + (lane >> 4) * 128 + (lane & 4) * 16 + (lane & 1) * 32 + (lane & 2) * 4;
                const uint4* tp = &S->tab[lane >> 3][lane & 7];
                pause_until(t_start, TDELAY);
#pragma unroll 1
                for (int e = 0; e < 5; e++) {
                    uint32_t w[4];
                    if (e > 1) mbar_wait(BAR(B_WE + 4 * e - 8), 0);
                    while (true) {
                        ldg4_rlx(w, tp);
                        if (!__any_sync(~0u, min(min(w[0], w[1]), min(w[2], w[3])) == 0) || ++gd > SPIN_LIMIT) break;
                        pause(P_TAB);
                    }
                    sts2(ta, w[0], w[1]); sts2(ta + 16, w[2], w[3]);
                    __syncwarp();
                    if (e == 0) { STAMPT(2, 288); if (lane == 0) sts1(sm + OFF_EP + EP_US + 8, ep0 << 22 & 0x40000000u); }
                    if (lane == 0) mbar_arrive(BAR(e ? B_TB - 1 + e : B_T0));
                    ta += 256; tp += 288;
                }
            }
            uint32_t h[5][4];
            while (ldg1_acq(&S->cnt) != inc(ep0) && ++gd < SPIN_LIMIT) __nanosleep(YSLEEP);
            __syncwarp();
            if (lane == 0) mbar_arrive(BAR(B_RDY));
            mbar_wait(BAR(HALO_GO), 0);
            pause(D_H);
            if ((ti & 7) == 0) {
#pragma unroll
                for (int s = 0; s < 20; s++) h[s >> 2][s & 3] = 0;
            } else {
                do {
#pragma unroll
                    for (int s = 0; s < 5; s++) ldg4_rlx(h[s], &X->halo[(role - 8 - (ti & 8)) * 160 + s * 32 + lane]);
                } while (__any_sync(~0u, min(min(min(h[0][0], h[1][0]), min(h[2][0], h[3][0])), h[4][0]) == 0) && ++gd < SPIN_LIMIT);
            }
            const uint32_t p8 = sm + OFF_P8 - 4096, va = p8 + 2048 + (lane & 7) * VP + (lane >> 3) * 16;
            sts4(p8 + 2048 + 1408 + lane * 16, h[0]); sts4(p8 + 1408 + lane * 16, h[1]); sts2(p8 + (lane >> 4) * 2048 + 1920 + (lane & 15) * 8, h[2][0], h[2][1]);
            stsm4(va, h[3]); stsm4(va + 64, h[4]); stsm2(va + 128, h[2][2], h[2][3]);
            __syncwarp();
            if (lane == 0) mbar_arrive(BAR(B_HL));
            STAMPT(19, 288);
            uint2* const rp = pinp((uint2*)&X->ra[(lane & 7) * 8][0] + ti);
            const uint2* const rq = pinp((const uint2*)&X->ra[grp * 8][0] + (lane & 15));
            mbar_wait(BAR(B_G3), 0);
            if (j == (ti & 7)) {
                lds2(h[0], sm + OFF_EP + EP_US + 48 + (lane & 7) * 8);
                const uint32_t km = __reduce_max_sync(~0u, h[0][0]), tk = __reduce_min_sync(~0u, h[0][0] == km ? h[0][1] : ~0u);
                if (lane < 8) asm volatile("red.relaxed.gpu.global.max.u64 [%0], %1;" ::"l"(rp), "l"((unsigned long long)tk << 32 | km) : "memory");
            }
            pause(D_REC);
            do { ldg2_rlx(h[0], rq); } while (__any_sync(~0u, h[0][1] == 0) && ++gd < SPIN_LIMIT);
            const uint32_t kwin = __reduce_max_sync(~0u, h[0][0]), tok = __reduce_min_sync(~0u, h[0][0] == kwin ? h[0][1] : ~0u);
            if (lane == 0) {
                const uint32_t t = (tok - 1) & 2047, wi = (t & 1) * 64 + (t >> 5), wv[4] = {kwin, t, wi, wi * 320};
                sts4(sm + OFF_EP + EP_US + 32, wv); mbar_arrive(BAR(B_WIN));
            }
            if (lane < 8 && role < 20) stg4_rlx(&S->tab[role][lane], 0u, 0u, 0u, 0u);
            return;
        }
        const int at = tid - 320;
        const int kg = at < 40 ? 80 * j + 2 * at : max(fi - 88, 0) * 16 + 2 * (at & 7);
        const uint32_t w2 = *(const uint32_t*)(wr + kg);
        mbar_wait(BAR(B_T0), 0);
        {
            uint4* p = &X->o[4 * 128 * 256] + role * RV + at;
#pragma unroll 1
            for (int r = 0; r < RV / 64; r++) {
                stg4_rlx(p, 0u, 0u, 0u, 0u);
                p += 64;
                __nanosleep(RSLEEP);
            }
        }
        bar_sync(5, 64);
        if (at == 0) { mbar_wait(BAR(B_TB), 0); }
        if (at == 0) asm volatile("red.release.gpu.global.add.u32 [%0], 1;" ::"l"(&S->cnt) : "memory");
        mbar_wait(BAR(B_RDY), 0);
        const uint32_t* const mp = (const uint32_t*)&S->tab[0][0] + ((kg >> 4) & 3) * 8 + (kg & 6) + ((kg >> 3) & 1);
        const int p = odd ? (at < 8 ? at + 32 : at - 8) : at, lm = min(lane, 9);
        const uint32_t a = sm + OFF_EP + (p & 3) * 48 + (p >> 2) * 4;
#pragma unroll 1
        for (int ph = 0; ph < 4; ph++) {
            uint32_t v, us;
            mbar_wait(BAR(ph < 2 ? TB_GO : TB_GO2), 0);
            while (true) {
                v = ldg1_rlx(mp + (ph < 2 ? 20 + ph + (kg >> 6) * 2 : 20 + ph * 10 + (kg >> 6)) * 288);
                us = ldg1_rlx(&S->tab[ph < 2 ? 20 + ph + lm * 2 : 20 + ph * 10 + lm][8]);
                if (!__any_sync(~0u, min(v, us) == 0) || ++gd > SPIN_LIMIT) break;
                __nanosleep(200);
            }
            if (at < 40) {
                sts1(a + ph * 192, v);
                if (ph == 1) {
                    const float u0 = blo(v) * blo(w2), u1 = bhi(v) * bhi(w2);
                    const uint32_t uh = pack2(u0, u1);
                    sts1(a + 768, 0x3f803f80u); sts1(a + 960, uh); sts1(a + 1152, pack2(u0 - blo(uh), u1 - bhi(uh)));
                }
            } else sts1(sm + OFF_EP + EP_GD + (at & 7) * 4, v);
            float t = lane < 10 ? __uint_as_float(us) : 0.f;
#pragma unroll
            for (int o = 1; o < 16; o <<= 1) t += __shfl_xor_sync(~0u, t, o);
            if (at == 0) sts1f(sm + OFF_EP + EP_US + 12 + ph * 4, t);
            __syncwarp();
            if (lane == 0 && ph) mbar_arrive(BAR(B_EP - 1 + ph));
        }
        STAMPT(20, 320);
    } else {
        asm volatile("setmaxnreg.inc.sync.aligned.u32 216;");
        asm volatile("barrier.cluster.wait.aligned;" ::: "memory");
        LANE_VARS
        const int tw = ti * 8 + warp;
        const uint32_t oo = tw * 4096 + j * 512 + lane * 16;
        const uint32_t pair = (uint32_t)(lane & 1) << 24;
        const uint32_t hi = lane >> 4, xa = sm + (warp * 16 + (lane & 15)) * 128 + ((hi ^ (lane & 7)) << 4);
        const uint32_t p8 = sm + OFF_P8 + warp * 2048, q8 = p8 - (warp ? 2048 : 4096), q9 = p8 - 2048 + (warp ? 16384 : 0);
        const uint32_t l16 = PIN(lane * 16), kt = PIN(hi * 16384 + (lane & 15) * 8), va = PIN(p8 + (lane & 7) * VP + (lane >> 3) * 16);
        const uint32_t vc = PIN(p8 + (lane & 7) * VP + fh * 16384 + hi * 16);
        const uint32_t vh = PIN((fh ? p8 : q9) + (lane & 7) * VP + hi * 16), kh = PIN((hi ? q9 : q8) + (lane & 15) * 8);
        const uint32_t mgt = PIN((2 * q > g ? 0xffffu : 0u) | (2 * q + 1 > g ? 0xffff0000u : 0u));
        uint32_t rr0, rr1, nn0, nn1;
        {
            float gA[2][4] = {}, gB[2][4] = {};
            uint32_t xb = sm + (warp * 16 + frow) * 128 + ((fh ^ (lane & 7)) << 4), one[16];
#pragma unroll
            for (int k = 0; k < 16; k++) one[k] = 0x3f803f80u + ((uint32_t)tid >> (12 + k));
#pragma unroll 1
            for (int c = 0; c < 10; c += 2) {
                mbar_wait(BAR(B_XF + c), 0); mbar_wait(BAR(B_XF + c + 1), 0);
                uint32_t a[8][4];
#pragma unroll
                for (int k = 0; k < 8; k++) ldsm4(a[k], (xb ^ ((k & 3) * 32)) + (k >> 2) * 16384);
                xb += 32768;
#pragma unroll
                for (int k = 0; k < 8; k++) {
                    uint32_t t[4];
#pragma unroll
                    for (int e = 0; e < 4; e++) asm volatile("mov.b32 %0, %1;" : "=r"(t[e]) : "r"(a[k][e]));
                    mma16(gA[k & 1], t[0], one[(k & 3) * 4], t[1], one[(k & 3) * 4 + 1], a[k][0], a[k][1]);
                    mma16(gB[k & 1], t[2], one[(k & 3) * 4 + 2], t[3], one[(k & 3) * 4 + 3], a[k][2], a[k][3]);
                }
            }
            const int src = (lane & ~3) | (g >> 1), e = g & 1;
            const float ss0 = __shfl_sync(~0u, e ? gA[0][1] + gA[1][1] : gA[0][0] + gA[1][0], src), ss1 = __shfl_sync(~0u, e ? gB[0][1] + gB[1][1] : gB[0][0] + gB[1][0], src);
            const float m0 = __shfl_sync(~0u, e ? gA[0][3] + gA[1][3] : gA[0][2] + gA[1][2], src) * (1.f / 640), m1 = __shfl_sync(~0u, e ? gB[0][3] + gB[1][3] : gB[0][2] + gB[1][2], src) * (1.f / 640);
            const float r0 = rbf(rsq(fmaxf(ss0 * (1.f / 640) - m0 * m0, 0.f) + 1e-5f)), r1 = rbf(rsq(fmaxf(ss1 * (1.f / 640) - m1 * m1, 0.f) + 1e-5f));
            rr0 = pack2(r0, r0); rr1 = pack2(r1, r1); nn0 = pack2(-m0 * r0, -m0 * r0); nn1 = pack2(-m1 * r1, -m1 * r1);
        }
        uint32_t xr[5][4];
#pragma unroll
        for (int s = 0; s < 5; s++) {
            const int ks = 5 * j + (odd ? (s == 4 ? 0 : s + 1) : s);
            ldsm4(xr[s], (xa ^ ((ks & 3) * 32)) + (ks >> 2) * 16384);
        }
        STAMP(0);
        mbar_wait(BAR(B_T0), 0);
        float acc[120];
#pragma unroll
        for (int i = 0; i < 120; i++) asm volatile("" : "=f"(acc[i]));
        {
            uint32_t a[2][2][4], raw[2][4], tt[2][4];
            uint32_t tb = sm + OFF_TAB + q * 16, xp = xa;
            auto load = [&](int u) {
                ldsm4(raw[0], xp ^ (u * 64)); ldsm4(raw[1], xp ^ (u * 64 + 32));
                lds4(tt[0], tb + u * 64 + 1280); lds4(tt[1], tb + u * 64);
            };
            auto xform = [&](uint32_t (*dst)[4]) {
#pragma unroll
                for (int h = 0; h < 2; h++) {
                    dst[h][0] = hf2(hf2(raw[h][0], rr0, nn0), tt[0][2 * h], tt[1][2 * h]); dst[h][1] = hf2(hf2(raw[h][1], rr1, nn1), tt[0][2 * h], tt[1][2 * h]);
                    dst[h][2] = hf2(hf2(raw[h][2], rr0, nn0), tt[0][2 * h + 1], tt[1][2 * h + 1]); dst[h][3] = hf2(hf2(raw[h][3], rr1, nn1), tt[0][2 * h + 1], tt[1][2 * h + 1]);
                }
            };
            const uint64_t dm0 = al ? mkdesc(SM0, 2048, 1024, 1) : mkdesc(SM0, 1024, 512, 2), dt0 = mkdesc(SM0 + 12288, 512, 256, 3);
            load(0); xform(a[0]);
            STAMP(3);
#pragma unroll 1
            for (int i2 = 0; i2 < 10; i2++) {
#pragma unroll
                for (int u = 0; u < 2; u++) {
                    const int it = i2 * 2 + u;
                    const uint32_t bo = wbuf(it) >> 4;
                    mbar_wait(BAR(B_WF + it), 0);
                    if (LAG && warp < 4 && i2 * 2 + u == 20 - LAG) bar_sync(4, 256);
                    wg_fence();
#pragma unroll
                    for (int h = 0; h < 2; h++) { wgmma_rs_n192(acc, a[u][h], dm0 + bo + h * 384, (u | h) ? 1 : i2); wgmma_rs_n48(acc + 96, a[u][h], dt0 + bo + h * 96, (u | h) ? 1 : i2); }
                    wg_commit();
                    if (LAG && u == 1 && warp >= 4 && i2 == 9) asm volatile("bar.arrive 4, 256;" ::: "memory");
                    if (u == 1) { xp += 16384; tb += 128; }
                    if (u == 1 && (i2 & 1) && i2 < 9) mbar_wait(BAR(B_TB + (i2 >> 1)), 0);
                    load(u ^ 1);
                    wg_wait<1>();
                    if (lane < 2 && (u == 1 || i2 > 0)) mbar_arrive_cl(pair + BAR0(B_WE - 1 + it));
                    xform(a[u ^ 1]);
                }
            }
        }
        uint32_t own[5][4], ab[3][7][4], sv, tc, fz = 0;
        const char* op[7];
        auto ldo = [&](int s, uint32_t (*dst)[4]) {
#pragma unroll
            for (int w = 0; w < 7; w++) ldg4_rlx(dst[w], op[w] + (4 - s) * 524288);
        };
        {
            uint32_t Q[10][2], K[2][10], V[2][10];
            mbar_wait(BAR(B_RDY), 0);
            const bool pub = warp == 7 && (~ti & 7);
            uint4* const hp = pinp(&X->halo[(role - (ti & 8)) * 160 + lane]);
            sv = lds1(sm + OFF_EP + EP_US + 8); tc = (sv ^ 0x40000000u) - 0x20000000u;
            wg_wait<0>();
            STAMP(4); STAMPT(18, 128);
#define ACC_IDX(t, m) (odd_ ? (t >= 2 ? m * 32 + (t - 2) * 4 : 96 + m * 8 + t * 4) : (t < 8 ? m * 32 + t * 4 : 96 + m * 8 + (t - 8) * 4))
#define PACK1(odd_v) { constexpr bool odd_ = odd_v; _Pragma("unroll") for (int t = 0; t < 10; t++) { \
                K[1][t] = pack2(acc[ACC_IDX(t, 1) + 2], acc[ACC_IDX(t, 1) + 3]); V[1][t] = pack2(acc[ACC_IDX(t, 2) + 2], acc[ACC_IDX(t, 2) + 3]); } }
#define PACK2(odd_v) { constexpr bool odd_ = odd_v; _Pragma("unroll") for (int t = 0; t < 10; t++) { \
                V[0][t] = pack2(acc[ACC_IDX(t, 2)], acc[ACC_IDX(t, 2) + 1]); \
                K[0][t] = pack2(acc[ACC_IDX(t, 1)], acc[ACC_IDX(t, 1) + 1]); \
                Q[t][0] = pack2(acc[ACC_IDX(t, 0)], acc[ACC_IDX(t, 0) + 1]); Q[t][1] = pack2(acc[ACC_IDX(t, 0) + 2], acc[ACC_IDX(t, 0) + 3]); } }
            if (odd) PACK1(true) else PACK1(false)
            if (pub) {
                K[1][0] = nz(K[1][0]); K[1][5] = nz(K[1][5]); K[1][2] = nz(K[1][2]); V[1][0] = nz(V[1][0]); V[1][4] = nz(V[1][4]);
                stg4_rlx(hp, K[1][0], K[1][1], K[1][3], K[1][4]); stg4_rlx(hp + 32, K[1][5], K[1][6], K[1][8], K[1][9]);
                stg4_rlx(hp + 96, V[1][0], V[1][1], V[1][2], V[1][3]); stg4_rlx(hp + 128, V[1][4], V[1][5], V[1][6], V[1][7]); stg4_rlx(hp + 64, K[1][2], K[1][7], V[1][8], V[1][9]);
            }
            uint32_t VT[5][4], KH[10];
            {
                const uint32_t k0[4] = {K[1][0], K[1][1], K[1][3], K[1][4]}, k1[4] = {K[1][5], K[1][6], K[1][8], K[1][9]};
                sts4(p8 + 16384 + 1408 + l16, k0); sts4(p8 + 1408 + l16, k1); sts2(p8 + 1920 + kt, K[1][2], K[1][7]);
                stsm4(va + 16384, V[1]); stsm4(va + 16384 + 64, V[1] + 4); stsm2(va + 16384 + 128, V[1][8], V[1][9]);
            }
            __syncwarp();
            if (lane == 0) mbar_arrive(BAR(B_HL + 1 + warp));
            if (odd) PACK2(true) else PACK2(false)
            stsm4(va, V[0]); stsm4(va + 64, V[0] + 4); stsm2(va + 128, V[0][8], V[0][9]);
            __syncwarp();
#pragma unroll
            for (int s = 0; s < 5; s++) ldsm4t(VT[s], vc + s * 32);
            float sb[4][4], sc[4][4];
            uint32_t qs[4][2];
#pragma unroll
            for (int h = 0; h < 4; h++) {
                const int ts = (h >> 1) * 5 + 2, ta = (h >> 1) * 5 + (h & 1) * 3;
                const bool mine = (q >> 1) == (h & 1);
                qs[h][0] = mine ? Q[ts][0] : 0u; qs[h][1] = mine ? Q[ts][1] : 0u;
                mma16c(sb[h], Q[ta][0], Q[ta][1], Q[ta + 1][0], Q[ta + 1][1], K[0][ta], K[0][ta + 1], 0.f, 0.f);
                mma16c(sc[h], Q[ta][0], Q[ta][1], Q[ta + 1][0], Q[ta + 1][1], K[1][ta], K[1][ta + 1], 0.f, 0.f);
                mma8(sb[h], qs[h][0], qs[h][1], K[0][ts]);
                mma8(sc[h], qs[h][0], qs[h][1], K[1][ts]);
            }
            const bool gt0 = mgt & 1, gt1 = (int)mgt < 0;
            auto half = [&](int h0, int h1, int e, float (*pv)[4], float (*cu)[4], uint32_t (*VT)[4]) {
                const float cs = 0.22360679774997896f * 1.4426950408889634f;
                uint32_t p[4];
                float t0[4], t1[4], m[4];
#pragma unroll
                for (int h = h0; h < h1; h++) { t0[h] = gt0 ? pv[h][2 * e] : cu[h][2 * e]; t1[h] = gt1 ? pv[h][2 * e + 1] : cu[h][2 * e + 1]; m[h] = fmaxf(t0[h], t1[h]); }
#pragma unroll
                for (int h = h0; h < h1; h++) m[h] = fmaxf(m[h], __shfl_xor_sync(~0u, m[h], 1));
#pragma unroll
                for (int h = h0; h < h1; h++) m[h] = fmaxf(m[h], __shfl_xor_sync(~0u, m[h], 2)) * -cs;
#pragma unroll
                for (int h = h0; h < h1; h++) p[h] = pack2(ex2(fmaf(t0[h], cs, m[h])), ex2(fmaf(t1[h], cs, m[h])));
#pragma unroll
                for (int pr = h0 / 2; pr < h1 / 2; pr++) {
                    const uint32_t a0 = p[2 * pr] & mgt, a1 = p[2 * pr + 1] & mgt, a2 = p[2 * pr] & ~mgt, a3 = p[2 * pr + 1] & ~mgt;
                    float l[4];
                    mma16c(l, a0, a1, a2, a3, 0x3f803f80u, 0x3f803f80u, 0.f, 0.f);
                    l[0] = rcp(l[0]); l[2] = rcp(l[2]);
#pragma unroll
                    for (int r = 0; r < 5; r++) {
                        const int t = pr * 5 + r;
                        float d[4];
                        mma16c(d, a0, a1, a2, a3, VT[t >> 1][(t & 1) * 2], VT[t >> 1][(t & 1) * 2 + 1], 0.f, 0.f);
                        const bool od = r == 2 ? (q & 2) : r > 2;
                        const float li = od ? l[2] : l[0];
                        own[t >> 1][(t & 1) * 2 + e] = pack2((od ? d[2] : d[0]) * li, (od ? d[3] : d[1]) * li);
                    }
                }
            };
            mbar_wait(BAR(B_HL + warp), 0);
            uint32_t VH[5][4];
            float sa[4][4];
            lds4(KH, q9 + 1408 + l16); lds4(KH + 4, q8 + 1408 + l16); lds2(KH + 8, kh + 1920);
#pragma unroll
            for (int s = 0; s < 5; s++) ldsm4t(VH[s], vh + s * 32);
            STAMP(5); STAMPT(25, 64);
            fz |= clock32();
            const float ninf = (tw & 63) == 0 ? -INFINITY : 0.f;
#pragma unroll
            for (int h = 0; h < 4; h++) {
                const int ta = (h >> 1) * 5 + (h & 1) * 3;
                mma16c(sa[h], Q[ta][0], Q[ta][1], Q[ta + 1][0], Q[ta + 1][1], KH[2 * h], KH[2 * h + 1], ninf, ninf);
                mma8(sa[h], qs[h][0], qs[h][1], KH[8 + (h >> 1)]);
            }
            auto sto = [&](int s) { own[s][0] = s ? tagw(own[s][0], tc) : nz(own[s][0]); stg4_rlx((char*)X->o + oo + (4 - s) * 524288, own[s][0], own[s][1], own[s][2], own[s][3]); };
            if (SPLIT == 1) {
                half(0, 2, 1, sb, sc, VT); half(0, 2, 0, sa, sb, VH);
                sto(0); sto(1);
                fz |= clock32();
                half(2, 4, 1, sb, sc, VT); half(2, 4, 0, sa, sb, VH);
                if (ELD) {
#pragma unroll
                    for (int w = 0; w < 7; w++) op[w] = (const char*)X->o + (oo ^ (w * 512 + 512));
                    fz |= clock32();
                    if (ELD == 4) sto(2);
                    ldo(0, ab[0]);
                    if (ELD == 2) ldo(1, ab[1]);
                }
                if (ELD != 4) sto(2);
                sto(3); sto(4);
            } else {
                half(0, 4, 1, sb, sc, VT); half(0, 4, 0, sa, sb, VH);
                sto(0); sto(1); sto(2); sto(3); sto(4);
            }
#pragma unroll
            for (int w = 0; w < 7; w++) op[w] = (const char*)X->o + (oo ^ (w * 512 + 512));
        }
        STAMP(6); STAMPT(21, 128); STAMPT(26, 64);
        float ac2[40];
#pragma unroll
        for (int i = 0; i < 40; i++) asm volatile("" : "=f"(ac2[i]));
        {
            const uint64_t d0 = mkdesc(SM0, 5120, 512, 2);
            mbar_wait(BAR(B_WO0), 0);
#pragma unroll
            for (int s = 1; s < 5; s++) own[s][0] -= tc;
            wg_fence();
#pragma unroll
            for (int s = 0; s < 5; s++) wgmma_rs_n80(ac2, own[s], d0 + (wobuf(0) >> 4) + s * 64, s);
            wg_commit();
            const uint32_t t6 = clock32();
            fz |= t6;
            if (!ELD) { pause_until(t6, D_O); ldo(0, ab[0]); }
            if (ELD == 3) ldo(1, ab[1]);
            mbar_wait(BAR(B_WO), 0);
#pragma unroll
            for (int s = 0; s < 5; s++) {
                uint32_t (*cur)[4] = ab[s % 3];
                if (s == 0) await7<0>(cur, op, fz, sv);
                else {
                    if (s == 1) await7<1>(cur, op, fz, sv); else if (s == 2) await7<2>(cur, op, fz, sv); else if (s == 3) await7<3>(cur, op, fz, sv); else await7<4>(cur, op, fz, sv);
#pragma unroll
                    for (int w = 0; w < 7; w++) cur[w][0] -= tc;
                }
                if (s == 0) { STAMP(7); STAMPT(1, 128); }
                wg_fence();
#pragma unroll
                for (int w = 1; w < 8; w++) wgmma_rs_n80(ac2, cur[w - 1], d0 + (wobuf(w) >> 4) + s * 64, 1);
                wg_commit();
                if (s < 3) { if (s) wg_wait<1>(); else fz |= clock32(); if (s == 0 && ELD != 2 && ELD != 3) ldo(1, ab[1]); if (s == 0 && D_2) pause_until(t6, D_2); ldo(s + 2, ab[(s + 2) % 3]); }
                if (s == FD_AT && lane == 0) mbar_arrive(BAR(B_G2));
            }
        }
        mbar_wait(BAR(B_EP), 0);
        uint32_t tga[12], tst[12];
        const uint32_t ep = sm + OFF_EP + q * 48;
#pragma unroll
        for (int s = 0; s < 3; s++) { lds4(tga + 4 * s, ep + s * 16); lds4(tst + 4 * s, ep + 768 + min(g, 2) * 192 + s * 16); }
        uint4* const sp0 = pinp(&X->stats[j][tw * 16 + g]);
        const int prow = (ti & 7) * 128 + warp * 16;
        const uint4* const sp = pinp(&X->stats[hi * 4][tw * 16 + (lane & 15)]);
        const int dsrc = PIN((lane & ~3) | (g >> 1));
        wg_wait<0>();
        if (lane == 0) mbar_arrive(BAR(B_G4));
        STAMP(8); STAMPT(23, 128);
        {
            float gA[2][4] = {}, gB[2][4] = {}, sd[4] = {};
#pragma unroll
            for (int s = 0; s < 5; s++) {
#pragma unroll
                for (int e = 0; e < 4; e++) xr[s][e] = hf2(tga[2 * s + (e >> 1)], pack2(ac2[s * 8 + e * 2], ac2[s * 8 + e * 2 + 1]), xr[s][e]);
                mma16(sd, xr[s][0], xr[s][1], xr[s][2], xr[s][3], tst[2 * s], tst[2 * s + 1]);
                mma8(gA[0], xr[s][0], xr[s][1], xr[s][0]); mma8(gB[0], xr[s][0], xr[s][1], xr[s][1]);
                mma8(gA[1], xr[s][2], xr[s][3], xr[s][2]); mma8(gB[1], xr[s][2], xr[s][3], xr[s][3]);
            }
            const float l0 = __shfl_down_sync(~0u, sd[0], 1), l1 = __shfl_down_sync(~0u, sd[2], 1);
            const float q0 = __shfl_sync(~0u, fsel(g & 1, gA[0][1] + gA[1][1], gA[0][0] + gA[1][0]), dsrc), q1 = __shfl_sync(~0u, fsel(g & 1, gB[0][3] + gB[1][3], gB[0][2] + gB[1][2]), dsrc);
            stg4_if(q == 0, sp0, __float_as_uint(sd[0]), __float_as_uint(sd[1] + l0), __float_as_uint(q0), 1u);
            stg4_if(q == 0, sp0 + 8, __float_as_uint(sd[2]), __float_as_uint(sd[3] + l1), __float_as_uint(q1), 1u);
        }
        const uint32_t t9 = clock32();
        STAMP(9);
        uint32_t fg[5][4], fu[5][4], tcb[12], tsb[12];
        uint32_t st[4][4];
        if (fi < 108) {
            mbar_wait(BAR(B_FG), 0);
#pragma unroll
            for (int s = 0; s < 5; s++) {
                const uint32_t off = sm + OFF_WG + (5 * warp + ((warp & 1) ? (s == 4 ? 0 : s + 1) : s)) * 1024 + frow * 64 + ((fh ^ ((lane >> 1) & 3)) << 4);
                ldsm4t(fg[s], off); ldsm4t(fu[s], off ^ 32);
            }
        }
        pause_until(t9, D_ST);
#pragma unroll
        for (int e = 0; e < 4; e++) ldg4_rlx(st[e], sp + e * 2056);
        mbar_wait(BAR(B_EP2), 0);
#pragma unroll
        for (int s = 0; s < 3; s++) { lds4(tcb + 4 * s, ep + 192 + s * 16); lds4(tsb + 4 * s, ep + 384 + s * 16); }
        int crow;
        {
            const float2 su = lds2f(sm + OFF_EP + EP_US + 16);
            int gd = 0;
            const int tk = PIN(prow * 2 + (ti >> 3) + 1);
            float v[3];
            bool bad;
            while (true) {
                bad = __any_sync(~0u, (st[0][3] & st[1][3] & st[2][3] & st[3][3]) == 0);
#pragma unroll
                for (int e = 0; e < 3; e++) {
                    v[e] = (__uint_as_float(st[0][e]) + __uint_as_float(st[1][e])) + (__uint_as_float(st[2][e]) + __uint_as_float(st[3][e]));
                    v[e] += __shfl_xor_sync(~0u, v[e], 16);
                }
                if (!bad || ++gd > SPIN_LIMIT) break;
#pragma unroll
                for (int e = 0; e < 4; e++) ldg4_again(st[e], sp + e * 2056);
            }
            STAMP(10);
            const float m = v[0] * (1.f / 640), rs = rsq(fmaxf(fmaf(v[2], 1.f / 640, 1e-5f) - m * m, 1e-5f));
            const uint32_t key = fkey(fmaf(rs, fmaf(-m, su.x, v[1]), su.y)), kmax = __reduce_max_sync(~0u, key);
            crow = __ffs(__ballot_sync(~0u, key == kmax)) - 1;
            if (lane == 0) { sts2(sm + OFF_EP + EP_US + 48 + warp * 8, kmax, tk + 2 * crow); mbar_arrive(BAR(B_G3)); }
            const uint32_t rn = pack2(rs, -m * rbf(rs)), a0 = __shfl_sync(~0u, rn, g), a1 = __shfl_sync(~0u, rn, g + 8);
            rr0 = __byte_perm(a0, 0, 0x1010); nn0 = __byte_perm(a0, 0, 0x3232); rr1 = __byte_perm(a1, 0, 0x1010); nn1 = __byte_perm(a1, 0, 0x3232);
        }
        {
            const bool up = crow >= 8;
            const uint32_t rr = up ? rr1 : rr0, nn = up ? nn1 : nn0;
            if (g == (crow & 7)) {
                uint4* cp = &X->cand[j][tw * 20 + q];
#pragma unroll
                for (int s = 0; s < 5; s++) {
                    const uint32_t xa_ = up ? xr[s][1] : xr[s][0], xb_ = up ? xr[s][3] : xr[s][2];
                    stg4_rlx(cp + s * 4, nz(hf2(hf2(xa_, rr, nn), tcb[2 * s], tsb[2 * s])), hf2(hf2(xb_, rr, nn), tcb[2 * s + 1], tsb[2 * s + 1]), xa_, xb_);
                }
            }
        }
        STAMP(11);
        const uint32_t stg = sm + 5 * WST + warp * 2560;
        {
            mbar_wait(BAR(B_EP3), 0);
#pragma unroll
            for (int s = 0; s < 3; s++) lds4(tga + 4 * s, ep + 576 + s * 16);
#pragma unroll
            for (int s = 0; s < 5; s++) {
#pragma unroll
                for (int e = 0; e < 4; e++) { const int t = 2 * s + (e >> 1); xr[s][e] = hf2(tga[t], hf2(hf2(xr[s][e], (e & 1) ? rr1 : rr0, (e & 1) ? nn1 : nn0), tcb[t], tsb[t]), xr[s][e]); }
            }
            mbar_wait(BAR(B_G4), 0);
#pragma unroll
            for (int s = 0; s < 5; s++) stsm4(stg + (lane & 15) * 160 + (odd ? (s == 4 ? 0 : s + 1) : s) * 32 + hi * 16, xr[s]);
            asm volatile("fence.proxy.async.shared::cta;" ::: "memory");
            __syncwarp();
            if (elect1()) tma3d_st(&mout, 80 * j, ti >> 3, prow + (~crow & 8), stg + (~crow & 8) * 160);
        }
        STAMP(12);
        const char* cp = (const char*)pinp(&X->cand[warp][q]);
        uint32_t* const ap0 = pinp((uint32_t*)&X->ra[fi >> 1][8 + (fi & 1) * 4] + (lane & 8) + (lane & 3) * 2 + ((lane >> 2) & 1));
        const uint32_t rw = PIN(sm + OFF_RED - 256 + (q * 4 + (g >> 1)) * 80 + warp * 8 + (g & 1) * 4), rd = PIN(sm + OFF_RED - 256 + (lane & 15) * 80);
        if (smem_u32(sm_raw) != sm) return;
        uint32_t wv[4]; int gd = 0;
        mbar_wait(BAR(B_WIN), 0);
        lds4(wv, sm + OFF_EP + EP_US + 32);
        const uint32_t kwin = wv[0];
        const int tokwin = wv[1], win = wv[2];
        STAMP(13);
        if (fi < 108) {
            uint32_t hb[5][2];
            float mine;
            bool bad;
            cp += wv[3];
            do {
#pragma unroll
                for (int s = 0; s < 5; s++) ldg2_rlx(hb[s], cp + s * 64);
                bad = __any_sync(~0u, min(min(min(hb[0][0], hb[1][0]), min(hb[2][0], hb[3][0])), hb[4][0]) == 0);
                float dg[2][4] = {}, du[2][4] = {};
#pragma unroll
                for (int s = 0; s < 5; s++) {
                    mma16(dg[s & 1], fg[s][0], fg[s][1], fg[s][2], fg[s][3], hb[s][0], hb[s][1]);
                    mma16(du[s & 1], fu[s][0], fu[s][1], fu[s][2], fu[s][3], hb[s][0], hb[s][1]);
                }
                mine = fsel(q & 2, fsel(q & 1, du[1][2], du[1][0]), fsel(q & 1, dg[1][2], dg[1][0])) + fsel(q & 2, fsel(q & 1, du[0][2], du[0][0]), fsel(q & 1, dg[0][2], dg[0][0]));
                sts1f(rw, mine);
                gd++;
            } while (bad && gd < SPIN_LIMIT);
            bar_sync(2, 256);
            if (warp == 0) {
                uint32_t v[4][4];
#pragma unroll
                for (int e = 0; e < 4; e++) lds4(v[e], rd + e * 16);
                float t[2];
#pragma unroll
                for (int e = 0; e < 2; e++)
                    t[e] = ((__uint_as_float(v[0][e]) + __uint_as_float(v[0][e + 2])) + (__uint_as_float(v[1][e]) + __uint_as_float(v[1][e + 2]))) +
                           ((__uint_as_float(v[2][e]) + __uint_as_float(v[2][e + 2])) + (__uint_as_float(v[3][e]) + __uint_as_float(v[3][e + 2])));
                uint32_t pr = pack2(t[0], t[1]);
                if (!(fi & 1)) pr = pack2(blo(pr) * sigm(blo(pr)), bhi(pr) * sigm(bhi(pr)));
                stg1_if(lane < 16, ap0, nz(pr));
            }
        }
        STAMP(14);
        if (win != tw) {
            if (elect1()) tma3d_st(&mout, 80 * j, ti >> 3, prow + (crow & 8), stg + (crow & 8) * 160);
        } else {
#pragma unroll 1
            for (int r = crow & 8; r <= (crow | 7); r++)
                if (r != crow && lane < 20) { uint32_t v[2]; lds2(v, stg + r * 160 + lane * 8); *(uint2*)(out + (size_t)((prow + r) * 2 + (ti >> 3)) * 640 + 80 * j + lane * 4) = make_uint2(v[0], v[1]); }
        }
        if (fi >= 88) {
            const int d = fi - 88, dj = d / 5, dm = d - dj * 5, sp = (dj & 1) ? (dm == 0 ? 4 : dm - 1) : dm;
            const int ks0 = min(warp * 14, 94);
            const uint32_t frag = frow * 32 + ((fh ^ ((lane >> 2) & 1)) << 4);
            uint32_t fd[14][4];
            mbar_wait(BAR(B_FD), 0);
#pragma unroll
            for (int s = 0; s < 14; s++) ldsm4t(fd[s], sm + OFF_WD + (ks0 + s) * 512 + frag);
            const float sf = sigm(rbf(__uint_as_float((kwin & 0x80000000u) ? kwin & 0x7fffffffu : ~kwin)));
            const uint32_t sg = PIN(pack2(sf, sf));
            const uint32_t gbd = lds1(sm + OFF_EP + EP_GD + (lane & 7) * 4);
            uint32_t* const op = (uint32_t*)(out + (size_t)tokwin * 640 + d * 16) + (lane & 7);
            uint32_t bsv[4], ag[4], au[4];
            const uint4* ap = &X->ra[(ks0 >> 1) + min(g, 6)][8 + q];
            const uint32_t keep = warp == 7 && g < 2 ? 0u : ~0u;
            const uint32_t as = PIN(sm + 7 * WST + warp * 512 + q * 16), aw = PIN(sm + 7 * WST + warp * 512 + g * 64 + (q & 1) * 32 + (q >> 1) * 8);
            const uint32_t yw = PIN(sm + OFF_TAB + ((q & 1) * 4 + (g >> 1)) * 80 + warp * 8 + (g & 1) * 4), yr = PIN(sm + OFF_TAB + (lane & 7) * 80);
            bool bad;
            do {
                ldg4_rlx(ag, ap); ldg4_rlx(au, ap + 4); ldg4_rlx(bsv, &X->cand[dj][win * 20 + sp * 4 + q]);
                bad = __any_sync(~0u, min(min(min(min(ag[0], ag[1]), min(ag[2], ag[3])), min(min(au[0], au[1]), min(au[2], au[3]))), bsv[0]) == 0);
                sts2(aw, hm2(ag[0], au[0]) & keep, hm2(ag[1], au[1]) & keep); sts2(aw + 16, hm2(ag[2], au[2]) & keep, hm2(ag[3], au[3]) & keep);
                gd++;
            } while (bad && gd < SPIN_LIMIT);
            STAMP(15);
            __syncwarp();
            float dy[4][4] = {};
            uint32_t av[7][4];
#pragma unroll
            for (int s = 0; s < 7; s++) lds4(av[s], as + s * 64);
#pragma unroll
            for (int s = 0; s < 7; s++) {
                mma16(dy[(2 * s) & 3], fd[2 * s][0], fd[2 * s][1], fd[2 * s][2], fd[2 * s][3], av[s][0], av[s][1]);
                mma16(dy[(2 * s + 1) & 3], fd[2 * s + 1][0], fd[2 * s + 1][1], fd[2 * s + 1][2], fd[2 * s + 1][3], av[s][2], av[s][3]);
            }
            sts1f(yw, (fsel(q & 1, dy[2][2], dy[2][0]) + fsel(q & 1, dy[3][2], dy[3][0])) + (fsel(q & 1, dy[0][2], dy[0][0]) + fsel(q & 1, dy[1][2], dy[1][0])));
            bar_sync(2, 256);
            if (warp == 0) {
                uint32_t v[4][4];
#pragma unroll
                for (int e = 0; e < 4; e++) lds4(v[e], yr + e * 16);
                float t[2];
#pragma unroll
                for (int e = 0; e < 2; e++)
                    t[e] = ((__uint_as_float(v[0][e]) + __uint_as_float(v[0][e + 2])) + (__uint_as_float(v[1][e]) + __uint_as_float(v[1][e + 2]))) +
                           ((__uint_as_float(v[2][e]) + __uint_as_float(v[2][e + 2])) + (__uint_as_float(v[3][e]) + __uint_as_float(v[3][e + 2])));
                const uint32_t hh = (lane & 4) ? bsv[1] : bsv[0], xx = (lane & 4) ? bsv[3] : bsv[2];
                if (lane < 8) *op = hf2(gbd, hf2(hm2(pack2(t[0], t[1]), sg), 0x3f803f80u, hh), xx);
            }
        }
        asm volatile("cp.async.bulk.commit_group;\ncp.async.bulk.wait_group.read 0;" ::: "memory");
        STAMP(16);
    }
}

typedef CUresult (*EncFn)(CUtensorMap*, CUtensorMapDataType, cuuint32_t, void*, const cuuint64_t*, const cuuint64_t*, const cuuint32_t*, const cuuint32_t*,
                          CUtensorMapInterleave, CUtensorMapSwizzle, CUtensorMapL2promotion, CUtensorMapFloatOOBfill);
static void make_map(EncFn enc, CUtensorMap* m, const void* base, int rank, const cuuint64_t* dims, const cuuint64_t* strides, const cuuint32_t* box, CUtensorMapSwizzle sw) {
    const cuuint32_t es[5] = {1, 1, 1, 1, 1};
    enc(m, CU_TENSOR_MAP_DATA_TYPE_BFLOAT16, rank, (void*)base, dims, strides, box, es, CU_TENSOR_MAP_INTERLEAVE_NONE, sw, CU_TENSOR_MAP_L2_PROMOTION_NONE, CU_TENSOR_MAP_FLOAT_OOB_FILL_NONE);
}

extern "C" void kernel_launch(void* const* d_in, const int* in_sizes, int n_in, void* d_out, int out_size) {
    typedef const __nv_bfloat16* P;
    P x = (P)d_in[0], wqkv = (P)d_in[1], wo = (P)d_in[2], wr = (P)d_in[4], wg = (P)d_in[5], wu = (P)d_in[6], wd = (P)d_in[7], c = (P)d_in[8], wmod = (P)d_in[9];
    void* fn = nullptr; cudaDriverEntryPointQueryResult qr;
    cudaGetDriverEntryPoint("cuTensorMapEncodeTiled", &fn, cudaEnableDefault, &qr);
    EncFn enc = (EncFn)fn;
    CUtensorMap mx, mw, mt, mo, mg, mu, md, mm, mw2, mout, mo2;
    { cuuint64_t d[] = {640, 2, 1024}, s[] = {1280, 2560}; cuuint32_t b[] = {64, 1, 128}; make_map(enc, &mx, x, 3, d, s, b, CU_TENSOR_MAP_SWIZZLE_128B); }
    { cuuint64_t d[] = {32, 640, 20, 3}, s[] = {3840, 64, 1280}; cuuint32_t b[] = {32, 16, 2, 3}; make_map(enc, &mw, wqkv, 4, d, s, b, CU_TENSOR_MAP_SWIZZLE_64B); }
    { cuuint64_t d[] = {640, 640, 3}, s[] = {3840, 1280}; cuuint32_t b[] = {16, 16, 3}; make_map(enc, &mt, wqkv, 3, d, s, b, CU_TENSOR_MAP_SWIZZLE_32B); }
    { cuuint64_t d[] = {640, 640}, s[] = {1280}; cuuint32_t b[] = {32, 40}; make_map(enc, &mo, wo, 2, d, s, b, CU_TENSOR_MAP_SWIZZLE_64B);
      b[0] = 16; make_map(enc, &mo2, wo, 2, d, s, b, CU_TENSOR_MAP_SWIZZLE_64B); }
    { cuuint64_t d[] = {1728, 640}, s[] = {3456}; cuuint32_t b[] = {32, 160}; make_map(enc, &mg, wg, 2, d, s, b, CU_TENSOR_MAP_SWIZZLE_64B); make_map(enc, &mu, wu, 2, d, s, b, CU_TENSOR_MAP_SWIZZLE_64B); }
    { cuuint64_t d[] = {640, 216, 8}, s[] = {1280, 1280 * 216}; cuuint32_t b[] = {16, 216, 8}; make_map(enc, &md, wd, 3, d, s, b, CU_TENSOR_MAP_SWIZZLE_32B); }
    { cuuint64_t d[] = {3840, 640}, s[] = {7680}; cuuint32_t b[] = {64, 80}; make_map(enc, &mm, wmod, 2, d, s, b, CU_TENSOR_MAP_SWIZZLE_128B); }
    { cuuint64_t d[] = {64, 640, 10, 3}, s[] = {3840, 128, 1280}; cuuint32_t b[] = {64, 16, 1, 3}; make_map(enc, &mw2, wqkv, 4, d, s, b, CU_TENSOR_MAP_SWIZZLE_128B); }
    { cuuint64_t d[] = {640, 2, 1024}, s[] = {1280, 2560}; cuuint32_t b[] = {80, 1, 8}; make_map(enc, &mout, d_out, 3, d, s, b, CU_TENSOR_MAP_SWIZZLE_NONE); }
    void* sp = nullptr;
    cudaGetSymbolAddress(&sp, g_s);
    cudaFuncSetAttribute(fused_kernel, cudaFuncAttributeMaxDynamicSharedMemorySize, SMEM_BYTES);
    fused_kernel<<<132, 384, SMEM_BYTES>>>(wmod, c, (Scratch*)sp, wqkv, wo, (__nv_bfloat16*)d_out, wr, wg, wu, wd, mm, mx, mw, mt, mo, mg, mu, md, mw2, mout, mo2);
}
```

```cpp
#include <cuda_runtime.h>
#include <cuda_bf16.h>
#include <cuda.h>
#include <stdint.h>

#define SPIN_LIMIT (1 << 17)

constexpr int RV = 704;
struct __align__(4096) Exch {
    uint4 o[5 * 128 * 256];
    uint4 halo[112 * 160];
    uint4 stats[8][2056];
    uint4 cand[8][128 * 20 + 8];
    uint4 ra[64][24];
    uint4 pad[128 * RV - (128 * 256 + 112 * 160 + 8 * 2056 + 8 * (128 * 20 + 8) + 64 * 24)];
};
struct __align__(4096) Scratch {
    Exch x;
    uint4 tab[60][72];
    unsigned cnt;
};
__device__ Scratch g_s;
#define STAMP(n)
#define GSTAMP(n)
#define STAMPT(n, t)

constexpr uint32_t OFF_W = 163840, WST = 15360;
constexpr uint32_t OFF_WM = OFF_W + 2 * WST;
constexpr uint32_t OFF_FF = OFF_WM + 20480;
constexpr uint32_t OFF_P8 = 131072, VP = 176;
constexpr uint32_t OFF_WD = 129024, OFF_WG = 184320;
constexpr uint32_t OFF_TAB = 225280;
constexpr uint32_t OFF_RED = OFF_TAB + 2560;
constexpr uint32_t OFF_EP = OFF_TAB + 4096;
constexpr uint32_t EP_GD = 1344, EP_US = 1376;
constexpr uint32_t OFF_BAR = OFF_EP + 1488;
constexpr uint32_t OFF_PROF = OFF_BAR + 640;
constexpr uint32_t SMEM_BYTES = OFF_PROF + 128;
enum { B_XF = 0, B_WF = 10, B_WO0 = 30, B_WO, B_FG, B_FD, B_TB, B_HL = B_TB + 4, B_G0 = B_HL + 8, B_RDY, B_WIN, B_EP, B_EP2, B_EP3, B_G2, B_G3, B_G4, B_WE = 55, B_T0 = B_WE + 19 };
#define SPLIT 1
#define ELD 4
#define D_2 0
#define CPF 32
#define D_ST 400
#define D_REC 300
#define D_O 300
#define D_H 300
#define WO_MASK 0x1f5000
#define P_TAB 100
#define LAG 2
#define XWAIT 2
#define FD_AT 2
#define GU_MASK 0xaa00
#define TB_GO B_HL
#define TB_GO2 B_G2
#define TDELAY 3700
#define PFN 5
#define PF0 1
#define YSLEEP 300
#define MPF0 6
#define XDELAY 600
#define RSLEEP 40
#define HALO_GO B_G0
constexpr uint32_t SM0 = 1024;
#define BAR0(i) (SM0 + OFF_BAR + 8 * (i))
#define BAR(i) (sm + OFF_BAR + 8 * (i))

__device__ __forceinline__ uint32_t smem_u32(const void* p) { return (uint32_t)__cvta_generic_to_shared(p); }
__device__ __forceinline__ void mbar_init(uint32_t b, int cnt) { asm volatile("mbarrier.init.shared::cta.b64 [%0], %1;" ::"r"(b), "r"(cnt) : "memory"); }
__device__ __forceinline__ void mbar_expect_tx(uint32_t b, uint32_t bytes) { asm volatile("mbarrier.arrive.expect_tx.shared::cta.b64 _, [%0], %1;" ::"r"(b), "r"(bytes) : "memory"); }
__device__ __forceinline__ void mbar_arrive(uint32_t b) { asm volatile("mbarrier.arrive.shared::cta.b64 _, [%0];" ::"r"(b) : "memory"); }
__device__ __forceinline__ bool mbar_try(uint32_t b, uint32_t par) {
    uint32_t ok;
    asm volatile("{.reg .pred p; mbarrier.try_wait.parity.shared::cta.b64 p, [%1], %2; selp.u32 %0, 1, 0, p;}" : "=r"(ok) : "r"(b), "r"(par) : "memory");
    return ok;
}
__device__ __forceinline__ void mbar_wait(uint32_t b, uint32_t par) {
    asm volatile("{.reg .pred p;\nW: mbarrier.try_wait.parity.shared::cta.b64 p, [%0], %1;\n@!p bra W;}" ::"r"(b), "r"(par) : "memory");
}
__device__ __forceinline__ void bar_sync(int id, int n) { asm volatile("bar.sync %0, %1;" ::"r"(id), "r"(n) : "memory"); }
__device__ __forceinline__ void tma2d(uint32_t dst, const CUtensorMap* m, int c0, int c1, uint32_t bar) {
    asm volatile("cp.async.bulk.tensor.2d.shared::cluster.global.mbarrier::complete_tx::bytes [%0], [%1, {%3, %4}], [%2];" ::"r"(dst), "l"(m), "r"(bar), "r"(c0), "r"(c1) : "memory");
}
__device__ __forceinline__ void tma3d(uint32_t dst, const CUtensorMap* m, int c0, int c1, int c2, uint32_t bar) {
    asm volatile("cp.async.bulk.tensor.3d.shared::cluster.global.mbarrier::complete_tx::bytes [%0], [%1, {%3, %4, %5}], [%2];" ::"r"(dst), "l"(m), "r"(bar), "r"(c0), "r"(c1), "r"(c2) : "memory");
}
__device__ __forceinline__ void l2_prefetch(const void* p, uint32_t bytes) { asm volatile("cp.async.bulk.prefetch.L2.global [%0], %1;" ::"l"(p), "r"(bytes) : "memory"); }
__device__ __forceinline__ void wg_fence() { asm volatile("wgmma.fence.sync.aligned;" ::: "memory"); }
__device__ __forceinline__ void wg_commit() { asm volatile("wgmma.commit_group.sync.aligned;" ::: "memory"); }
template <int N> __device__ __forceinline__ void wg_wait() { asm volatile("wgmma.wait_group.sync.aligned %0;" ::"n"(N) : "memory"); }
__device__ __forceinline__ void ldsm4(uint32_t* r, uint32_t addr) { asm volatile("ldmatrix.sync.aligned.m8n8.x4.shared.b16 {%0,%1,%2,%3}, [%4];" : "=r"(r[0]), "=r"(r[1]), "=r"(r[2]), "=r"(r[3]) : "r"(addr) : "memory"); }
__device__ __forceinline__ void ldsm4t(uint32_t* r, uint32_t addr) { asm volatile("ldmatrix.sync.aligned.m8n8.x4.trans.shared.b16 {%0,%1,%2,%3}, [%4];" : "=r"(r[0]), "=r"(r[1]), "=r"(r[2]), "=r"(r[3]) : "r"(addr) : "memory"); }
__device__ __forceinline__ void stsm4(uint32_t addr, const uint32_t* r) { asm volatile("stmatrix.sync.aligned.m8n8.x4.shared.b16 [%4], {%0,%1,%2,%3};" ::"r"(r[0]), "r"(r[1]), "r"(r[2]), "r"(r[3]), "r"(addr) : "memory"); }
__device__ __forceinline__ void lds4(uint32_t* r, uint32_t addr) { asm volatile("ld.shared.v4.u32 {%0,%1,%2,%3}, [%4];" : "=r"(r[0]), "=r"(r[1]), "=r"(r[2]), "=r"(r[3]) : "r"(addr) : "memory"); }
__device__ __forceinline__ void sts4(uint32_t addr, const uint32_t* r) { asm volatile("st.shared.v4.u32 [%4], {%0,%1,%2,%3};" ::"r"(r[0]), "r"(r[1]), "r"(r[2]), "r"(r[3]), "r"(addr) : "memory"); }
__device__ __forceinline__ float2 lds2f(uint32_t addr) { float2 v; asm volatile("ld.shared.v2.f32 {%0,%1}, [%2];" : "=f"(v.x), "=f"(v.y) : "r"(addr) : "memory"); return v; }
__device__ __forceinline__ void sts1f(uint32_t addr, float v) { asm volatile("st.shared.f32 [%0], %1;" ::"r"(addr), "f"(v) : "memory"); }
__device__ __forceinline__ void sts1(uint32_t addr, uint32_t v) { asm volatile("st.shared.u32 [%0], %1;" ::"r"(addr), "r"(v) : "memory"); }
__device__ __forceinline__ void ldg4_rlx(uint32_t* r, const void* p) { asm volatile("{.reg .b128 t; ld.relaxed.gpu.global.b128 t, [%4]; mov.b128 {%0,%1,%2,%3}, t;}" : "=r"(r[0]), "=r"(r[1]), "=r"(r[2]), "=r"(r[3]) : "l"(p) : "memory"); }
__device__ __forceinline__ void ldg2_rlx(uint32_t* r, const void* p) { asm volatile("{.reg .b64 t; ld.relaxed.gpu.global.b64 t, [%2]; mov.b64 {%0,%1}, t;}" : "=r"(r[0]), "=r"(r[1]) : "l"(p) : "memory"); }
__device__ __forceinline__ uint32_t ldg1_rlx(const void* p) { uint32_t v; asm volatile("ld.relaxed.gpu.global.u32 %0, [%1];" : "=r"(v) : "l"(p) : "memory"); return v; }
__device__ __forceinline__ void stg4_rlx(void* p, uint32_t a, uint32_t b, uint32_t c, uint32_t d) { asm volatile("{.reg .b128 t; mov.b128 t, {%1,%2,%3,%4}; st.relaxed.gpu.global.b128 [%0], t;}" ::"l"(p), "r"(a), "r"(b), "r"(c), "r"(d) : "memory"); }
__device__ __forceinline__ void stg1_rlx(void* p, uint32_t a) { asm volatile("st.relaxed.gpu.global.u32 [%0], %1;" ::"l"(p), "r"(a) : "memory"); }
__device__ __forceinline__ uint64_t mkdesc(uint32_t addr, uint32_t lbo, uint32_t sbo, uint32_t sw) { return (uint64_t)((addr & 0x3FFFF) >> 4) | ((uint64_t)(lbo >> 4) << 16) | ((uint64_t)(sbo >> 4) << 32) | ((uint64_t)sw << 62); }
__device__ __forceinline__ uint32_t pack2(float lo, float hi) { uint32_t r; asm("cvt.rn.bf16x2.f32 %0, %1, %2;" : "=r"(r) : "f"(hi), "f"(lo)); return r; }
__device__ __forceinline__ float blo(uint32_t v) { return __uint_as_float(v << 16); }
__device__ __forceinline__ float bhi(uint32_t v) { return __uint_as_float(v & 0xffff0000u); }
__device__ __forceinline__ float rbf(float x) { return blo(pack2(x, 0.f)); }
__device__ __forceinline__ uint32_t hf2(uint32_t a, uint32_t b, uint32_t c) { uint32_t r; asm("fma.rn.bf16x2 %0, %1, %2, %3;" : "=r"(r) : "r"(a), "r"(b), "r"(c)); return r; }
__device__ __forceinline__ float ex2(float x) { float r; asm("ex2.approx.ftz.f32 %0, %1;" : "=f"(r) : "f"(x)); return r; }
__device__ __forceinline__ void mma16(float* d, uint32_t a0, uint32_t a1, uint32_t a2, uint32_t a3, uint32_t b0, uint32_t b1) {
    asm("mma.sync.aligned.m16n8k16.row.col.f32.bf16.bf16.f32 {%0,%1,%2,%3}, {%4,%5,%6,%7}, {%8,%9}, {%0,%1,%2,%3};"
                 : "+f"(d[0]), "+f"(d[1]), "+f"(d[2]), "+f"(d[3]) : "r"(a0), "r"(a1), "r"(a2), "r"(a3), "r"(b0), "r"(b1));
}
__device__ __forceinline__ void mma8(float* d, uint32_t a0, uint32_t a1, uint32_t b0) {
    asm("mma.sync.aligned.m16n8k8.row.col.f32.bf16.bf16.f32 {%0,%1,%2,%3}, {%4,%5}, {%6}, {%0,%1,%2,%3};"
                 : "+f"(d[0]), "+f"(d[1]), "+f"(d[2]), "+f"(d[3]) : "r"(a0), "r"(a1), "r"(b0));
}
__device__ __forceinline__ uint32_t fkey(float f) { const uint32_t u = __float_as_uint(f); return u ^ (((int)u >> 31) | 0x80000000u); }
__device__ __forceinline__ float rcp(float x) { float r; asm("rcp.approx.ftz.f32 %0, %1;" : "=f"(r) : "f"(x)); return r; }
__device__ __forceinline__ float sigm(float x) { return rcp(1.f + ex2(x * -1.4426950408889634f)); }
__device__ __forceinline__ void mma16c(float* d, uint32_t a0, uint32_t a1, uint32_t a2, uint32_t a3, uint32_t b0, uint32_t b1, float c0, float c1) {
    asm("mma.sync.aligned.m16n8k16.row.col.f32.bf16.bf16.f32 {%0,%1,%2,%3}, {%4,%5,%6,%7}, {%8,%9}, {%10,%11,%12,%12};"
                 : "=f"(d[0]), "=f"(d[1]), "=f"(d[2]), "=f"(d[3]) : "r"(a0), "r"(a1), "r"(a2), "r"(a3), "r"(b0), "r"(b1), "f"(c0), "f"(c1), "f"(0.f));
}
__device__ __forceinline__ void stsm2(uint32_t addr, uint32_t a, uint32_t b) { asm volatile("stmatrix.sync.aligned.m8n8.x2.shared.b16 [%2], {%0,%1};" ::"r"(a), "r"(b), "r"(addr) : "memory"); }
__device__ __forceinline__ void lds2(uint32_t* r, uint32_t addr) { asm volatile("ld.shared.v2.u32 {%0,%1}, [%2];" : "=r"(r[0]), "=r"(r[1]) : "r"(addr) : "memory"); }
__device__ __forceinline__ void sts2(uint32_t addr, uint32_t a, uint32_t b) { asm volatile("st.shared.v2.u32 [%2], {%0,%1};" ::"r"(a), "r"(b), "r"(addr) : "memory"); }
__device__ __forceinline__ uint32_t lds1(uint32_t addr) { uint32_t v; asm volatile("ld.shared.u32 %0, [%1];" : "=r"(v) : "r"(addr) : "memory"); return v; }
__device__ __forceinline__ bool elect1() { uint32_t p; asm volatile("{.reg .pred P; elect.sync _|P, 0xffffffff; selp.u32 %0, 1, 0, P;}" : "=r"(p)); return p; }
__device__ __forceinline__ void tma2d_mc(uint32_t dst, const CUtensorMap* m, int c0, int c1, uint32_t bar) {
    asm volatile("cp.async.bulk.tensor.2d.shared::cluster.global.mbarrier::complete_tx::bytes.multicast::cluster [%0], [%1, {%3, %4}], [%2], %5;" ::"r"(dst), "l"(m), "r"(bar), "r"(c0), "r"(c1), "h"((unsigned short)3) : "memory");
}
__device__ __forceinline__ void tma3d_mc(uint32_t dst, const CUtensorMap* m, int c0, int c1, int c2, uint32_t bar) {
    asm volatile("cp.async.bulk.tensor.3d.shared::cluster.global.mbarrier::complete_tx::bytes.multicast::cluster [%0], [%1, {%3, %4, %5}], [%2], %6;" ::"r"(dst), "l"(m), "r"(bar), "r"(c0), "r"(c1), "r"(c2), "h"((unsigned short)3) : "memory");
}
__device__ __forceinline__ void tma4d_mc(uint32_t dst, const CUtensorMap* m, int c0, int c1, int c2, int c3, uint32_t bar) {
    asm volatile("cp.async.bulk.tensor.4d.shared::cluster.global.mbarrier::complete_tx::bytes.multicast::cluster [%0], [%1, {%3, %4, %5, %6}], [%2], %7;" ::"r"(dst), "l"(m), "r"(bar), "r"(c0), "r"(c1), "r"(c2), "r"(c3), "h"((unsigned short)3) : "memory");
}
__device__ __forceinline__ void mbar_arrive_cl(uint32_t b) { asm volatile("mbarrier.arrive.shared::cluster.b64 _, [%0];" ::"r"(b) : "memory"); }
__device__ __forceinline__ uint32_t hm2(uint32_t a, uint32_t b) { uint32_t r; asm("mul.rn.bf16x2 %0, %1, %2;" : "=r"(r) : "r"(a), "r"(b)); return r; }
__device__ __forceinline__ uint32_t clock32() { uint32_t c; asm volatile("mov.u32 %0, %clock;" : "=r"(c)); return c; }
__device__ __forceinline__ float rsq(float x) { float r; asm("rsqrt.approx.ftz.f32 %0, %1;" : "=f"(r) : "f"(x)); return r; }
__device__ __forceinline__ void pause_until(uint32_t t0, uint32_t n) {
    asm volatile("{.reg .pred p; .reg .u32 t;\nP: mov.u32 t, %clock; sub.u32 t, t, %0; setp.lt.u32 p, t, %1;\n@p bra.uni P;}" ::"r"(t0), "r"(n) : "memory");
}
__device__ __forceinline__ void pause(uint32_t n) { if (n) { const uint32_t t = clock32(); while (clock32() - t < n) {} } }
__device__ __forceinline__ uint32_t wbuf(int it) {
    const uint32_t v = it < 4 ? it + 8 : (uint32_t)(0x8302418302b1a908ull >> (4 * it - 16)) & 15;
    return v * WST + (v >> 3) * (OFF_W - 8 * WST);
}
__device__ __forceinline__ uint32_t wobuf(int w) { return ((0x30241765u >> (4 * w)) & 7) * WST; }
__device__ __forceinline__ uint32_t inc(uint32_t v) { uint32_t r; asm volatile("{.reg .u32 t; or.b32 t, %1, 255; add.u32 %0, t, 1;}" : "=r"(r) : "r"(v)); return r; }
__device__ __forceinline__ uint32_t ldg1_acq(const void* p) { uint32_t v; asm volatile("ld.acquire.gpu.global.u32 %0, [%1];" : "=r"(v) : "l"(p) : "memory"); return v; }
__device__ __forceinline__ void tma3d_st(const CUtensorMap* m, int c0, int c1, int c2, uint32_t src) {
    asm volatile("cp.async.bulk.tensor.3d.global.shared::cta.bulk_group [%0, {%2, %3, %4}], [%1];" ::"l"(m), "r"(src), "r"(c0), "r"(c1), "r"(c2) : "memory");
}
__device__ __forceinline__ uint32_t nz(uint32_t v) { uint32_t r; asm("max.u32 %0, %1, 1;" : "=r"(r) : "r"(v)); return r; }
__device__ __forceinline__ uint32_t tagw(uint32_t w, uint32_t tc) { return ((w & 0x8000ffffu) | min(max(w & 0x7fff0000u, 0x20000000u), 0x5fff0000u)) + tc; }
template <int S_> __device__ __forceinline__ void await7(uint32_t (*r)[4], const char* const* p, uint32_t fz, uint32_t stale) {
    if (S_ == 0) asm volatile("{.reg .b128 t; .reg .pred p; .reg .u32 m, k, n;\nmov.u32 n, %clock; or.b32 n, n, %37; shr.u32 n, n, 31;\nL:\n"
        "min.u32 m, %0, %4; min.u32 m, m, %8; min.u32 m, m, %12; min.u32 m, m, %16; min.u32 m, m, %20; min.u32 m, m, %24;\n"
        "setp.eq.u32 p, m, 0; vote.sync.any.pred p, p, 0xffffffff; add.u32 n, n, 1; setp.lt.and.u32 p, n, %36, p;\n@!p bra.uni D;\n"
        "setp.eq.u32 p, %0, 0; mov.b128 t, {%0,%1,%2,%3}; @p ld.relaxed.gpu.global.b128 t, [%28+%35]; mov.b128 {%0,%1,%2,%3}, t;\n"
        "setp.eq.u32 p, %4, 0; mov.b128 t, {%4,%5,%6,%7}; @p ld.relaxed.gpu.global.b128 t, [%29+%35]; mov.b128 {%4,%5,%6,%7}, t;\n"
        "setp.eq.u32 p, %8, 0; mov.b128 t, {%8,%9,%10,%11}; @p ld.relaxed.gpu.global.b128 t, [%30+%35]; mov.b128 {%8,%9,%10,%11}, t;\n"
        "setp.eq.u32 p, %12, 0; mov.b128 t, {%12,%13,%14,%15}; @p ld.relaxed.gpu.global.b128 t, [%31+%35]; mov.b128 {%12,%13,%14,%15}, t;\n"
        "setp.eq.u32 p, %16, 0; mov.b128 t, {%16,%17,%18,%19}; @p ld.relaxed.gpu.global.b128 t, [%32+%35]; mov.b128 {%16,%17,%18,%19}, t;\n"
        "setp.eq.u32 p, %20, 0; mov.b128 t, {%20,%21,%22,%23}; @p ld.relaxed.gpu.global.b128 t, [%33+%35]; mov.b128 {%20,%21,%22,%23}, t;\n"
        "setp.eq.u32 p, %24, 0; mov.b128 t, {%24,%25,%26,%27}; @p ld.relaxed.gpu.global.b128 t, [%34+%35]; mov.b128 {%24,%25,%26,%27}, t;\n"
        "bra.uni L;\nD:}"
        : "+r"(r[0][0]), "+r"(r[0][1]), "+r"(r[0][2]), "+r"(r[0][3]), "+r"(r[1][0]), "+r"(r[1][1]), "+r"(r[1][2]), "+r"(r[1][3]), "+r"(r[2][0]), "+r"(r[2][1]), "+r"(r[2][2]), "+r"(r[2][3]), "+r"(r[3][0]), "+r"(r[3][1]), "+r"(r[3][2]), "+r"(r[3][3]), "+r"(r[4][0]), "+r"(r[4][1]), "+r"(r[4][2]), "+r"(r[4][3]), "+r"(r[5][0]), "+r"(r[5][1]), "+r"(r[5][2]), "+r"(r[5][3]), "+r"(r[6][0]), "+r"(r[6][1]), "+r"(r[6][2]), "+r"(r[6][3])
        : "l"(p[0]), "l"(p[1]), "l"(p[2]), "l"(p[3]), "l"(p[4]), "l"(p[5]), "l"(p[6]), "n"((4 - S_) * 524288), "n"(SPIN_LIMIT), "r"(fz), "r"(stale) : "memory");
    else asm volatile("{.reg .b128 t; .reg .pred p; .reg .u32 m, k, n;\nmov.u32 n, %clock; or.b32 n, n, %37; shr.u32 n, n, 31;\nL:\n"
        "xor.b32 m, %0, %38; xor.b32 k, %4, %38; and.b32 m, m, k; xor.b32 k, %8, %38; and.b32 m, m, k; xor.b32 k, %12, %38; and.b32 m, m, k; xor.b32 k, %16, %38; and.b32 m, m, k;\n"
        "xor.b32 k, %20, %38; and.b32 m, m, k; xor.b32 k, %24, %38; and.b32 m, m, k; and.b32 m, m, 0x40000000;\n"
        "setp.eq.u32 p, m, 0; vote.sync.any.pred p, p, 0xffffffff; add.u32 n, n, 1; setp.lt.and.u32 p, n, %36, p;\n@!p bra.uni D;\n"
        "xor.b32 k, %0, %38; and.b32 k, k, 0x40000000; setp.eq.u32 p, k, 0; mov.b128 t, {%0,%1,%2,%3}; @p ld.relaxed.gpu.global.b128 t, [%28+%35]; mov.b128 {%0,%1,%2,%3}, t;\n"
        "xor.b32 k, %4, %38; and.b32 k, k, 0x40000000; setp.eq.u32 p, k, 0; mov.b128 t, {%4,%5,%6,%7}; @p ld.relaxed.gpu.global.b128 t, [%29+%35]; mov.b128 {%4,%5,%6,%7}, t;\n"
        "xor.b32 k, %8, %38; and.b32 k, k, 0x40000000; setp.eq.u32 p, k, 0; mov.b128 t, {%8,%9,%10,%11}; @p ld.relaxed.gpu.global.b128 t, [%30+%35]; mov.b128 {%8,%9,%10,%11}, t;\n"
        "xor.b32 k, %12, %38; and.b32 k, k, 0x40000000; setp.eq.u32 p, k, 0; mov.b128 t, {%12,%13,%14,%15}; @p ld.relaxed.gpu.global.b128 t, [%31+%35]; mov.b128 {%12,%13,%14,%15}, t;\n"
        "xor.b32 k, %16, %38; and.b32 k, k, 0x40000000; setp.eq.u32 p, k, 0; mov.b128 t, {%16,%17,%18,%19}; @p ld.relaxed.gpu.global.b128 t, [%32+%35]; mov.b128 {%16,%17,%18,%19}, t;\n"
        "xor.b32 k, %20, %38; and.b32 k, k, 0x40000000; setp.eq.u32 p, k, 0; mov.b128 t, {%20,%21,%22,%23}; @p ld.relaxed.gpu.global.b128 t, [%33+%35]; mov.b128 {%20,%21,%22,%23}, t;\n"
        "xor.b32 k, %24, %38; and.b32 k, k, 0x40000000; setp.eq.u32 p, k, 0; mov.b128 t, {%24,%25,%26,%27}; @p ld.relaxed.gpu.global.b128 t, [%34+%35]; mov.b128 {%24,%25,%26,%27}, t;\n"
        "bra.uni L;\nD:}"
        : "+r"(r[0][0]), "+r"(r[0][1]), "+r"(r[0][2]), "+r"(r[0][3]), "+r"(r[1][0]), "+r"(r[1][1]), "+r"(r[1][2]), "+r"(r[1][3]), "+r"(r[2][0]), "+r"(r[2][1]), "+r"(r[2][2]), "+r"(r[2][3]), "+r"(r[3][0]), "+r"(r[3][1]), "+r"(r[3][2]), "+r"(r[3][3]), "+r"(r[4][0]), "+r"(r[4][1]), "+r"(r[4][2]), "+r"(r[4][3]), "+r"(r[5][0]), "+r"(r[5][1]), "+r"(r[5][2]), "+r"(r[5][3]), "+r"(r[6][0]), "+r"(r[6][1]), "+r"(r[6][2]), "+r"(r[6][3])
        : "l"(p[0]), "l"(p[1]), "l"(p[2]), "l"(p[3]), "l"(p[4]), "l"(p[5]), "l"(p[6]), "n"((4 - S_) * 524288), "n"(SPIN_LIMIT), "r"(fz), "r"(stale) : "memory");
}
template <class T> __device__ __forceinline__ T* pinp(T* p) { return (T*)__shfl_xor_sync(~0u, (unsigned long long)p, 0); }
__device__ __forceinline__ float fsel(bool c, float a, float b) { float r; asm("{.reg .pred p; setp.ne.u32 p, %3, 0; selp.f32 %0, %1, %2, p;}" : "=f"(r) : "f"(a), "f"(b), "r"((int)c)); return r; }
__device__ __forceinline__ void stg4_if(bool c, void* p, uint32_t a, uint32_t b, uint32_t d, uint32_t e) {
    asm volatile("{.reg .b128 t; .reg .pred p; setp.ne.u32 p, %5, 0; mov.b128 t, {%1,%2,%3,%4}; @p st.relaxed.gpu.global.b128 [%0], t;}" ::"l"(p), "r"(a), "r"(b), "r"(d), "r"(e), "r"((int)c) : "memory");
}
__device__ __forceinline__ void stg1_if(bool c, void* p, uint32_t a) {
    asm volatile("{.reg .pred p; setp.ne.u32 p, %2, 0; @p st.relaxed.gpu.global.u32 [%0], %1;}" ::"l"(p), "r"(a), "r"((int)c) : "memory");
}
__device__ __forceinline__ void ldg4_again(uint32_t* r, const void* p) {
    asm volatile("{.reg .b128 t; .reg .pred p; setp.eq.u32 p, %3, 0; mov.b128 t, {%0,%1,%2,%3}; @p ld.relaxed.gpu.global.b128 t, [%4]; mov.b128 {%0,%1,%2,%3}, t;}"
                 : "+r"(r[0]), "+r"(r[1]), "+r"(r[2]), "+r"(r[3]) : "l"(p) : "memory");
}
__device__ __forceinline__ void wgmma_rs_n192(float* d, const uint32_t* a, uint64_t bdesc, int accum) {
    asm volatile("{.reg .pred p; setp.ne.b32 p, %101, 0; wgmma.mma_async.sync.aligned.m64n192k16.f32.bf16.bf16 {%0,%1,%2,%3,%4,%5,%6,%7,%8,%9,%10,%11,%12,%13,%14,%15,%16,%17,%18,%19,%20,%21,%22,%23,%24,%25,%26,%27,%28,%29,%30,%31,%32,%33,%34,%35,%36,%37,%38,%39,%40,%41,%42,%43,%44,%45,%46,%47,%48,%49,%50,%51,%52,%53,%54,%55,%56,%57,%58,%59,%60,%61,%62,%63,%64,%65,%66,%67,%68,%69,%70,%71,%72,%73,%74,%75,%76,%77,%78,%79,%80,%81,%82,%83,%84,%85,%86,%87,%88,%89,%90,%91,%92,%93,%94,%95}, {%96,%97,%98,%99}, %100, p, 1, 1, 1;}"
        : "+f"(d[0]),"+f"(d[1]),"+f"(d[2]),"+f"(d[3]),"+f"(d[4]),"+f"(d[5]),"+f"(d[6]),"+f"(d[7]),"+f"(d[8]),"+f"(d[9]),"+f"(d[10]),"+f"(d[11]),"+f"(d[12]),"+f"(d[13]),"+f"(d[14]),"+f"(d[15]),"+f"(d[16]),"+f"(d[17]),"+f"(d[18]),"+f"(d[19]),"+f"(d[20]),"+f"(d[21]),"+f"(d[22]),"+f"(d[23]),"+f"(d[24]),"+f"(d[25]),"+f"(d[26]),"+f"(d[27]),"+f"(d[28]),"+f"(d[29]),"+f"(d[30]),"+f"(d[31]),"+f"(d[32]),"+f"(d[33]),"+f"(d[34]),"+f"(d[35]),"+f"(d[36]),"+f"(d[37]),"+f"(d[38]),"+f"(d[39]),"+f"(d[40]),"+f"(d[41]),"+f"(d[42]),"+f"(d[43]),"+f"(d[44]),"+f"(d[45]),"+f"(d[46]),"+f"(d[47]),"+f"(d[48]),"+f"(d[49]),"+f"(d[50]),"+f"(d[51]),"+f"(d[52]),"+f"(d[53]),"+f"(d[54]),"+f"(d[55]),"+f"(d[56]),"+f"(d[57]),"+f"(d[58]),"+f"(d[59]),"+f"(d[60]),"+f"(d[61]),"+f"(d[62]),"+f"(d[63]),"+f"(d[64]),"+f"(d[65]),"+f"(d[66]),"+f"(d[67]),"+f"(d[68]),"+f"(d[69]),"+f"(d[70]),"+f"(d[71]),"+f"(d[72]),"+f"(d[73]),"+f"(d[74]),"+f"(d[75]),"+f"(d[76]),"+f"(d[77]),"+f"(d[78]),"+f"(d[79]),"+f"(d[80]),"+f"(d[81]),"+f"(d[82]),"+f"(d[83]),"+f"(d[84]),"+f"(d[85]),"+f"(d[86]),"+f"(d[87]),"+f"(d[88]),"+f"(d[89]),"+f"(d[90]),"+f"(d[91]),"+f"(d[92]),"+f"(d[93]),"+f"(d[94]),"+f"(d[95])
        : "r"(a[0]), "r"(a[1]), "r"(a[2]), "r"(a[3]), "l"(bdesc), "r"(accum));
}
__device__ __forceinline__ void wgmma_rs_n48(float* d, const uint32_t* a, uint64_t bdesc, int accum) {
    asm volatile("{.reg .pred p; setp.ne.b32 p, %29, 0; wgmma.mma_async.sync.aligned.m64n48k16.f32.bf16.bf16 {%0,%1,%2,%3,%4,%5,%6,%7,%8,%9,%10,%11,%12,%13,%14,%15,%16,%17,%18,%19,%20,%21,%22,%23}, {%24,%25,%26,%27}, %28, p, 1, 1, 1;}"
        : "+f"(d[0]),"+f"(d[1]),"+f"(d[2]),"+f"(d[3]),"+f"(d[4]),"+f"(d[5]),"+f"(d[6]),"+f"(d[7]),"+f"(d[8]),"+f"(d[9]),"+f"(d[10]),"+f"(d[11]),"+f"(d[12]),"+f"(d[13]),"+f"(d[14]),"+f"(d[15]),"+f"(d[16]),"+f"(d[17]),"+f"(d[18]),"+f"(d[19]),"+f"(d[20]),"+f"(d[21]),"+f"(d[22]),"+f"(d[23])
        : "r"(a[0]), "r"(a[1]), "r"(a[2]), "r"(a[3]), "l"(bdesc), "r"(accum));
}
__device__ __forceinline__ void wgmma_rs_n80(float* d, const uint32_t* a, uint64_t bdesc, int accum) {
    asm volatile("{.reg .pred p; setp.ne.b32 p, %45, 0; wgmma.mma_async.sync.aligned.m64n80k16.f32.bf16.bf16 {%0,%1,%2,%3,%4,%5,%6,%7,%8,%9,%10,%11,%12,%13,%14,%15,%16,%17,%18,%19,%20,%21,%22,%23,%24,%25,%26,%27,%28,%29,%30,%31,%32,%33,%34,%35,%36,%37,%38,%39}, {%40,%41,%42,%43}, %44, p, 1, 1, 1;}"
        : "+f"(d[0]),"+f"(d[1]),"+f"(d[2]),"+f"(d[3]),"+f"(d[4]),"+f"(d[5]),"+f"(d[6]),"+f"(d[7]),"+f"(d[8]),"+f"(d[9]),"+f"(d[10]),"+f"(d[11]),"+f"(d[12]),"+f"(d[13]),"+f"(d[14]),"+f"(d[15]),"+f"(d[16]),"+f"(d[17]),"+f"(d[18]),"+f"(d[19]),"+f"(d[20]),"+f"(d[21]),"+f"(d[22]),"+f"(d[23]),"+f"(d[24]),"+f"(d[25]),"+f"(d[26]),"+f"(d[27]),"+f"(d[28]),"+f"(d[29]),"+f"(d[30]),"+f"(d[31]),"+f"(d[32]),"+f"(d[33]),"+f"(d[34]),"+f"(d[35]),"+f"(d[36]),"+f"(d[37]),"+f"(d[38]),"+f"(d[39])
        : "r"(a[0]), "r"(a[1]), "r"(a[2]), "r"(a[3]), "l"(bdesc), "r"(accum));
}

__global__ void __cluster_dims__(2, 1, 1) __launch_bounds__(384, 1)
fused_kernel(const __nv_bfloat16* __restrict__ wmod, const __nv_bfloat16* __restrict__ cvec, Scratch* __restrict__ S,
             const __nv_bfloat16* __restrict__ wqkv, const __nv_bfloat16* __restrict__ wo, __nv_bfloat16* __restrict__ out,
             const __nv_bfloat16* __restrict__ wr, const __nv_bfloat16* __restrict__ wg, const __nv_bfloat16* __restrict__ wu,
             const __nv_bfloat16* __restrict__ wd,
             const __grid_constant__ CUtensorMap mm, const __grid_constant__ CUtensorMap mx, const __grid_constant__ CUtensorMap mw,
             const __grid_constant__ CUtensorMap mt, const __grid_constant__ CUtensorMap mo, const __grid_constant__ CUtensorMap mg,
             const __grid_constant__ CUtensorMap mu, const __grid_constant__ CUtensorMap md,
             const __grid_constant__ CUtensorMap mw2, const __grid_constant__ CUtensorMap mout,
             const __grid_constant__ CUtensorMap mo2) {
    extern __shared__ __align__(1024) char sm_raw[];
    const int bid = blockIdx.x;
    const uint32_t sm = ((bid & 1) << 24) + SM0;
    STAMP(30);
    const uint32_t t_start = clock32();
    if (bid < CPF && threadIdx.x == 0)
        asm volatile("cp.async.bulk.prefetch.tensor.2d.L2.global [%0, {%1, %2}];" ::"l"(&mm), "r"((bid & 1) * 640 + (bid >> 4) * 64), "r"(((bid >> 1) & 7) * 80) : "memory");
    const int cl = bid >> 1, rank = bid & 1, c7 = ((cl - 36) * 37) >> 8;
    const int grp = cl < 4 ? 0 : (cl < 36 ? (cl - 4) & 7 : cl - 35 - 7 * c7);
    const int ti = grp * 2 + rank;
    auto ldx = [&](int c) { mbar_expect_tx(BAR(B_XF + c), 16384); tma3d(sm + c * 16384, &mx, c * 64, ti >> 3, (ti & 7) * 128, BAR(B_XF + c)); };
    if (threadIdx.x == 256 && bid < 128) {
        mbar_init(BAR(B_XF), 1); mbar_init(BAR(B_XF + 1), 1);
        pause_until(t_start, XDELAY);
        ldx(0); ldx(1);
        STAMPT(22, 256);
#pragma unroll
        for (int i = 2; i < 10; i++) mbar_init(BAR(B_XF + i), 1);
        mbar_init(BAR(B_T0), 1);
        asm volatile("fence.mbarrier_init.release.cluster;" ::: "memory");
        ldx(2); ldx(3); ldx(4);
    }
    const int warp = __shfl_sync(~0u, threadIdx.x >> 5, 0);

#define PIN(v) __shfl_xor_sync(~0u, (v), 0)
#define LANE_VARS const int tid = PIN(threadIdx.x), lane = tid & 31, g = lane >> 2, q = lane & 3; \
    const uint32_t frow = (lane & 7) + (lane >> 4) * 8, fh = (lane >> 3) & 1;
    if (bid >= 128) {
        LANE_VARS
        const int h = bid - 128;
        if (warp >= 8) {
            if (warp == 8) return;
            const int t = tid - 288;
            if (t < 90) stg4_rlx(&S->tab[(5 + t / 9) * 4 + h][t % 9], 0u, 0u, 0u, 0u);
            __syncwarp();
            asm volatile("bar.arrive 1, 352;" ::: "memory");
            bar_sync(2, 96);
            if (t == 0) asm volatile("red.release.gpu.global.add.u32 [%0], 32;" ::"l"(&S->cnt) : "memory");
            return;
        }
        const uint32_t slot = sm + warp * 20480, bar = BAR(warp * 2);
        auto column = [&](int job) {
            const int n = job * 4 + h;
            return job < 10 ? ((h & 1) ? (job < 5 ? 10 : 30) : (job < 5 ? 0 : 10)) + (n >> 1) : (n < 50 ? n - 10 : n);
        };
        auto load = [&](int job) {
            mbar_expect_tx(bar + (job & 1) * 8, 10240);
            tma2d(slot + (job & 1) * 10240, &mm, column(job) * 64, warp * 80, bar + (job & 1) * 8);
        };
        if (elect1()) { mbar_init(bar, 1); mbar_init(bar + 8, 1); load(0); }
        __syncwarp();
        uint32_t b[10];
#pragma unroll
        for (int s = 0; s < 10; s++) b[s] = ldg1_rlx((const uint32_t*)cvec + warp * 40 + s * 4 + q);
        if (lane < 8 && warp < 5) stg4_rlx(&S->tab[warp * 4 + h][lane], 0u, 0u, 0u, 0u);
#pragma unroll
        for (int s = 0; s < 10; s++) b[s] = pack2(blo(b[s]) * sigm(blo(b[s])), bhi(b[s]) * sigm(bhi(b[s])));
        const uint32_t fa = slot + frow * 128 + ((fh ^ (lane & 7)) << 4);
        const int c0 = (lane >> 3) * 16 + (lane & 1) * 8 + (lane & 6);
#pragma unroll 1
        for (int job = 0; job < 15; job++) {
            uint32_t w2 = 0;
            if (job >= 5) w2 = ldg1_rlx(wr + (column(job) % 10) * 64 + c0);

            mbar_wait(bar + (job & 1) * 8, (job >> 1) & 1);
            if (job == 0) { if (elect1()) load(1); __syncwarp(); }
            float d[4][4] = {};
#pragma unroll
            for (int s = 0; s < 5; s++) {
#pragma unroll
                for (int m = 0; m < 4; m++) { uint32_t a[4]; ldsm4t(a, (fa ^ (m * 32)) + (job & 1) * 10240 + s * 2048); mma16(d[m], a[0], a[1], a[2], a[3], b[2 * s], b[2 * s + 1]); }
            }
            const uint32_t red = sm + OFF_W + (job & 1) * 2048;
            sts1f(red + (warp * 64 + q * 8 + g) * 4, q == 0 ? d[0][0] : (q == 1 ? d[0][2] : (q == 2 ? d[1][0] : d[1][2])));
            sts1f(red + (warp * 64 + 32 + q * 8 + g) * 4, q == 0 ? d[2][0] : (q == 1 ? d[2][2] : (q == 2 ? d[3][0] : d[3][2])));
            __syncwarp();
            if (job < 13 && elect1()) load(job + 2);
            __syncwarp();
            bar_sync(0, 256);
            if (job == 5) bar_sync(1, 352);
            if (warp == (job & 7)) {
                float y0 = 0.f, y1 = 0.f;
#pragma unroll
                for (int w = 0; w < 8; w++) { const float2 v = lds2f(red + (w * 64 + c0) * 4); y0 += v.x; y1 += v.y; }
                const uint32_t t = hf2(pack2(y0, y1), 0x3f803f80u, ((h & 1) && job < 10) ? 0x3f803f80u : 0x80008000u);
                uint32_t* const p = (uint32_t*)&S->tab[job * 4 + h][0];
                stg1_rlx(p + lane, nz(t));
                float dot = fmaf(blo(t), blo(w2), bhi(t) * bhi(w2));
#pragma unroll
                for (int o = 16; o; o >>= 1) dot += __shfl_xor_sync(~0u, dot, o);
                if (lane == 0) stg1_rlx(p + 32, dot == 0.f ? 0x80000000u : __float_as_uint(dot));
            }
            if (job == 0) STAMP(27);
            if (job == 8) STAMP(28);
        }
        STAMP(17);
        return;
    }
    uint32_t ep0;
    if (__builtin_expect(warp == 8, 1)) {
        asm volatile("barrier.cluster.arrive.relaxed.aligned;" ::: "memory");
        if (elect1()) {
#pragma unroll 1
            for (int c = 5; c < 10; c++) ldx(c);
        }
        __syncwarp();
    } else {
        if (warp < 8) {
            if (elect1()) {
#pragma unroll
                for (int i = 0; i < 8; i++) { const int b = B_WF + warp * 8 + i; mbar_init(BAR(b), b >= B_WE ? 16 : (b >= B_G2 ? 8 : (b >= B_EP ? 2 : (b == B_WO ? 7 : 1)))); }
                asm volatile("fence.mbarrier_init.release.cluster;" ::: "memory");
            }
            __syncwarp();
        }
        if (warp == 9) ep0 = ldg1_rlx(&S->cnt);
        asm volatile("barrier.cluster.arrive.relaxed.aligned;" ::: "memory");
    }
    const int sl = cl < 4 ? 4 + cl : (cl < 36 ? (cl - 4) >> 3 : 4 + c7);
    const int j = sl ^ (((sl + 2) >> 2) & 1), role = ti * 8 + j, odd = j & 1;
    const int fi = j * 16 + ti;
    const int al = ((j + 1) & 2) == 0;
    Exch* const X = &S->x;
    if (warp >= 8) {
        asm volatile("setmaxnreg.dec.sync.aligned.u32 72;");
        if (warp == 8) {
            asm volatile("barrier.cluster.wait.aligned;" ::: "memory");
            if (!elect1()) return;
            const int col_main = 80 * j + 16 * odd, col_tail = 80 * j + (odd ? 0 : 64);
            auto load_w = [&](int it) {
                const uint32_t b = BAR(B_WF + it), dst = sm + wbuf(it) + rank * 6144;
                mbar_expect_tx(b, WST);
                tma4d_mc(dst, al ? &mw2 : &mw, 0, it * 32 + rank * 16, col_main >> (5 + al), 0, b);
                tma3d_mc(dst + 12288 - rank * 4608, &mt, col_tail, it * 32 + rank * 16, 0, b);
            };
            int it = 0, wn = 0, gn = 0;
#pragma unroll 1
            for (int r = -2; r < 19; r++) {
                if (r == -1) mbar_wait(BAR(B_XF + XWAIT), 0);
                if (r >= 0) mbar_wait(BAR(B_WE + r), 0);
                const int lim = min(r < 2 ? (r == 1 ? 7 : 2 * r + 6) : r + 7, 20);
#pragma unroll 1
                for (; it < lim; it++) load_w(it);
                if (r == -1 || r == 0) l2_prefetch(wqkv + (size_t)(384 + r * 256 + role * 2) * 1920, 2 * 3840);
                if (r == 0) l2_prefetch(wo + role * 3200, 6400);
                if (r >= MPF0 && r < MPF0 + 10) l2_prefetch(wmod + (size_t)(role * 5 + ((r - MPF0) >> 1)) * 3840 + 1920 + (r & 1) * 1280, 1280);
                if (((GU_MASK >> (r + 2)) & 1) && fi < 108) { if (gn == 0) mbar_expect_tx(BAR(B_FG), 40960); tma2d(sm + OFF_WG + gn * 10240, (fi & 1) ? &mu : &mg, (fi >> 1) * 32, gn * 160, BAR(B_FG)); gn++; }
#pragma unroll 1
                for (int n = ((WO_MASK >> (r + 2)) & 1) + (r == 14); n > 0; n--) {
                    const int row = (j ^ wn) * 80 + rank * 40;
                    const uint32_t b = BAR(wn ? B_WO : B_WO0), dst = sm + wobuf(wn) + rank * 2560;
                    mbar_expect_tx(b, 12800);
                    tma2d_mc(dst, &mo, col_main, row, b); tma2d_mc(dst + 5120, &mo, col_main + 32, row, b); tma2d_mc(dst + 10240, &mo2, col_tail, row, b);
                    wn++;
                }
                if (r >= PF0 && r < PF0 + 3 * PFN) { const int m = (r - PF0) / PFN; l2_prefetch((m == 0 ? wg : (m == 1 ? wu : wd)) + role * 8640 + (r - PF0 - m * PFN) * (8640 / PFN), 17280 / PFN); }
            }
            STAMPT(24, 256);
            if (fi >= 88) { mbar_wait(BAR(B_G2), 0); mbar_expect_tx(BAR(B_FD), 55296); tma3d(sm + OFF_WD, &md, (fi - 88) * 16, 0, 0, BAR(B_FD)); }
            return;
        }
        asm volatile("barrier.cluster.wait.aligned;" ::: "memory");
        const int tid = threadIdx.x, lane = tid & 31, fh = (lane >> 3) & 1;
        int gd = 0;
        if (warp == 9) {
            {
                uint32_t ta = sm + OFF_TAB + fh * 1280 + (lane >> 4) * 128 + (lane & 4) * 16 + (lane & 1) * 32 + (lane & 2) * 4;
                const uint4* tp = &S->tab[lane >> 3][lane & 7];
                pause_until(t_start, TDELAY);
#pragma unroll 1
                for (int e = 0; e < 5; e++) {
                    uint32_t w[4];
                    if (e > 1) mbar_wait(BAR(B_WE + 4 * e - 8), 0);
                    while (true) {
                        ldg4_rlx(w, tp);
                        if (!__any_sync(~0u, min(min(w[0], w[1]), min(w[2], w[3])) == 0) || ++gd > SPIN_LIMIT) break;
                        pause(P_TAB);
                    }
                    sts2(ta, w[0], w[1]); sts2(ta + 16, w[2], w[3]);
                    __syncwarp();
                    if (e == 0) { STAMPT(2, 288); if (lane == 0) sts1(sm + OFF_EP + EP_US + 8, ep0 << 22 & 0x40000000u); }
                    if (lane == 0) mbar_arrive(BAR(e ? B_TB - 1 + e : B_T0));
                    ta += 256; tp += 288;
                }
            }
            uint32_t h[5][4];
            while (ldg1_acq(&S->cnt) != inc(ep0) && ++gd < SPIN_LIMIT) __nanosleep(YSLEEP);
            __syncwarp();
            if (lane == 0) mbar_arrive(BAR(B_RDY));
            mbar_wait(BAR(HALO_GO), 0);
            pause(D_H);
            if ((ti & 7) == 0) {
#pragma unroll
                for (int s = 0; s < 20; s++) h[s >> 2][s & 3] = 0;
            } else {
                do {
#pragma unroll
                    for (int s = 0; s < 5; s++) ldg4_rlx(h[s], &X->halo[(role - 8 - (ti & 8)) * 160 + s * 32 + lane]);
                } while (__any_sync(~0u, min(min(min(h[0][0], h[1][0]), min(h[2][0], h[3][0])), h[4][0]) == 0) && ++gd < SPIN_LIMIT);
            }
            const uint32_t p8 = sm + OFF_P8 - 4096, va = p8 + 2048 + (lane & 7) * VP + (lane >> 3) * 16;
            sts4(p8 + 2048 + 1408 + lane * 16, h[0]); sts4(p8 + 1408 + lane * 16, h[1]); sts2(p8 + (lane >> 4) * 2048 + 1920 + (lane & 15) * 8, h[2][0], h[2][1]);
            stsm4(va, h[3]); stsm4(va + 64, h[4]); stsm2(va + 128, h[2][2], h[2][3]);
            __syncwarp();
            if (lane == 0) mbar_arrive(BAR(B_HL));
            STAMPT(19, 288);
            uint2* const rp = pinp((uint2*)&X->ra[(lane & 7) * 8][0] + ti);
            const uint2* const rq = pinp((const uint2*)&X->ra[grp * 8][0] + (lane & 15));
            const uint32_t tk0 = PIN(((ti & 7) * 128 + lane * 4) * 2 + (ti >> 3) + 1);
            mbar_wait(BAR(B_G3), 0);
            if (j == (ti & 7)) {
                lds4(h[0], sm + OFF_TAB + 1024 + lane * 16);
                const uint32_t k01 = max(h[0][0], h[0][1]), k = max(k01, max(h[0][2], h[0][3])), km = __reduce_max_sync(~0u, k);
                const uint32_t t = tk0 + (k01 == k ? (h[0][0] == k ? 0 : 2) : (h[0][2] == k ? 4 : 6)), tk = __reduce_min_sync(~0u, k == km ? t : ~0u);
                asm volatile("{.reg .pred p; setp.lt.u32 p, %2, 8; @p red.relaxed.gpu.global.max.u64 [%0], %1;}" ::"l"(rp), "l"((unsigned long long)tk << 32 | km), "r"(lane) : "memory");
            }
            pause(D_REC);
            uint32_t kwin;
            bool bad;
            do { ldg2_rlx(h[0], rq); bad = __any_sync(~0u, h[0][1] == 0); kwin = __reduce_max_sync(~0u, h[0][0]); gd++; } while (bad && gd < SPIN_LIMIT);
            {
                const uint32_t t = (h[0][1] - 1) & 2047, wi = (t & 1) * 64 + (t >> 5), wv[4] = {kwin, t, wi, wi * 320}, m = __ballot_sync(~0u, h[0][0] == kwin);
                if ((m & -m) == 1u << lane) { sts4(sm + OFF_EP + EP_US + 32, wv); mbar_arrive(BAR(B_WIN)); }
            }
            if (lane < 8 && role < 20) stg4_rlx(&S->tab[role][lane], 0u, 0u, 0u, 0u);
            return;
        }
        const int at = tid - 320;
        const int kg = at < 40 ? 80 * j + 2 * at : max(fi - 88, 0) * 16 + 2 * (at & 7);
        const uint32_t w2 = *(const uint32_t*)(wr + kg);
        mbar_wait(BAR(B_T0), 0);
        {
            uint4* p = &X->o[4 * 128 * 256] + role * RV + at;
#pragma unroll 1
            for (int r = 0; r < RV / 64; r++) {
                stg4_rlx(p, 0u, 0u, 0u, 0u);
                p += 64;
                __nanosleep(RSLEEP);
            }
        }
        bar_sync(5, 64);
        if (at == 0) { mbar_wait(BAR(B_TB), 0); }
        if (at == 0) asm volatile("red.release.gpu.global.add.u32 [%0], 1;" ::"l"(&S->cnt) : "memory");
        mbar_wait(BAR(B_RDY), 0);
        const uint32_t* const mp = (const uint32_t*)&S->tab[0][0] + ((kg >> 4) & 3) * 8 + (kg & 6) + ((kg >> 3) & 1);
        const int p = odd ? (at < 8 ? at + 32 : at - 8) : at, lm = min(lane, 9);
        const uint32_t a = sm + OFF_EP + (p & 3) * 48 + (p >> 2) * 4;
#pragma unroll 1
        for (int ph = 0; ph < 4; ph++) {
            uint32_t v, us;
            mbar_wait(BAR(ph < 2 ? TB_GO : TB_GO2), 0);
            while (true) {
                v = ldg1_rlx(mp + (ph < 2 ? 20 + ph + (kg >> 6) * 2 : 20 + ph * 10 + (kg >> 6)) * 288);
                us = ldg1_rlx(&S->tab[ph < 2 ? 20 + ph + lm * 2 : 20 + ph * 10 + lm][8]);
                if (!__any_sync(~0u, min(v, us) == 0) || ++gd > SPIN_LIMIT) break;
                __nanosleep(200);
            }
            if (at < 40) {
                sts1(a + ph * 192, v);
                if (ph == 1) {
                    const float u0 = blo(v) * blo(w2), u1 = bhi(v) * bhi(w2);
                    const uint32_t uh = pack2(u0, u1);
                    sts1(a + 768, 0x3f803f80u); sts1(a + 960, uh); sts1(a + 1152, pack2(u0 - blo(uh), u1 - bhi(uh)));
                }
            } else sts1(sm + OFF_EP + EP_GD + (at & 7) * 4, v);
            float t = lane < 10 ? __uint_as_float(us) : 0.f;
#pragma unroll
            for (int o = 1; o < 16; o <<= 1) t += __shfl_xor_sync(~0u, t, o);
            if (at == 0) sts1f(sm + OFF_EP + EP_US + 12 + ph * 4, t);
            __syncwarp();
            if (lane == 0 && ph) mbar_arrive(BAR(B_EP - 1 + ph));
        }
        STAMPT(20, 320);
    } else {
        asm volatile("setmaxnreg.inc.sync.aligned.u32 216;");
        asm volatile("barrier.cluster.wait.aligned;" ::: "memory");
        LANE_VARS
        const int tw = ti * 8 + warp;
        const uint32_t oo = tw * 4096 + j * 512 + lane * 16;
        const uint32_t pair = (uint32_t)(lane & 1) << 24;
        const uint32_t hi = lane >> 4, xa = sm + (warp * 16 + (lane & 15)) * 128 + ((hi ^ (lane & 7)) << 4);
        const uint32_t p8 = sm + OFF_P8 + warp * 2048, q8 = p8 - (warp ? 2048 : 4096), q9 = p8 - 2048 + (warp ? 16384 : 0);
        const uint32_t l16 = PIN(lane * 16), kt = PIN(hi * 16384 + (lane & 15) * 8), va = PIN(p8 + (lane & 7) * VP + (lane >> 3) * 16);
        const uint32_t vc = PIN(p8 + (lane & 7) * VP + fh * 16384 + hi * 16);
        const uint32_t vh = PIN((fh ? p8 : q9) + (lane & 7) * VP + hi * 16), kh = PIN((hi ? q9 : q8) + (lane & 15) * 8);
        const uint32_t mgt = PIN((2 * q > g ? 0xffffu : 0u) | (2 * q + 1 > g ? 0xffff0000u : 0u));
        uint32_t rr0, rr1, nn0, nn1;
        {
            float gA[2][4] = {}, gB[2][4] = {};
            uint32_t xb = sm + (warp * 16 + frow) * 128 + ((fh ^ (lane & 7)) << 4), one[16];
#pragma unroll
            for (int k = 0; k < 16; k++) one[k] = 0x3f803f80u + ((uint32_t)tid >> (12 + k));
#pragma unroll 1
            for (int c = 0; c < 10; c += 2) {
                mbar_wait(BAR(B_XF + c), 0); mbar_wait(BAR(B_XF + c + 1), 0);
                uint32_t a[8][4];
#pragma unroll
                for (int k = 0; k < 8; k++) ldsm4(a[k], (xb ^ ((k & 3) * 32)) + (k >> 2) * 16384);
                xb += 32768;
#pragma unroll
                for (int k = 0; k < 8; k++) {
                    uint32_t t[4];
#pragma unroll
                    for (int e = 0; e < 4; e++) asm volatile("mov.b32 %0, %1;" : "=r"(t[e]) : "r"(a[k][e]));
                    mma16(gA[k & 1], t[0], one[(k & 3) * 4], t[1], one[(k & 3) * 4 + 1], a[k][0], a[k][1]);
                    mma16(gB[k & 1], t[2], one[(k & 3) * 4 + 2], t[3], one[(k & 3) * 4 + 3], a[k][2], a[k][3]);
                }
            }
            const int src = (lane & ~3) | (g >> 1), e = g & 1;
            const float ss0 = __shfl_sync(~0u, e ? gA[0][1] + gA[1][1] : gA[0][0] + gA[1][0], src), ss1 = __shfl_sync(~0u, e ? gB[0][1] + gB[1][1] : gB[0][0] + gB[1][0], src);
            const float m0 = __shfl_sync(~0u, e ? gA[0][3] + gA[1][3] : gA[0][2] + gA[1][2], src) * (1.f / 640), m1 = __shfl_sync(~0u, e ? gB[0][3] + gB[1][3] : gB[0][2] + gB[1][2], src) * (1.f / 640);
            const float r0 = rbf(rsq(fmaxf(ss0 * (1.f / 640) - m0 * m0, 0.f) + 1e-5f)), r1 = rbf(rsq(fmaxf(ss1 * (1.f / 640) - m1 * m1, 0.f) + 1e-5f));
            rr0 = pack2(r0, r0); rr1 = pack2(r1, r1); nn0 = pack2(-m0 * r0, -m0 * r0); nn1 = pack2(-m1 * r1, -m1 * r1);
        }
        uint32_t xr[5][4];
#pragma unroll
        for (int s = 0; s < 5; s++) {
            const int ks = 5 * j + (odd ? (s == 4 ? 0 : s + 1) : s);
            ldsm4(xr[s], (xa ^ ((ks & 3) * 32)) + (ks >> 2) * 16384);
        }
        STAMP(0);
        mbar_wait(BAR(B_T0), 0);
        float acc[120];
#pragma unroll
        for (int i = 0; i < 120; i++) asm volatile("" : "=f"(acc[i]));
        {
            uint32_t a[2][2][4], raw[2][4], tt[2][4];
            uint32_t tb = sm + OFF_TAB + q * 16, xp = xa;
            auto load = [&](int u) {
                ldsm4(raw[0], xp ^ (u * 64)); ldsm4(raw[1], xp ^ (u * 64 + 32));
                lds4(tt[0], tb + u * 64 + 1280); lds4(tt[1], tb + u * 64);
            };
            auto xform = [&](uint32_t (*dst)[4]) {
#pragma unroll
                for (int h = 0; h < 2; h++) {
                    dst[h][0] = hf2(hf2(raw[h][0], rr0, nn0), tt[0][2 * h], tt[1][2 * h]); dst[h][1] = hf2(hf2(raw[h][1], rr1, nn1), tt[0][2 * h], tt[1][2 * h]);
                    dst[h][2] = hf2(hf2(raw[h][2], rr0, nn0), tt[0][2 * h + 1], tt[1][2 * h + 1]); dst[h][3] = hf2(hf2(raw[h][3], rr1, nn1), tt[0][2 * h + 1], tt[1][2 * h + 1]);
                }
            };
            const uint64_t dm0 = al ? mkdesc(SM0, 2048, 1024, 1) : mkdesc(SM0, 1024, 512, 2), dt0 = mkdesc(SM0 + 12288, 512, 256, 3);
            load(0); xform(a[0]);
            STAMP(3);
#pragma unroll 1
            for (int i2 = 0; i2 < 10; i2++) {
#pragma unroll
                for (int u = 0; u < 2; u++) {
                    const int it = i2 * 2 + u;
                    const uint32_t bo = wbuf(it) >> 4;
                    mbar_wait(BAR(B_WF + it), 0);
                    if (LAG && warp < 4 && i2 * 2 + u == 20 - LAG) bar_sync(4, 256);
                    wg_fence();
#pragma unroll
                    for (int h = 0; h < 2; h++) { wgmma_rs_n192(acc, a[u][h], dm0 + bo + h * 384, (u | h) ? 1 : i2); wgmma_rs_n48(acc + 96, a[u][h], dt0 + bo + h * 96, (u | h) ? 1 : i2); }
                    wg_commit();
                    if (LAG && u == 1 && warp >= 4 && i2 == 9) asm volatile("bar.arrive 4, 256;" ::: "memory");
                    if (u == 1) { xp += 16384; tb += 128; }
                    if (u == 1 && (i2 & 1) && i2 < 9) mbar_wait(BAR(B_TB + (i2 >> 1)), 0);
                    load(u ^ 1);
                    wg_wait<1>();
                    if (lane < 2 && (u == 1 || i2 > 0)) mbar_arrive_cl(pair + BAR0(B_WE - 1 + it));
                    xform(a[u ^ 1]);
                }
            }
        }
        uint32_t own[5][4], ab[3][7][4], sv, tc, fz = 0;
        const char* op[7];
        auto ldo = [&](int s, uint32_t (*dst)[4]) {
#pragma unroll
            for (int w = 0; w < 7; w++) ldg4_rlx(dst[w], op[w] + (4 - s) * 524288);
        };
        {
            uint32_t Q[10][2], K[2][10], V[2][10];
            mbar_wait(BAR(B_RDY), 0);
            const bool pub = warp == 7 && (~ti & 7);
            uint4* const hp = pinp(&X->halo[(role - (ti & 8)) * 160 + lane]);
            sv = lds1(sm + OFF_EP + EP_US + 8); tc = (sv ^ 0x40000000u) - 0x20000000u;
            wg_wait<0>();
            STAMP(4); STAMPT(18, 128);
#define ACC_IDX(t, m) (odd_ ? (t >= 2 ? m * 32 + (t - 2) * 4 : 96 + m * 8 + t * 4) : (t < 8 ? m * 32 + t * 4 : 96 + m * 8 + (t - 8) * 4))
#define PACK1(odd_v) { constexpr bool odd_ = odd_v; _Pragma("unroll") for (int t = 0; t < 10; t++) { \
                K[1][t] = pack2(acc[ACC_IDX(t, 1) + 2], acc[ACC_IDX(t, 1) + 3]); V[1][t] = pack2(acc[ACC_IDX(t, 2) + 2], acc[ACC_IDX(t, 2) + 3]); } }
#define PACK2(odd_v) { constexpr bool odd_ = odd_v; _Pragma("unroll") for (int t = 0; t < 10; t++) { \
                V[0][t] = pack2(acc[ACC_IDX(t, 2)], acc[ACC_IDX(t, 2) + 1]); \
                K[0][t] = pack2(acc[ACC_IDX(t, 1)], acc[ACC_IDX(t, 1) + 1]); \
                Q[t][0] = pack2(acc[ACC_IDX(t, 0)], acc[ACC_IDX(t, 0) + 1]); Q[t][1] = pack2(acc[ACC_IDX(t, 0) + 2], acc[ACC_IDX(t, 0) + 3]); } }
            if (odd) PACK1(true) else PACK1(false)
            if (pub) {
                K[1][0] = nz(K[1][0]); K[1][5] = nz(K[1][5]); K[1][2] = nz(K[1][2]); V[1][0] = nz(V[1][0]); V[1][4] = nz(V[1][4]);
                stg4_rlx(hp, K[1][0], K[1][1], K[1][3], K[1][4]); stg4_rlx(hp + 32, K[1][5], K[1][6], K[1][8], K[1][9]);
                stg4_rlx(hp + 96, V[1][0], V[1][1], V[1][2], V[1][3]); stg4_rlx(hp + 128, V[1][4], V[1][5], V[1][6], V[1][7]); stg4_rlx(hp + 64, K[1][2], K[1][7], V[1][8], V[1][9]);
            }
            uint32_t VT[5][4], KH[10];
            {
                const uint32_t k0[4] = {K[1][0], K[1][1], K[1][3], K[1][4]}, k1[4] = {K[1][5], K[1][6], K[1][8], K[1][9]};
                sts4(p8 + 16384 + 1408 + l16, k0); sts4(p8 + 1408 + l16, k1); sts2(p8 + 1920 + kt, K[1][2], K[1][7]);
                stsm4(va + 16384, V[1]); stsm4(va + 16384 + 64, V[1] + 4); stsm2(va + 16384 + 128, V[1][8], V[1][9]);
            }
            __syncwarp();
            if (lane == 0) mbar_arrive(BAR(B_HL + 1 + warp));
            if (odd) PACK2(true) else PACK2(false)
            stsm4(va, V[0]); stsm4(va + 64, V[0] + 4); stsm2(va + 128, V[0][8], V[0][9]);
            __syncwarp();
#pragma unroll
            for (int s = 0; s < 5; s++) ldsm4t(VT[s], vc + s * 32);
            float sb[4][4], sc[4][4];
            uint32_t qs[4][2];
#pragma unroll
            for (int h = 0; h < 4; h++) {
                const int ts = (h >> 1) * 5 + 2, ta = (h >> 1) * 5 + (h & 1) * 3;
                const bool mine = (q >> 1) == (h & 1);
                qs[h][0] = mine ? Q[ts][0] : 0u; qs[h][1] = mine ? Q[ts][1] : 0u;
                mma16c(sb[h], Q[ta][0], Q[ta][1], Q[ta + 1][0], Q[ta + 1][1], K[0][ta], K[0][ta + 1], 0.f, 0.f);
                mma16c(sc[h], Q[ta][0], Q[ta][1], Q[ta + 1][0], Q[ta + 1][1], K[1][ta], K[1][ta + 1], 0.f, 0.f);
                mma8(sb[h], qs[h][0], qs[h][1], K[0][ts]);
                mma8(sc[h], qs[h][0], qs[h][1], K[1][ts]);
            }
            const bool gt0 = mgt & 1, gt1 = (int)mgt < 0;
            auto half = [&](int h0, int h1, int e, float (*pv)[4], float (*cu)[4], uint32_t (*VT)[4]) {
                const float cs = 0.22360679774997896f * 1.4426950408889634f;
                uint32_t p[4];
                float t0[4], t1[4], m[4];
#pragma unroll
                for (int h = h0; h < h1; h++) { t0[h] = gt0 ? pv[h][2 * e] : cu[h][2 * e]; t1[h] = gt1 ? pv[h][2 * e + 1] : cu[h][2 * e + 1]; m[h] = fmaxf(t0[h], t1[h]); }
#pragma unroll
                for (int h = h0; h < h1; h++) m[h] = fmaxf(m[h], __shfl_xor_sync(~0u, m[h], 1));
#pragma unroll
                for (int h = h0; h < h1; h++) m[h] = fmaxf(m[h], __shfl_xor_sync(~0u, m[h], 2)) * -cs;
#pragma unroll
                for (int h = h0; h < h1; h++) p[h] = pack2(ex2(fmaf(t0[h], cs, m[h])), ex2(fmaf(t1[h], cs, m[h])));
#pragma unroll
                for (int pr = h0 / 2; pr < h1 / 2; pr++) {
                    const uint32_t a0 = p[2 * pr] & mgt, a1 = p[2 * pr + 1] & mgt, a2 = p[2 * pr] & ~mgt, a3 = p[2 * pr + 1] & ~mgt;
                    float l[4];
                    mma16c(l, a0, a1, a2, a3, 0x3f803f80u, 0x3f803f80u, 0.f, 0.f);
                    l[0] = rcp(l[0]); l[2] = rcp(l[2]);
#pragma unroll
                    for (int r = 0; r < 5; r++) {
                        const int t = pr * 5 + r;
                        float d[4];
                        mma16c(d, a0, a1, a2, a3, VT[t >> 1][(t & 1) * 2], VT[t >> 1][(t & 1) * 2 + 1], 0.f, 0.f);
                        const bool od = r == 2 ? (q & 2) : r > 2;
                        const float li = od ? l[2] : l[0];
                        own[t >> 1][(t & 1) * 2 + e] = pack2((od ? d[2] : d[0]) * li, (od ? d[3] : d[1]) * li);
                    }
                }
            };
            mbar_wait(BAR(B_HL + warp), 0);
            uint32_t VH[5][4];
            float sa[4][4];
            lds4(KH, q9 + 1408 + l16); lds4(KH + 4, q8 + 1408 + l16); lds2(KH + 8, kh + 1920);
#pragma unroll
            for (int s = 0; s < 5; s++) ldsm4t(VH[s], vh + s * 32);
            STAMP(5); STAMPT(25, 64);
            fz |= clock32();
            const float ninf = (tw & 63) == 0 ? -INFINITY : 0.f;
#pragma unroll
            for (int h = 0; h < 4; h++) {
                const int ta = (h >> 1) * 5 + (h & 1) * 3;
                mma16c(sa[h], Q[ta][0], Q[ta][1], Q[ta + 1][0], Q[ta + 1][1], KH[2 * h], KH[2 * h + 1], ninf, ninf);
                mma8(sa[h], qs[h][0], qs[h][1], KH[8 + (h >> 1)]);
            }
            auto sto = [&](int s) { own[s][0] = s ? tagw(own[s][0], tc) : nz(own[s][0]); stg4_rlx((char*)X->o + oo + (4 - s) * 524288, own[s][0], own[s][1], own[s][2], own[s][3]); };
            if (SPLIT == 1) {
                half(0, 2, 1, sb, sc, VT); half(0, 2, 0, sa, sb, VH);
                sto(0); sto(1);
                fz |= clock32();
                half(2, 4, 1, sb, sc, VT); half(2, 4, 0, sa, sb, VH);
                if (ELD) {
#pragma unroll
                    for (int w = 0; w < 7; w++) op[w] = (const char*)X->o + (oo ^ (w * 512 + 512));
                    fz |= clock32();
                    if (ELD == 4) sto(2);
                    ldo(0, ab[0]);
                    if (ELD == 2) ldo(1, ab[1]);
                }
                if (ELD != 4) sto(2);
                sto(3); sto(4);
            } else {
                half(0, 4, 1, sb, sc, VT); half(0, 4, 0, sa, sb, VH);
                sto(0); sto(1); sto(2); sto(3); sto(4);
            }
#pragma unroll
            for (int w = 0; w < 7; w++) op[w] = (const char*)X->o + (oo ^ (w * 512 + 512));
        }
        STAMP(6); STAMPT(21, 128); STAMPT(26, 64);
        float ac2[40];
#pragma unroll
        for (int i = 0; i < 40; i++) asm volatile("" : "=f"(ac2[i]));
        {
            const uint64_t d0 = mkdesc(SM0, 5120, 512, 2);
            mbar_wait(BAR(B_WO0), 0);
#pragma unroll
            for (int s = 1; s < 5; s++) own[s][0] -= tc;
            wg_fence();
#pragma unroll
            for (int s = 0; s < 5; s++) wgmma_rs_n80(ac2, own[s], d0 + (wobuf(0) >> 4) + s * 64, s);
            wg_commit();
            const uint32_t t6 = clock32();
            fz |= t6;
            if (!ELD) { pause_until(t6, D_O); ldo(0, ab[0]); }
            if (ELD == 3) ldo(1, ab[1]);
            mbar_wait(BAR(B_WO), 0);
#pragma unroll
            for (int s = 0; s < 5; s++) {
                uint32_t (*cur)[4] = ab[s % 3];
                if (s == 0) await7<0>(cur, op, fz, sv);
                else {
                    if (s == 1) await7<1>(cur, op, fz, sv); else if (s == 2) await7<2>(cur, op, fz, sv); else if (s == 3) await7<3>(cur, op, fz, sv); else await7<4>(cur, op, fz, sv);
#pragma unroll
                    for (int w = 0; w < 7; w++) cur[w][0] -= tc;
                }
                if (s == 0) { STAMP(7); STAMPT(1, 128); }
                wg_fence();
#pragma unroll
                for (int w = 1; w < 8; w++) wgmma_rs_n80(ac2, cur[w - 1], d0 + (wobuf(w) >> 4) + s * 64, 1);
                wg_commit();
                if (s < 3) { if (s) wg_wait<1>(); else fz |= clock32(); if (s == 0 && ELD != 2 && ELD != 3) ldo(1, ab[1]); if (s == 0 && D_2) pause_until(t6, D_2); ldo(s + 2, ab[(s + 2) % 3]); }
                if (s == FD_AT && lane == 0) mbar_arrive(BAR(B_G2));
            }
        }
        mbar_wait(BAR(B_EP), 0);
        uint32_t tga[12], tst[12];
        const uint32_t ep = sm + OFF_EP + q * 48;
#pragma unroll
        for (int s = 0; s < 3; s++) { lds4(tga + 4 * s, ep + s * 16); lds4(tst + 4 * s, ep + 768 + min(g, 2) * 192 + s * 16); }
        uint4* const sp0 = pinp(&X->stats[j][tw * 16 + g]);
        const int prow = (ti & 7) * 128 + warp * 16;
        const uint4* const sp = pinp(&X->stats[hi * 4][tw * 16 + (lane & 15)]);
        const int dsrc = PIN((lane & ~3) | (g >> 1));
        wg_wait<0>();
        if (lane == 0) mbar_arrive(BAR(B_G4));
        STAMP(8); STAMPT(23, 128);
        {
            float gA[2][4] = {}, gB[2][4] = {}, sd[4] = {};
#pragma unroll
            for (int s = 0; s < 5; s++) {
#pragma unroll
                for (int e = 0; e < 4; e++) xr[s][e] = hf2(tga[2 * s + (e >> 1)], pack2(ac2[s * 8 + e * 2], ac2[s * 8 + e * 2 + 1]), xr[s][e]);
                mma16(sd, xr[s][0], xr[s][1], xr[s][2], xr[s][3], tst[2 * s], tst[2 * s + 1]);
                mma8(gA[0], xr[s][0], xr[s][1], xr[s][0]); mma8(gB[0], xr[s][0], xr[s][1], xr[s][1]);
                mma8(gA[1], xr[s][2], xr[s][3], xr[s][2]); mma8(gB[1], xr[s][2], xr[s][3], xr[s][3]);
            }
            const float l0 = __shfl_down_sync(~0u, sd[0], 1), l1 = __shfl_down_sync(~0u, sd[2], 1);
            const float q0 = __shfl_sync(~0u, fsel(g & 1, gA[0][1] + gA[1][1], gA[0][0] + gA[1][0]), dsrc), q1 = __shfl_sync(~0u, fsel(g & 1, gB[0][3] + gB[1][3], gB[0][2] + gB[1][2]), dsrc);
            stg4_if(q == 0, sp0, __float_as_uint(sd[0]), __float_as_uint(sd[1] + l0), __float_as_uint(q0), 1u);
            stg4_if(q == 0, sp0 + 8, __float_as_uint(sd[2]), __float_as_uint(sd[3] + l1), __float_as_uint(q1), 1u);
        }
        const uint32_t t9 = clock32();
        STAMP(9);
        uint32_t fg[5][4], fu[5][4], tcb[12], tsb[12];
        uint32_t st[4][4];
        if (fi < 108) {
            mbar_wait(BAR(B_FG), 0);
#pragma unroll
            for (int s = 0; s < 5; s++) {
                const uint32_t off = sm + OFF_WG + (5 * warp + ((warp & 1) ? (s == 4 ? 0 : s + 1) : s)) * 1024 + frow * 64 + ((fh ^ ((lane >> 1) & 3)) << 4);
                ldsm4t(fg[s], off); ldsm4t(fu[s], off ^ 32);
            }
        }
        pause_until(t9, D_ST);
#pragma unroll
        for (int e = 0; e < 4; e++) ldg4_rlx(st[e], sp + e * 2056);
        mbar_wait(BAR(B_EP2), 0);
#pragma unroll
        for (int s = 0; s < 3; s++) { lds4(tcb + 4 * s, ep + 192 + s * 16); lds4(tsb + 4 * s, ep + 384 + s * 16); }
        int crow;
        {
            const float2 su = lds2f(sm + OFF_EP + EP_US + 16);
            int gd = 0;
            const uint32_t ka = PIN(sm + OFF_TAB + 1024 + warp * 64 + (lane & 15) * 4);
            gd = clock32() >> 31;
            float v[3];
            bool bad;
            while (true) {
                bad = __any_sync(~0u, (st[0][3] & st[1][3] & st[2][3] & st[3][3]) == 0);
#pragma unroll
                for (int e = 0; e < 3; e++) {
                    v[e] = (__uint_as_float(st[0][e]) + __uint_as_float(st[1][e])) + (__uint_as_float(st[2][e]) + __uint_as_float(st[3][e]));
                    v[e] += __shfl_xor_sync(~0u, v[e], 16);
                }
                if (!bad || ++gd > SPIN_LIMIT) break;
#pragma unroll
                for (int e = 0; e < 4; e++) ldg4_again(st[e], sp + e * 2056);
            }
            STAMP(10);
            const float m = v[0] * (1.f / 640), rs = rsq(fmaxf(fmaf(v[2], 1.f / 640, 1e-5f) - m * m, 1e-5f));
            const uint32_t key = fkey(fmaf(rs, fmaf(-m, su.x, v[1]), su.y));
            sts1(ka, key);
            __syncwarp();
            if (lane == 0) mbar_arrive(BAR(B_G3));
            gd = clock32() >> 31;
            crow = (__ffs(__ballot_sync(~0u, key == __reduce_max_sync(~0u, key))) - 1 + gd * 16) & 15;
            const uint32_t rn = pack2(rs, -m * rbf(rs)), a0 = __shfl_sync(~0u, rn, g), a1 = __shfl_sync(~0u, rn, g + 8);
            rr0 = __byte_perm(a0, 0, 0x1010); nn0 = __byte_perm(a0, 0, 0x3232); rr1 = __byte_perm(a1, 0, 0x1010); nn1 = __byte_perm(a1, 0, 0x3232);
        }
        {
            const bool up = crow >= 8;
            const uint32_t rr = up ? rr1 : rr0, nn = up ? nn1 : nn0;
            if (g == (crow & 7)) {
                uint4* cp = &X->cand[j][tw * 20 + q];
#pragma unroll
                for (int s = 0; s < 5; s++) {
                    const uint32_t xa_ = up ? xr[s][1] : xr[s][0], xb_ = up ? xr[s][3] : xr[s][2];
                    stg4_rlx(cp + s * 4, nz(hf2(hf2(xa_, rr, nn), tcb[2 * s], tsb[2 * s])), hf2(hf2(xb_, rr, nn), tcb[2 * s + 1], tsb[2 * s + 1]), xa_, xb_);
                }
            }
        }
        STAMP(11);
        const uint32_t stg = sm + 5 * WST + warp * 2560;
        {
            mbar_wait(BAR(B_EP3), 0);
#pragma unroll
            for (int s = 0; s < 3; s++) lds4(tga + 4 * s, ep + 576 + s * 16);
#pragma unroll
            for (int s = 0; s < 5; s++) {
#pragma unroll
                for (int e = 0; e < 4; e++) { const int t = 2 * s + (e >> 1); xr[s][e] = hf2(tga[t], hf2(hf2(xr[s][e], (e & 1) ? rr1 : rr0, (e & 1) ? nn1 : nn0), tcb[t], tsb[t]), xr[s][e]); }
            }
            mbar_wait(BAR(B_G4), 0);
#pragma unroll
            for (int s = 0; s < 5; s++) stsm4(stg + (lane & 15) * 160 + (odd ? (s == 4 ? 0 : s + 1) : s) * 32 + hi * 16, xr[s]);
            asm volatile("fence.proxy.async.shared::cta;" ::: "memory");
            __syncwarp();
            if (elect1()) tma3d_st(&mout, 80 * j, ti >> 3, prow + (~crow & 8), stg + (~crow & 8) * 160);
        }
        STAMP(12);
        const char* cp = (const char*)pinp(&X->cand[warp][q]);
        uint32_t* const ap0 = pinp((uint32_t*)&X->ra[fi >> 1][8 + (fi & 1) * 4] + (lane & 8) + (lane & 3) * 2 + ((lane >> 2) & 1));
        const uint32_t rw = PIN(sm + OFF_RED - 256 + (q * 4 + (g >> 1)) * 80 + warp * 8 + (g & 1) * 4), rd = PIN(sm + OFF_RED - 256 + (lane & 15) * 80);
        if (smem_u32(sm_raw) != sm) return;
        uint32_t wv[4]; int gd = 0;
        mbar_wait(BAR(B_WIN), 0);
        lds4(wv, sm + OFF_EP + EP_US + 32);
        const uint32_t kwin = wv[0];
        const int tokwin = wv[1], win = wv[2];
        STAMP(13);
        if (fi < 108) {
            uint32_t hb[5][2];
            float mine;
            bool bad;
            cp += wv[3];
            do {
#pragma unroll
                for (int s = 0; s < 5; s++) ldg2_rlx(hb[s], cp + s * 64);
                bad = __any_sync(~0u, min(min(min(hb[0][0], hb[1][0]), min(hb[2][0], hb[3][0])), hb[4][0]) == 0);
                float dg[2][4] = {}, du[2][4] = {};
#pragma unroll
                for (int s = 0; s < 5; s++) {
                    mma16(dg[s & 1], fg[s][0], fg[s][1], fg[s][2], fg[s][3], hb[s][0], hb[s][1]);
                    mma16(du[s & 1], fu[s][0], fu[s][1], fu[s][2], fu[s][3], hb[s][0], hb[s][1]);
                }
                mine = fsel(q & 2, fsel(q & 1, du[1][2], du[1][0]), fsel(q & 1, dg[1][2], dg[1][0])) + fsel(q & 2, fsel(q & 1, du[0][2], du[0][0]), fsel(q & 1, dg[0][2], dg[0][0]));
                sts1f(rw, mine);
                gd++;
            } while (bad && gd < SPIN_LIMIT);
            bar_sync(2, 256);
            if (warp == 0) {
                uint32_t v[4][4];
#pragma unroll
                for (int e = 0; e < 4; e++) lds4(v[e], rd + e * 16);
                float t[2];
#pragma unroll
                for (int e = 0; e < 2; e++)
                    t[e] = ((__uint_as_float(v[0][e]) + __uint_as_float(v[0][e + 2])) + (__uint_as_float(v[1][e]) + __uint_as_float(v[1][e + 2]))) +
                           ((__uint_as_float(v[2][e]) + __uint_as_float(v[2][e + 2])) + (__uint_as_float(v[3][e]) + __uint_as_float(v[3][e + 2])));
                uint32_t pr = pack2(t[0], t[1]);
                if (!(fi & 1)) pr = pack2(blo(pr) * sigm(blo(pr)), bhi(pr) * sigm(bhi(pr)));
                stg1_if(lane < 16, ap0, nz(pr));
            }
        }
        STAMP(14);
        if (win != tw) {
            if (elect1()) tma3d_st(&mout, 80 * j, ti >> 3, prow + (crow & 8), stg + (crow & 8) * 160);
        } else {
#pragma unroll 1
            for (int r = crow & 8; r <= (crow | 7); r++)
                if (r != crow && lane < 20) { uint32_t v[2]; lds2(v, stg + r * 160 + lane * 8); *(uint2*)(out + (size_t)((prow + r) * 2 + (ti >> 3)) * 640 + 80 * j + lane * 4) = make_uint2(v[0], v[1]); }
        }
        if (fi >= 88) {
            const int d = fi - 88, dj = d / 5, dm = d - dj * 5, sp = (dj & 1) ? (dm == 0 ? 4 : dm - 1) : dm;
            const int ks0 = min(warp * 14, 94);
            const uint32_t frag = frow * 32 + ((fh ^ ((lane >> 2) & 1)) << 4);
            uint32_t fd[14][4];
            mbar_wait(BAR(B_FD), 0);
#pragma unroll
            for (int s = 0; s < 14; s++) ldsm4t(fd[s], sm + OFF_WD + (ks0 + s) * 512 + frag);
            const float sf = sigm(rbf(__uint_as_float((kwin & 0x80000000u) ? kwin & 0x7fffffffu : ~kwin)));
            const uint32_t sg = PIN(pack2(sf, sf));
            const uint32_t gbd = lds1(sm + OFF_EP + EP_GD + (lane & 7) * 4);
            uint32_t* const op = (uint32_t*)(out + (size_t)tokwin * 640 + d * 16) + (lane & 7);
            uint32_t bsv[4], ag[4], au[4];
            const uint4* ap = &X->ra[(ks0 >> 1) + min(g, 6)][8 + q];
            const uint32_t keep = warp == 7 && g < 2 ? 0u : ~0u;
            const uint32_t as = PIN(sm + 7 * WST + warp * 512 + q * 16), aw = PIN(sm + 7 * WST + warp * 512 + g * 64 + (q & 1) * 32 + (q >> 1) * 8);
            const uint32_t yw = PIN(sm + OFF_TAB + ((q & 1) * 4 + (g >> 1)) * 80 + warp * 8 + (g & 1) * 4), yr = PIN(sm + OFF_TAB + (lane & 7) * 80);
            bool bad;
            do {
                ldg4_rlx(ag, ap); ldg4_rlx(au, ap + 4); ldg4_rlx(bsv, &X->cand[dj][win * 20 + sp * 4 + q]);
                bad = __any_sync(~0u, min(min(min(min(ag[0], ag[1]), min(ag[2], ag[3])), min(min(au[0], au[1]), min(au[2], au[3]))), bsv[0]) == 0);
                sts2(aw, hm2(ag[0], au[0]) & keep, hm2(ag[1], au[1]) & keep); sts2(aw + 16, hm2(ag[2], au[2]) & keep, hm2(ag[3], au[3]) & keep);
                gd++;
            } while (bad && gd < SPIN_LIMIT);
            STAMP(15);
            __syncwarp();
            float dy[4][4] = {};
            uint32_t av[7][4];
#pragma unroll
            for (int s = 0; s < 7; s++) lds4(av[s], as + s * 64);
#pragma unroll
            for (int s = 0; s < 7; s++) {
                mma16(dy[(2 * s) & 3], fd[2 * s][0], fd[2 * s][1], fd[2 * s][2], fd[2 * s][3], av[s][0], av[s][1]);
                mma16(dy[(2 * s + 1) & 3], fd[2 * s + 1][0], fd[2 * s + 1][1], fd[2 * s + 1][2], fd[2 * s + 1][3], av[s][2], av[s][3]);
            }
            sts1f(yw, (fsel(q & 1, dy[2][2], dy[2][0]) + fsel(q & 1, dy[3][2], dy[3][0])) + (fsel(q & 1, dy[0][2], dy[0][0]) + fsel(q & 1, dy[1][2], dy[1][0])));
            bar_sync(2, 256);
            if (warp == 0) {
                uint32_t v[4][4];
#pragma unroll
                for (int e = 0; e < 4; e++) lds4(v[e], yr + e * 16);
                float t[2];
#pragma unroll
                for (int e = 0; e < 2; e++)
                    t[e] = ((__uint_as_float(v[0][e]) + __uint_as_float(v[0][e + 2])) + (__uint_as_float(v[1][e]) + __uint_as_float(v[1][e + 2]))) +
                           ((__uint_as_float(v[2][e]) + __uint_as_float(v[2][e + 2])) + (__uint_as_float(v[3][e]) + __uint_as_float(v[3][e + 2])));
                const uint32_t hh = (lane & 4) ? bsv[1] : bsv[0], xx = (lane & 4) ? bsv[3] : bsv[2];
                if (lane < 8) *op = hf2(gbd, hf2(hm2(pack2(t[0], t[1]), sg), 0x3f803f80u, hh), xx);
            }
        }
        asm volatile("cp.async.bulk.commit_group;\ncp.async.bulk.wait_group.read 0;" ::: "memory");
        STAMP(16);
    }
}

typedef CUresult (*EncFn)(CUtensorMap*, CUtensorMapDataType, cuuint32_t, void*, const cuuint64_t*, const cuuint64_t*, const cuuint32_t*, const cuuint32_t*,
                          CUtensorMapInterleave, CUtensorMapSwizzle, CUtensorMapL2promotion, CUtensorMapFloatOOBfill);
static void make_map(EncFn enc, CUtensorMap* m, const void* base, int rank, const cuuint64_t* dims, const cuuint64_t* strides, const cuuint32_t* box, CUtensorMapSwizzle sw) {
    const cuuint32_t es[5] = {1, 1, 1, 1, 1};
    enc(m, CU_TENSOR_MAP_DATA_TYPE_BFLOAT16, rank, (void*)base, dims, strides, box, es, CU_TENSOR_MAP_INTERLEAVE_NONE, sw, CU_TENSOR_MAP_L2_PROMOTION_NONE, CU_TENSOR_MAP_FLOAT_OOB_FILL_NONE);
}

extern "C" void kernel_launch(void* const* d_in, const int* in_sizes, int n_in, void* d_out, int out_size) {
    typedef const __nv_bfloat16* P;
    P x = (P)d_in[0], wqkv = (P)d_in[1], wo = (P)d_in[2], wr = (P)d_in[4], wg = (P)d_in[5], wu = (P)d_in[6], wd = (P)d_in[7], c = (P)d_in[8], wmod = (P)d_in[9];
    void* fn = nullptr; cudaDriverEntryPointQueryResult qr;
    cudaGetDriverEntryPoint("cuTensorMapEncodeTiled", &fn, cudaEnableDefault, &qr);
    EncFn enc = (EncFn)fn;
    CUtensorMap mx, mw, mt, mo, mg, mu, md, mm, mw2, mout, mo2;
    { cuuint64_t d[] = {640, 2, 1024}, s[] = {1280, 2560}; cuuint32_t b[] = {64, 1, 128}; make_map(enc, &mx, x, 3, d, s, b, CU_TENSOR_MAP_SWIZZLE_128B); }
    { cuuint64_t d[] = {32, 640, 20, 3}, s[] = {3840, 64, 1280}; cuuint32_t b[] = {32, 16, 2, 3}; make_map(enc, &mw, wqkv, 4, d, s, b, CU_TENSOR_MAP_SWIZZLE_64B); }
    { cuuint64_t d[] = {640, 640, 3}, s[] = {3840, 1280}; cuuint32_t b[] = {16, 16, 3}; make_map(enc, &mt, wqkv, 3, d, s, b, CU_TENSOR_MAP_SWIZZLE_32B); }
    { cuuint64_t d[] = {640, 640}, s[] = {1280}; cuuint32_t b[] = {32, 40}; make_map(enc, &mo, wo, 2, d, s, b, CU_TENSOR_MAP_SWIZZLE_64B);
      b[0] = 16; make_map(enc, &mo2, wo, 2, d, s, b, CU_TENSOR_MAP_SWIZZLE_64B); }
    { cuuint64_t d[] = {1728, 640}, s[] = {3456}; cuuint32_t b[] = {32, 160}; make_map(enc, &mg, wg, 2, d, s, b, CU_TENSOR_MAP_SWIZZLE_64B); make_map(enc, &mu, wu, 2, d, s, b, CU_TENSOR_MAP_SWIZZLE_64B); }
    { cuuint64_t d[] = {640, 216, 8}, s[] = {1280, 1280 * 216}; cuuint32_t b[] = {16, 216, 8}; make_map(enc, &md, wd, 3, d, s, b, CU_TENSOR_MAP_SWIZZLE_32B); }
    { cuuint64_t d[] = {3840, 640}, s[] = {7680}; cuuint32_t b[] = {64, 80}; make_map(enc, &mm, wmod, 2, d, s, b, CU_TENSOR_MAP_SWIZZLE_128B); }
    { cuuint64_t d[] = {64, 640, 10, 3}, s[] = {3840, 128, 1280}; cuuint32_t b[] = {64, 16, 1, 3}; make_map(enc, &mw2, wqkv, 4, d, s, b, CU_TENSOR_MAP_SWIZZLE_128B); }
    { cuuint64_t d[] = {640, 2, 1024}, s[] = {1280, 2560}; cuuint32_t b[] = {80, 1, 8}; make_map(enc, &mout, d_out, 3, d, s, b, CU_TENSOR_MAP_SWIZZLE_NONE); }
    void* sp = nullptr;
    cudaGetSymbolAddress(&sp, g_s);
    cudaFuncSetAttribute(fused_kernel, cudaFuncAttributeMaxDynamicSharedMemorySize, SMEM_BYTES);
    fused_kernel<<<132, 384, SMEM_BYTES>>>(wmod, c, (Scratch*)sp, wqkv, wo, (__nv_bfloat16*)d_out, wr, wg, wu, wd, mm, mx, mw, mt, mo, mg, mu, md, mw2, mout, mo2);
}
```

```cpp
#include <cuda_runtime.h>
#include <cuda_bf16.h>
#include <cuda.h>
#include <stdint.h>

#define SPIN_LIMIT (1 << 17)

constexpr int RV = 704;
struct __align__(4096) Exch {
    uint4 o[5 * 128 * 256];
    uint4 halo[112 * 160];
    uint4 stats[8][2056];
    uint4 cand[8][128 * 20 + 8];
    uint4 ra[64][24];
    uint4 pad[128 * RV - (128 * 256 + 112 * 160 + 8 * 2056 + 8 * (128 * 20 + 8) + 64 * 24)];
};
struct __align__(4096) Scratch {
    Exch x;
    uint4 tab[60][72];
    unsigned cnt;
};
__device__ Scratch g_s;
#define STAMP(n)
#define GSTAMP(n)
#define STAMPT(n, t)

constexpr uint32_t OFF_W = 163840, WST = 15360;
constexpr uint32_t OFF_WM = OFF_W + 2 * WST;
constexpr uint32_t OFF_FF = OFF_WM + 20480;
constexpr uint32_t OFF_P8 = 131072, VP = 176;
constexpr uint32_t OFF_WD = 129024, OFF_WG = 184320;
constexpr uint32_t OFF_TAB = 225280;
constexpr uint32_t OFF_RED = OFF_TAB + 2560;
constexpr uint32_t OFF_EP = OFF_TAB + 4096;
constexpr uint32_t EP_GD = 1344, EP_US = 1376;
constexpr uint32_t OFF_BAR = OFF_EP + 1488;
constexpr uint32_t OFF_PROF = OFF_BAR + 640;
constexpr uint32_t SMEM_BYTES = OFF_PROF + 128;
enum { B_XF = 0, B_WF = 10, B_WO0 = 30, B_WO, B_FG, B_FD, B_TB, B_HL = B_TB + 4, B_G0 = B_HL + 8, B_RDY, B_WIN, B_EP, B_EP2, B_EP3, B_G2, B_G3, B_G4, B_WE = 55, B_T0 = B_WE + 19 };
#define SPLIT 1
#define ELD 4
#define D_2 0
#define WP0 -1
#define WP1 2
#define WOP 0
#define CPF 32
#define D_ST 400
#define D_REC 300
#define D_O 300
#define D_H 300
#define WO_MASK 0x1f5000
#define P_TAB 100
#define LAG 2
#define XWAIT 2
#define FD_AT 2
#define GU_MASK 0xaa00
#define TB_GO B_HL
#define TB_GO2 B_G2
#define TDELAY 3700
#define PFN 5
#define PF0 1
#define YSLEEP 300
#define MPF0 6
#define XDELAY 600
#define RSLEEP 40
#define HALO_GO B_G0
constexpr uint32_t SM0 = 1024;
#define BAR0(i) (SM0 + OFF_BAR + 8 * (i))
#define BAR(i) (sm + OFF_BAR + 8 * (i))

__device__ __forceinline__ uint32_t smem_u32(const void* p) { return (uint32_t)__cvta_generic_to_shared(p); }
__device__ __forceinline__ void mbar_init(uint32_t b, int cnt) { asm volatile("mbarrier.init.shared::cta.b64 [%0], %1;" ::"r"(b), "r"(cnt) : "memory"); }
__device__ __forceinline__ void mbar_expect_tx(uint32_t b, uint32_t bytes) { asm volatile("mbarrier.arrive.expect_tx.shared::cta.b64 _, [%0], %1;" ::"r"(b), "r"(bytes) : "memory"); }
__device__ __forceinline__ void mbar_arrive(uint32_t b) { asm volatile("mbarrier.arrive.shared::cta.b64 _, [%0];" ::"r"(b) : "memory"); }
__device__ __forceinline__ bool mbar_try(uint32_t b, uint32_t par) {
    uint32_t ok;
    asm volatile("{.reg .pred p; mbarrier.try_wait.parity.shared::cta.b64 p, [%1], %2; selp.u32 %0, 1, 0, p;}" : "=r"(ok) : "r"(b), "r"(par) : "memory");
    return ok;
}
__device__ __forceinline__ void mbar_wait(uint32_t b, uint32_t par) {
    asm volatile("{.reg .pred p;\nW: mbarrier.try_wait.parity.shared::cta.b64 p, [%0], %1;\n@!p bra W;}" ::"r"(b), "r"(par) : "memory");
}
__device__ __forceinline__ void bar_sync(int id, int n) { asm volatile("bar.sync %0, %1;" ::"r"(id), "r"(n) : "memory"); }
__device__ __forceinline__ void tma2d(uint32_t dst, const CUtensorMap* m, int c0, int c1, uint32_t bar) {
    asm volatile("cp.async.bulk.tensor.2d.shared::cluster.global.mbarrier::complete_tx::bytes [%0], [%1, {%3, %4}], [%2];" ::"r"(dst), "l"(m), "r"(bar), "r"(c0), "r"(c1) : "memory");
}
__device__ __forceinline__ void tma3d(uint32_t dst, const CUtensorMap* m, int c0, int c1, int c2, uint32_t bar) {
    asm volatile("cp.async.bulk.tensor.3d.shared::cluster.global.mbarrier::complete_tx::bytes [%0], [%1, {%3, %4, %5}], [%2];" ::"r"(dst), "l"(m), "r"(bar), "r"(c0), "r"(c1), "r"(c2) : "memory");
}
__device__ __forceinline__ void l2_prefetch(const void* p, uint32_t bytes) { asm volatile("cp.async.bulk.prefetch.L2.global [%0], %1;" ::"l"(p), "r"(bytes) : "memory"); }
__device__ __forceinline__ void wg_fence() { asm volatile("wgmma.fence.sync.aligned;" ::: "memory"); }
__device__ __forceinline__ void wg_commit() { asm volatile("wgmma.commit_group.sync.aligned;" ::: "memory"); }
template <int N> __device__ __forceinline__ void wg_wait() { asm volatile("wgmma.wait_group.sync.aligned %0;" ::"n"(N) : "memory"); }
__device__ __forceinline__ void ldsm4(uint32_t* r, uint32_t addr) { asm volatile("ldmatrix.sync.aligned.m8n8.x4.shared.b16 {%0,%1,%2,%3}, [%4];" : "=r"(r[0]), "=r"(r[1]), "=r"(r[2]), "=r"(r[3]) : "r"(addr) : "memory"); }
__device__ __forceinline__ void ldsm4t(uint32_t* r, uint32_t addr) { asm volatile("ldmatrix.sync.aligned.m8n8.x4.trans.shared.b16 {%0,%1,%2,%3}, [%4];" : "=r"(r[0]), "=r"(r[1]), "=r"(r[2]), "=r"(r[3]) : "r"(addr) : "memory"); }
__device__ __forceinline__ void stsm4(uint32_t addr, const uint32_t* r) { asm volatile("stmatrix.sync.aligned.m8n8.x4.shared.b16 [%4], {%0,%1,%2,%3};" ::"r"(r[0]), "r"(r[1]), "r"(r[2]), "r"(r[3]), "r"(addr) : "memory"); }
__device__ __forceinline__ void lds4(uint32_t* r, uint32_t addr) { asm volatile("ld.shared.v4.u32 {%0,%1,%2,%3}, [%4];" : "=r"(r[0]), "=r"(r[1]), "=r"(r[2]), "=r"(r[3]) : "r"(addr) : "memory"); }
__device__ __forceinline__ void sts4(uint32_t addr, const uint32_t* r) { asm volatile("st.shared.v4.u32 [%4], {%0,%1,%2,%3};" ::"r"(r[0]), "r"(r[1]), "r"(r[2]), "r"(r[3]), "r"(addr) : "memory"); }
__device__ __forceinline__ float2 lds2f(uint32_t addr) { float2 v; asm volatile("ld.shared.v2.f32 {%0,%1}, [%2];" : "=f"(v.x), "=f"(v.y) : "r"(addr) : "memory"); return v; }
__device__ __forceinline__ void sts1f(uint32_t addr, float v) { asm volatile("st.shared.f32 [%0], %1;" ::"r"(addr), "f"(v) : "memory"); }
__device__ __forceinline__ void sts1(uint32_t addr, uint32_t v) { asm volatile("st.shared.u32 [%0], %1;" ::"r"(addr), "r"(v) : "memory"); }
__device__ __forceinline__ void ldg4_rlx(uint32_t* r, const void* p) { asm volatile("{.reg .b128 t; ld.relaxed.gpu.global.b128 t, [%4]; mov.b128 {%0,%1,%2,%3}, t;}" : "=r"(r[0]), "=r"(r[1]), "=r"(r[2]), "=r"(r[3]) : "l"(p) : "memory"); }
__device__ __forceinline__ void ldg2_rlx(uint32_t* r, const void* p) { asm volatile("{.reg .b64 t; ld.relaxed.gpu.global.b64 t, [%2]; mov.b64 {%0,%1}, t;}" : "=r"(r[0]), "=r"(r[1]) : "l"(p) : "memory"); }
__device__ __forceinline__ uint32_t ldg1_rlx(const void* p) { uint32_t v; asm volatile("ld.relaxed.gpu.global.u32 %0, [%1];" : "=r"(v) : "l"(p) : "memory"); return v; }
__device__ __forceinline__ void stg4_rlx(void* p, uint32_t a, uint32_t b, uint32_t c, uint32_t d) { asm volatile("{.reg .b128 t; mov.b128 t, {%1,%2,%3,%4}; st.relaxed.gpu.global.b128 [%0], t;}" ::"l"(p), "r"(a), "r"(b), "r"(c), "r"(d) : "memory"); }
__device__ __forceinline__ void stg1_rlx(void* p, uint32_t a) { asm volatile("st.relaxed.gpu.global.u32 [%0], %1;" ::"l"(p), "r"(a) : "memory"); }
__device__ __forceinline__ uint64_t mkdesc(uint32_t addr, uint32_t lbo, uint32_t sbo, uint32_t sw) { return (uint64_t)((addr & 0x3FFFF) >> 4) | ((uint64_t)(lbo >> 4) << 16) | ((uint64_t)(sbo >> 4) << 32) | ((uint64_t)sw << 62); }
__device__ __forceinline__ uint32_t pack2(float lo, float hi) { uint32_t r; asm("cvt.rn.bf16x2.f32 %0, %1, %2;" : "=r"(r) : "f"(hi), "f"(lo)); return r; }
__device__ __forceinline__ float blo(uint32_t v) { return __uint_as_float(v << 16); }
__device__ __forceinline__ float bhi(uint32_t v) { return __uint_as_float(v & 0xffff0000u); }
__device__ __forceinline__ float rbf(float x) { return blo(pack2(x, 0.f)); }
__device__ __forceinline__ uint32_t hf2(uint32_t a, uint32_t b, uint32_t c) { uint32_t r; asm("fma.rn.bf16x2 %0, %1, %2, %3;" : "=r"(r) : "r"(a), "r"(b), "r"(c)); return r; }
__device__ __forceinline__ float ex2(float x) { float r; asm("ex2.approx.ftz.f32 %0, %1;" : "=f"(r) : "f"(x)); return r; }
__device__ __forceinline__ void mma16(float* d, uint32_t a0, uint32_t a1, uint32_t a2, uint32_t a3, uint32_t b0, uint32_t b1) {
    asm("mma.sync.aligned.m16n8k16.row.col.f32.bf16.bf16.f32 {%0,%1,%2,%3}, {%4,%5,%6,%7}, {%8,%9}, {%0,%1,%2,%3};"
                 : "+f"(d[0]), "+f"(d[1]), "+f"(d[2]), "+f"(d[3]) : "r"(a0), "r"(a1), "r"(a2), "r"(a3), "r"(b0), "r"(b1));
}
__device__ __forceinline__ void mma8(float* d, uint32_t a0, uint32_t a1, uint32_t b0) {
    asm("mma.sync.aligned.m16n8k8.row.col.f32.bf16.bf16.f32 {%0,%1,%2,%3}, {%4,%5}, {%6}, {%0,%1,%2,%3};"
                 : "+f"(d[0]), "+f"(d[1]), "+f"(d[2]), "+f"(d[3]) : "r"(a0), "r"(a1), "r"(b0));
}
__device__ __forceinline__ uint32_t fkey(float f) { const uint32_t u = __float_as_uint(f); return u ^ (((int)u >> 31) | 0x80000000u); }
__device__ __forceinline__ float rcp(float x) { float r; asm("rcp.approx.ftz.f32 %0, %1;" : "=f"(r) : "f"(x)); return r; }
__device__ __forceinline__ float sigm(float x) { return rcp(1.f + ex2(x * -1.4426950408889634f)); }
__device__ __forceinline__ void mma16c(float* d, uint32_t a0, uint32_t a1, uint32_t a2, uint32_t a3, uint32_t b0, uint32_t b1, float c0, float c1) {
    asm("mma.sync.aligned.m16n8k16.row.col.f32.bf16.bf16.f32 {%0,%1,%2,%3}, {%4,%5,%6,%7}, {%8,%9}, {%10,%11,%12,%12};"
                 : "=f"(d[0]), "=f"(d[1]), "=f"(d[2]), "=f"(d[3]) : "r"(a0), "r"(a1), "r"(a2), "r"(a3), "r"(b0), "r"(b1), "f"(c0), "f"(c1), "f"(0.f));
}
__device__ __forceinline__ void stsm2(uint32_t addr, uint32_t a, uint32_t b) { asm volatile("stmatrix.sync.aligned.m8n8.x2.shared.b16 [%2], {%0,%1};" ::"r"(a), "r"(b), "r"(addr) : "memory"); }
__device__ __forceinline__ void lds2(uint32_t* r, uint32_t addr) { asm volatile("ld.shared.v2.u32 {%0,%1}, [%2];" : "=r"(r[0]), "=r"(r[1]) : "r"(addr) : "memory"); }
__device__ __forceinline__ void sts2(uint32_t addr, uint32_t a, uint32_t b) { asm volatile("st.shared.v2.u32 [%2], {%0,%1};" ::"r"(a), "r"(b), "r"(addr) : "memory"); }
__device__ __forceinline__ uint32_t lds1(uint32_t addr) { uint32_t v; asm volatile("ld.shared.u32 %0, [%1];" : "=r"(v) : "r"(addr) : "memory"); return v; }
__device__ __forceinline__ bool elect1() { uint32_t p; asm volatile("{.reg .pred P; elect.sync _|P, 0xffffffff; selp.u32 %0, 1, 0, P;}" : "=r"(p)); return p; }
__device__ __forceinline__ void tma2d_mc(uint32_t dst, const CUtensorMap* m, int c0, int c1, uint32_t bar) {
    asm volatile("cp.async.bulk.tensor.2d.shared::cluster.global.mbarrier::complete_tx::bytes.multicast::cluster [%0], [%1, {%3, %4}], [%2], %5;" ::"r"(dst), "l"(m), "r"(bar), "r"(c0), "r"(c1), "h"((unsigned short)3) : "memory");
}
__device__ __forceinline__ void tma3d_mc(uint32_t dst, const CUtensorMap* m, int c0, int c1, int c2, uint32_t bar) {
    asm volatile("cp.async.bulk.tensor.3d.shared::cluster.global.mbarrier::complete_tx::bytes.multicast::cluster [%0], [%1, {%3, %4, %5}], [%2], %6;" ::"r"(dst), "l"(m), "r"(bar), "r"(c0), "r"(c1), "r"(c2), "h"((unsigned short)3) : "memory");
}
__device__ __forceinline__ void tma4d_mc(uint32_t dst, const CUtensorMap* m, int c0, int c1, int c2, int c3, uint32_t bar) {
    asm volatile("cp.async.bulk.tensor.4d.shared::cluster.global.mbarrier::complete_tx::bytes.multicast::cluster [%0], [%1, {%3, %4, %5, %6}], [%2], %7;" ::"r"(dst), "l"(m), "r"(bar), "r"(c0), "r"(c1), "r"(c2), "r"(c3), "h"((unsigned short)3) : "memory");
}
__device__ __forceinline__ void mbar_arrive_cl(uint32_t b) { asm volatile("mbarrier.arrive.shared::cluster.b64 _, [%0];" ::"r"(b) : "memory"); }
__device__ __forceinline__ uint32_t hm2(uint32_t a, uint32_t b) { uint32_t r; asm("mul.rn.bf16x2 %0, %1, %2;" : "=r"(r) : "r"(a), "r"(b)); return r; }
__device__ __forceinline__ uint32_t clock32() { uint32_t c; asm volatile("mov.u32 %0, %clock;" : "=r"(c)); return c; }
__device__ __forceinline__ float rsq(float x) { float r; asm("rsqrt.approx.ftz.f32 %0, %1;" : "=f"(r) : "f"(x)); return r; }
__device__ __forceinline__ void pause_until(uint32_t t0, uint32_t n) {
    asm volatile("{.reg .pred p; .reg .u32 t;\nP: mov.u32 t, %clock; sub.u32 t, t, %0; setp.lt.u32 p, t, %1;\n@p bra.uni P;}" ::"r"(t0), "r"(n) : "memory");
}
__device__ __forceinline__ void pause(uint32_t n) { if (n) { const uint32_t t = clock32(); while (clock32() - t < n) {} } }
__device__ __forceinline__ uint32_t wbuf(int it) {
    const uint32_t v = it < 4 ? it + 8 : (uint32_t)(0x8302418302b1a908ull >> (4 * it - 16)) & 15;
    return v * WST + (v >> 3) * (OFF_W - 8 * WST);
}
__device__ __forceinline__ uint32_t wobuf(int w) { return ((0x30241765u >> (4 * w)) & 7) * WST; }
__device__ __forceinline__ uint32_t inc(uint32_t v) { uint32_t r; asm volatile("{.reg .u32 t; or.b32 t, %1, 255; add.u32 %0, t, 1;}" : "=r"(r) : "r"(v)); return r; }
__device__ __forceinline__ uint32_t ldg1_acq(const void* p) { uint32_t v; asm volatile("ld.acquire.gpu.global.u32 %0, [%1];" : "=r"(v) : "l"(p) : "memory"); return v; }
__device__ __forceinline__ void tma3d_st(const CUtensorMap* m, int c0, int c1, int c2, uint32_t src) {
    asm volatile("cp.async.bulk.tensor.3d.global.shared::cta.bulk_group [%0, {%2, %3, %4}], [%1];" ::"l"(m), "r"(src), "r"(c0), "r"(c1), "r"(c2) : "memory");
}
__device__ __forceinline__ uint32_t nz(uint32_t v) { uint32_t r; asm("max.u32 %0, %1, 1;" : "=r"(r) : "r"(v)); return r; }
__device__ __forceinline__ uint32_t tagw(uint32_t w, uint32_t tc) { return ((w & 0x8000ffffu) | min(max(w & 0x7fff0000u, 0x20000000u), 0x5fff0000u)) + tc; }
template <int S_> __device__ __forceinline__ void await7(uint32_t (*r)[4], const char* const* p, uint32_t fz, uint32_t stale) {
    if (S_ == 0) asm volatile("{.reg .b128 t; .reg .pred p; .reg .u32 m, k, n;\nmov.u32 n, %clock; or.b32 n, n, %37; shr.u32 n, n, 31;\nL:\n"
        "min.u32 m, %0, %4; min.u32 m, m, %8; min.u32 m, m, %12; min.u32 m, m, %16; min.u32 m, m, %20; min.u32 m, m, %24;\n"
        "setp.eq.u32 p, m, 0; vote.sync.any.pred p, p, 0xffffffff; add.u32 n, n, 1; setp.lt.and.u32 p, n, %36, p;\n@!p bra.uni D;\n"
        "setp.eq.u32 p, %0, 0; mov.b128 t, {%0,%1,%2,%3}; @p ld.relaxed.gpu.global.b128 t, [%28+%35]; mov.b128 {%0,%1,%2,%3}, t;\n"
        "setp.eq.u32 p, %4, 0; mov.b128 t, {%4,%5,%6,%7}; @p ld.relaxed.gpu.global.b128 t, [%29+%35]; mov.b128 {%4,%5,%6,%7}, t;\n"
        "setp.eq.u32 p, %8, 0; mov.b128 t, {%8,%9,%10,%11}; @p ld.relaxed.gpu.global.b128 t, [%30+%35]; mov.b128 {%8,%9,%10,%11}, t;\n"
        "setp.eq.u32 p, %12, 0; mov.b128 t, {%12,%13,%14,%15}; @p ld.relaxed.gpu.global.b128 t, [%31+%35]; mov.b128 {%12,%13,%14,%15}, t;\n"
        "setp.eq.u32 p, %16, 0; mov.b128 t, {%16,%17,%18,%19}; @p ld.relaxed.gpu.global.b128 t, [%32+%35]; mov.b128 {%16,%17,%18,%19}, t;\n"
        "setp.eq.u32 p, %20, 0; mov.b128 t, {%20,%21,%22,%23}; @p ld.relaxed.gpu.global.b128 t, [%33+%35]; mov.b128 {%20,%21,%22,%23}, t;\n"
        "setp.eq.u32 p, %24, 0; mov.b128 t, {%24,%25,%26,%27}; @p ld.relaxed.gpu.global.b128 t, [%34+%35]; mov.b128 {%24,%25,%26,%27}, t;\n"
        "bra.uni L;\nD:}"
        : "+r"(r[0][0]), "+r"(r[0][1]), "+r"(r[0][2]), "+r"(r[0][3]), "+r"(r[1][0]), "+r"(r[1][1]), "+r"(r[1][2]), "+r"(r[1][3]), "+r"(r[2][0]), "+r"(r[2][1]), "+r"(r[2][2]), "+r"(r[2][3]), "+r"(r[3][0]), "+r"(r[3][1]), "+r"(r[3][2]), "+r"(r[3][3]), "+r"(r[4][0]), "+r"(r[4][1]), "+r"(r[4][2]), "+r"(r[4][3]), "+r"(r[5][0]), "+r"(r[5][1]), "+r"(r[5][2]), "+r"(r[5][3]), "+r"(r[6][0]), "+r"(r[6][1]), "+r"(r[6][2]), "+r"(r[6][3])
        : "l"(p[0]), "l"(p[1]), "l"(p[2]), "l"(p[3]), "l"(p[4]), "l"(p[5]), "l"(p[6]), "n"((4 - S_) * 524288), "n"(SPIN_LIMIT), "r"(fz), "r"(stale) : "memory");
    else asm volatile("{.reg .b128 t; .reg .pred p; .reg .u32 m, k, n;\nmov.u32 n, %clock; or.b32 n, n, %37; shr.u32 n, n, 31;\nL:\n"
        "xor.b32 m, %0, %38; xor.b32 k, %4, %38; and.b32 m, m, k; xor.b32 k, %8, %38; and.b32 m, m, k; xor.b32 k, %12, %38; and.b32 m, m, k; xor.b32 k, %16, %38; and.b32 m, m, k;\n"
        "xor.b32 k, %20, %38; and.b32 m, m, k; xor.b32 k, %24, %38; and.b32 m, m, k; and.b32 m, m, 0x40000000;\n"
        "setp.eq.u32 p, m, 0; vote.sync.any.pred p, p, 0xffffffff; add.u32 n, n, 1; setp.lt.and.u32 p, n, %36, p;\n@!p bra.uni D;\n"
        "xor.b32 k, %0, %38; and.b32 k, k, 0x40000000; setp.eq.u32 p, k, 0; mov.b128 t, {%0,%1,%2,%3}; @p ld.relaxed.gpu.global.b128 t, [%28+%35]; mov.b128 {%0,%1,%2,%3}, t;\n"
        "xor.b32 k, %4, %38; and.b32 k, k, 0x40000000; setp.eq.u32 p, k, 0; mov.b128 t, {%4,%5,%6,%7}; @p ld.relaxed.gpu.global.b128 t, [%29+%35]; mov.b128 {%4,%5,%6,%7}, t;\n"
        "xor.b32 k, %8, %38; and.b32 k, k, 0x40000000; setp.eq.u32 p, k, 0; mov.b128 t, {%8,%9,%10,%11}; @p ld.relaxed.gpu.global.b128 t, [%30+%35]; mov.b128 {%8,%9,%10,%11}, t;\n"
        "xor.b32 k, %12, %38; and.b32 k, k, 0x40000000; setp.eq.u32 p, k, 0; mov.b128 t, {%12,%13,%14,%15}; @p ld.relaxed.gpu.global.b128 t, [%31+%35]; mov.b128 {%12,%13,%14,%15}, t;\n"
        "xor.b32 k, %16, %38; and.b32 k, k, 0x40000000; setp.eq.u32 p, k, 0; mov.b128 t, {%16,%17,%18,%19}; @p ld.relaxed.gpu.global.b128 t, [%32+%35]; mov.b128 {%16,%17,%18,%19}, t;\n"
        "xor.b32 k, %20, %38; and.b32 k, k, 0x40000000; setp.eq.u32 p, k, 0; mov.b128 t, {%20,%21,%22,%23}; @p ld.relaxed.gpu.global.b128 t, [%33+%35]; mov.b128 {%20,%21,%22,%23}, t;\n"
        "xor.b32 k, %24, %38; and.b32 k, k, 0x40000000; setp.eq.u32 p, k, 0; mov.b128 t, {%24,%25,%26,%27}; @p ld.relaxed.gpu.global.b128 t, [%34+%35]; mov.b128 {%24,%25,%26,%27}, t;\n"
        "bra.uni L;\nD:}"
        : "+r"(r[0][0]), "+r"(r[0][1]), "+r"(r[0][2]), "+r"(r[0][3]), "+r"(r[1][0]), "+r"(r[1][1]), "+r"(r[1][2]), "+r"(r[1][3]), "+r"(r[2][0]), "+r"(r[2][1]), "+r"(r[2][2]), "+r"(r[2][3]), "+r"(r[3][0]), "+r"(r[3][1]), "+r"(r[3][2]), "+r"(r[3][3]), "+r"(r[4][0]), "+r"(r[4][1]), "+r"(r[4][2]), "+r"(r[4][3]), "+r"(r[5][0]), "+r"(r[5][1]), "+r"(r[5][2]), "+r"(r[5][3]), "+r"(r[6][0]), "+r"(r[6][1]), "+r"(r[6][2]), "+r"(r[6][3])
        : "l"(p[0]), "l"(p[1]), "l"(p[2]), "l"(p[3]), "l"(p[4]), "l"(p[5]), "l"(p[6]), "n"((4 - S_) * 524288), "n"(SPIN_LIMIT), "r"(fz), "r"(stale) : "memory");
}
template <class T> __device__ __forceinline__ T* pinp(T* p) { return (T*)__shfl_xor_sync(~0u, (unsigned long long)p, 0); }
__device__ __forceinline__ float fsel(bool c, float a, float b) { float r; asm("{.reg .pred p; setp.ne.u32 p, %3, 0; selp.f32 %0, %1, %2, p;}" : "=f"(r) : "f"(a), "f"(b), "r"((int)c)); return r; }
__device__ __forceinline__ void stg4_if(bool c, void* p, uint32_t a, uint32_t b, uint32_t d, uint32_t e) {
    asm volatile("{.reg .b128 t; .reg .pred p; setp.ne.u32 p, %5, 0; mov.b128 t, {%1,%2,%3,%4}; @p st.relaxed.gpu.global.b128 [%0], t;}" ::"l"(p), "r"(a), "r"(b), "r"(d), "r"(e), "r"((int)c) : "memory");
}
__device__ __forceinline__ void stg1_if(bool c, void* p, uint32_t a) {
    asm volatile("{.reg .pred p; setp.ne.u32 p, %2, 0; @p st.relaxed.gpu.global.u32 [%0], %1;}" ::"l"(p), "r"(a), "r"((int)c) : "memory");
}
__device__ __forceinline__ void ldg4_again(uint32_t* r, const void* p) {
    asm volatile("{.reg .b128 t; .reg .pred p; setp.eq.u32 p, %3, 0; mov.b128 t, {%0,%1,%2,%3}; @p ld.relaxed.gpu.global.b128 t, [%4]; mov.b128 {%0,%1,%2,%3}, t;}"
                 : "+r"(r[0]), "+r"(r[1]), "+r"(r[2]), "+r"(r[3]) : "l"(p) : "memory");
}
__device__ __forceinline__ void wgmma_rs_n192(float* d, const uint32_t* a, uint64_t bdesc, int accum) {
    asm volatile("{.reg .pred p; setp.ne.b32 p, %101, 0; wgmma.mma_async.sync.aligned.m64n192k16.f32.bf16.bf16 {%0,%1,%2,%3,%4,%5,%6,%7,%8,%9,%10,%11,%12,%13,%14,%15,%16,%17,%18,%19,%20,%21,%22,%23,%24,%25,%26,%27,%28,%29,%30,%31,%32,%33,%34,%35,%36,%37,%38,%39,%40,%41,%42,%43,%44,%45,%46,%47,%48,%49,%50,%51,%52,%53,%54,%55,%56,%57,%58,%59,%60,%61,%62,%63,%64,%65,%66,%67,%68,%69,%70,%71,%72,%73,%74,%75,%76,%77,%78,%79,%80,%81,%82,%83,%84,%85,%86,%87,%88,%89,%90,%91,%92,%93,%94,%95}, {%96,%97,%98,%99}, %100, p, 1, 1, 1;}"
        : "+f"(d[0]),"+f"(d[1]),"+f"(d[2]),"+f"(d[3]),"+f"(d[4]),"+f"(d[5]),"+f"(d[6]),"+f"(d[7]),"+f"(d[8]),"+f"(d[9]),"+f"(d[10]),"+f"(d[11]),"+f"(d[12]),"+f"(d[13]),"+f"(d[14]),"+f"(d[15]),"+f"(d[16]),"+f"(d[17]),"+f"(d[18]),"+f"(d[19]),"+f"(d[20]),"+f"(d[21]),"+f"(d[22]),"+f"(d[23]),"+f"(d[24]),"+f"(d[25]),"+f"(d[26]),"+f"(d[27]),"+f"(d[28]),"+f"(d[29]),"+f"(d[30]),"+f"(d[31]),"+f"(d[32]),"+f"(d[33]),"+f"(d[34]),"+f"(d[35]),"+f"(d[36]),"+f"(d[37]),"+f"(d[38]),"+f"(d[39]),"+f"(d[40]),"+f"(d[41]),"+f"(d[42]),"+f"(d[43]),"+f"(d[44]),"+f"(d[45]),"+f"(d[46]),"+f"(d[47]),"+f"(d[48]),"+f"(d[49]),"+f"(d[50]),"+f"(d[51]),"+f"(d[52]),"+f"(d[53]),"+f"(d[54]),"+f"(d[55]),"+f"(d[56]),"+f"(d[57]),"+f"(d[58]),"+f"(d[59]),"+f"(d[60]),"+f"(d[61]),"+f"(d[62]),"+f"(d[63]),"+f"(d[64]),"+f"(d[65]),"+f"(d[66]),"+f"(d[67]),"+f"(d[68]),"+f"(d[69]),"+f"(d[70]),"+f"(d[71]),"+f"(d[72]),"+f"(d[73]),"+f"(d[74]),"+f"(d[75]),"+f"(d[76]),"+f"(d[77]),"+f"(d[78]),"+f"(d[79]),"+f"(d[80]),"+f"(d[81]),"+f"(d[82]),"+f"(d[83]),"+f"(d[84]),"+f"(d[85]),"+f"(d[86]),"+f"(d[87]),"+f"(d[88]),"+f"(d[89]),"+f"(d[90]),"+f"(d[91]),"+f"(d[92]),"+f"(d[93]),"+f"(d[94]),"+f"(d[95])
        : "r"(a[0]), "r"(a[1]), "r"(a[2]), "r"(a[3]), "l"(bdesc), "r"(accum));
}
__device__ __forceinline__ void wgmma_rs_n48(float* d, const uint32_t* a, uint64_t bdesc, int accum) {
    asm volatile("{.reg .pred p; setp.ne.b32 p, %29, 0; wgmma.mma_async.sync.aligned.m64n48k16.f32.bf16.bf16 {%0,%1,%2,%3,%4,%5,%6,%7,%8,%9,%10,%11,%12,%13,%14,%15,%16,%17,%18,%19,%20,%21,%22,%23}, {%24,%25,%26,%27}, %28, p, 1, 1, 1;}"
        : "+f"(d[0]),"+f"(d[1]),"+f"(d[2]),"+f"(d[3]),"+f"(d[4]),"+f"(d[5]),"+f"(d[6]),"+f"(d[7]),"+f"(d[8]),"+f"(d[9]),"+f"(d[10]),"+f"(d[11]),"+f"(d[12]),"+f"(d[13]),"+f"(d[14]),"+f"(d[15]),"+f"(d[16]),"+f"(d[17]),"+f"(d[18]),"+f"(d[19]),"+f"(d[20]),"+f"(d[21]),"+f"(d[22]),"+f"(d[23])
        : "r"(a[0]), "r"(a[1]), "r"(a[2]), "r"(a[3]), "l"(bdesc), "r"(accum));
}
__device__ __forceinline__ void wgmma_rs_n80(float* d, const uint32_t* a, uint64_t bdesc, int accum) {
    asm volatile("{.reg .pred p; setp.ne.b32 p, %45, 0; wgmma.mma_async.sync.aligned.m64n80k16.f32.bf16.bf16 {%0,%1,%2,%3,%4,%5,%6,%7,%8,%9,%10,%11,%12,%13,%14,%15,%16,%17,%18,%19,%20,%21,%22,%23,%24,%25,%26,%27,%28,%29,%30,%31,%32,%33,%34,%35,%36,%37,%38,%39}, {%40,%41,%42,%43}, %44, p, 1, 1, 1;}"
        : "+f"(d[0]),"+f"(d[1]),"+f"(d[2]),"+f"(d[3]),"+f"(d[4]),"+f"(d[5]),"+f"(d[6]),"+f"(d[7]),"+f"(d[8]),"+f"(d[9]),"+f"(d[10]),"+f"(d[11]),"+f"(d[12]),"+f"(d[13]),"+f"(d[14]),"+f"(d[15]),"+f"(d[16]),"+f"(d[17]),"+f"(d[18]),"+f"(d[19]),"+f"(d[20]),"+f"(d[21]),"+f"(d[22]),"+f"(d[23]),"+f"(d[24]),"+f"(d[25]),"+f"(d[26]),"+f"(d[27]),"+f"(d[28]),"+f"(d[29]),"+f"(d[30]),"+f"(d[31]),"+f"(d[32]),"+f"(d[33]),"+f"(d[34]),"+f"(d[35]),"+f"(d[36]),"+f"(d[37]),"+f"(d[38]),"+f"(d[39])
        : "r"(a[0]), "r"(a[1]), "r"(a[2]), "r"(a[3]), "l"(bdesc), "r"(accum));
}

__global__ void __cluster_dims__(2, 1, 1) __launch_bounds__(384, 1)
fused_kernel(const __nv_bfloat16* __restrict__ wmod, const __nv_bfloat16* __restrict__ cvec, Scratch* __restrict__ S,
             const __nv_bfloat16* __restrict__ wqkv, const __nv_bfloat16* __restrict__ wo, __nv_bfloat16* __restrict__ out,
             const __nv_bfloat16* __restrict__ wr, const __nv_bfloat16* __restrict__ wg, const __nv_bfloat16* __restrict__ wu,
             const __nv_bfloat16* __restrict__ wd,
             const __grid_constant__ CUtensorMap mm, const __grid_constant__ CUtensorMap mx, const __grid_constant__ CUtensorMap mw,
             const __grid_constant__ CUtensorMap mt, const __grid_constant__ CUtensorMap mo, const __grid_constant__ CUtensorMap mg,
             const __grid_constant__ CUtensorMap mu, const __grid_constant__ CUtensorMap md,
             const __grid_constant__ CUtensorMap mw2, const __grid_constant__ CUtensorMap mout,
             const __grid_constant__ CUtensorMap mo2) {
    extern __shared__ __align__(1024) char sm_raw[];
    const int bid = blockIdx.x;
    const uint32_t sm = ((bid & 1) << 24) + SM0;
    STAMP(30);
    const uint32_t t_start = clock32();
    if (bid < CPF && threadIdx.x == 0)
        asm volatile("cp.async.bulk.prefetch.tensor.2d.L2.global [%0, {%1, %2}];" ::"l"(&mm), "r"((bid & 1) * 640 + (bid >> 4) * 64), "r"(((bid >> 1) & 7) * 80) : "memory");
    const int cl = bid >> 1, rank = bid & 1, c7 = ((cl - 36) * 37) >> 8;
    const int grp = cl < 4 ? 0 : (cl < 36 ? (cl - 4) & 7 : cl - 35 - 7 * c7);
    const int ti = grp * 2 + rank;
    auto ldx = [&](int c) { mbar_expect_tx(BAR(B_XF + c), 16384); tma3d(sm + c * 16384, &mx, c * 64, ti >> 3, (ti & 7) * 128, BAR(B_XF + c)); };
    if (threadIdx.x == 256 && bid < 128) {
        mbar_init(BAR(B_XF), 1); mbar_init(BAR(B_XF + 1), 1);
        pause_until(t_start, XDELAY);
        ldx(0); ldx(1);
        STAMPT(22, 256);
#pragma unroll
        for (int i = 2; i < 10; i++) mbar_init(BAR(B_XF + i), 1);
        mbar_init(BAR(B_T0), 1);
        asm volatile("fence.mbarrier_init.release.cluster;" ::: "memory");
        ldx(2); ldx(3); ldx(4);
    }
    const int warp = __shfl_sync(~0u, threadIdx.x >> 5, 0);

#define PIN(v) __shfl_xor_sync(~0u, (v), 0)
#define LANE_VARS const int tid = PIN(threadIdx.x), lane = tid & 31, g = lane >> 2, q = lane & 3; \
    const uint32_t frow = (lane & 7) + (lane >> 4) * 8, fh = (lane >> 3) & 1;
    if (bid >= 128) {
        LANE_VARS
        const int h = bid - 128;
        if (warp >= 8) {
            if (warp == 8) return;
            const int t = tid - 288;
            if (t < 90) stg4_rlx(&S->tab[(5 + t / 9) * 4 + h][t % 9], 0u, 0u, 0u, 0u);
            __syncwarp();
            asm volatile("bar.arrive 1, 352;" ::: "memory");
            bar_sync(2, 96);
            if (t == 0) asm volatile("red.release.gpu.global.add.u32 [%0], 32;" ::"l"(&S->cnt) : "memory");
            return;
        }
        const uint32_t slot = sm + warp * 20480, bar = BAR(warp * 2);
        auto column = [&](int job) {
            const int n = job * 4 + h;
            return job < 10 ? ((h & 1) ? (job < 5 ? 10 : 30) : (job < 5 ? 0 : 10)) + (n >> 1) : (n < 50 ? n - 10 : n);
        };
        auto load = [&](int job) {
            mbar_expect_tx(bar + (job & 1) * 8, 10240);
            tma2d(slot + (job & 1) * 10240, &mm, column(job) * 64, warp * 80, bar + (job & 1) * 8);
        };
        if (elect1()) { mbar_init(bar, 1); mbar_init(bar + 8, 1); load(0); }
        __syncwarp();
        uint32_t b[10];
#pragma unroll
        for (int s = 0; s < 10; s++) b[s] = ldg1_rlx((const uint32_t*)cvec + warp * 40 + s * 4 + q);
        if (lane < 8 && warp < 5) stg4_rlx(&S->tab[warp * 4 + h][lane], 0u, 0u, 0u, 0u);
#pragma unroll
        for (int s = 0; s < 10; s++) b[s] = pack2(blo(b[s]) * sigm(blo(b[s])), bhi(b[s]) * sigm(bhi(b[s])));
        const uint32_t fa = slot + frow * 128 + ((fh ^ (lane & 7)) << 4);
        const int c0 = (lane >> 3) * 16 + (lane & 1) * 8 + (lane & 6);
#pragma unroll 1
        for (int job = 0; job < 15; job++) {
            uint32_t w2 = 0;
            if (job >= 5) w2 = ldg1_rlx(wr + (column(job) % 10) * 64 + c0);

            mbar_wait(bar + (job & 1) * 8, (job >> 1) & 1);
            if (job == 0) { if (elect1()) load(1); __syncwarp(); }
            float d[4][4] = {};
#pragma unroll
            for (int s = 0; s < 5; s++) {
#pragma unroll
                for (int m = 0; m < 4; m++) { uint32_t a[4]; ldsm4t(a, (fa ^ (m * 32)) + (job & 1) * 10240 + s * 2048); mma16(d[m], a[0], a[1], a[2], a[3], b[2 * s], b[2 * s + 1]); }
            }
            const uint32_t red = sm + OFF_W + (job & 1) * 2048;
            sts1f(red + (warp * 64 + q * 8 + g) * 4, q == 0 ? d[0][0] : (q == 1 ? d[0][2] : (q == 2 ? d[1][0] : d[1][2])));
            sts1f(red + (warp * 64 + 32 + q * 8 + g) * 4, q == 0 ? d[2][0] : (q == 1 ? d[2][2] : (q == 2 ? d[3][0] : d[3][2])));
            __syncwarp();
            if (job < 13 && elect1()) load(job + 2);
            __syncwarp();
            bar_sync(0, 256);
            if (job == 5) bar_sync(1, 352);
            if (warp == (job & 7)) {
                float y0 = 0.f, y1 = 0.f;
#pragma unroll
                for (int w = 0; w < 8; w++) { const float2 v = lds2f(red + (w * 64 + c0) * 4); y0 += v.x; y1 += v.y; }
                const uint32_t t = hf2(pack2(y0, y1), 0x3f803f80u, ((h & 1) && job < 10) ? 0x3f803f80u : 0x80008000u);
                uint32_t* const p = (uint32_t*)&S->tab[job * 4 + h][0];
                stg1_rlx(p + lane, nz(t));
                float dot = fmaf(blo(t), blo(w2), bhi(t) * bhi(w2));
#pragma unroll
                for (int o = 16; o; o >>= 1) dot += __shfl_xor_sync(~0u, dot, o);
                if (lane == 0) stg1_rlx(p + 32, dot == 0.f ? 0x80000000u : __float_as_uint(dot));
            }
            if (job == 0) STAMP(27);
            if (job == 8) STAMP(28);
        }
        STAMP(17);
        return;
    }
    uint32_t ep0;
    if (__builtin_expect(warp == 8, 1)) {
        asm volatile("barrier.cluster.arrive.relaxed.aligned;" ::: "memory");
        if (elect1()) {
#pragma unroll 1
            for (int c = 5; c < 10; c++) ldx(c);
        }
        __syncwarp();
    } else {
        if (warp < 8) {
            if (elect1()) {
#pragma unroll
                for (int i = 0; i < 8; i++) { const int b = B_WF + warp * 8 + i; mbar_init(BAR(b), b >= B_WE ? 16 : (b >= B_G2 ? 8 : (b >= B_EP ? 2 : (b == B_WO ? 7 : 1)))); }
                asm volatile("fence.mbarrier_init.release.cluster;" ::: "memory");
            }
            __syncwarp();
        }
        if (warp == 9) ep0 = ldg1_rlx(&S->cnt);
        asm volatile("barrier.cluster.arrive.relaxed.aligned;" ::: "memory");
    }
    const int sl = cl < 4 ? 4 + cl : (cl < 36 ? (cl - 4) >> 3 : 4 + c7);
    const int j = sl ^ (((sl + 2) >> 2) & 1), role = ti * 8 + j, odd = j & 1;
    const int fi = j * 16 + ti;
    const int al = ((j + 1) & 2) == 0;
    Exch* const X = &S->x;
    if (warp >= 8) {
        asm volatile("setmaxnreg.dec.sync.aligned.u32 72;");
        if (warp == 8) {
            asm volatile("barrier.cluster.wait.aligned;" ::: "memory");
            if (!elect1()) return;
            const int col_main = 80 * j + 16 * odd, col_tail = 80 * j + (odd ? 0 : 64);
            auto load_w = [&](int it) {
                const uint32_t b = BAR(B_WF + it), dst = sm + wbuf(it) + rank * 6144;
                mbar_expect_tx(b, WST);
                tma4d_mc(dst, al ? &mw2 : &mw, 0, it * 32 + rank * 16, col_main >> (5 + al), 0, b);
                tma3d_mc(dst + 12288 - rank * 4608, &mt, col_tail, it * 32 + rank * 16, 0, b);
            };
            int it = 0, wn = 0, gn = 0;
#pragma unroll 1
            for (int r = -2; r < 19; r++) {
                if (r == -1) mbar_wait(BAR(B_XF + XWAIT), 0);
                if (r >= 0) mbar_wait(BAR(B_WE + r), 0);
                const int lim = min(r < 2 ? (r == 1 ? 7 : 2 * r + 6) : r + 7, 20);
#pragma unroll 1
                for (; it < lim; it++) load_w(it);
                if (r == WP0 || r == WP1) l2_prefetch(wqkv + (size_t)((r == WP0 ? 128 : 384) + role * 2) * 1920, 2 * 3840);
                if (r == WOP) l2_prefetch(wo + role * 3200, 6400);
                if (r >= MPF0 && r < MPF0 + 10) l2_prefetch(wmod + (size_t)(role * 5 + ((r - MPF0) >> 1)) * 3840 + 1920 + (r & 1) * 1280, 1280);
                if (((GU_MASK >> (r + 2)) & 1) && fi < 108) { if (gn == 0) mbar_expect_tx(BAR(B_FG), 40960); tma2d(sm + OFF_WG + gn * 10240, (fi & 1) ? &mu : &mg, (fi >> 1) * 32, gn * 160, BAR(B_FG)); gn++; }
#pragma unroll 1
                for (int n = ((WO_MASK >> (r + 2)) & 1) + (r == 14); n > 0; n--) {
                    const int row = (j ^ wn) * 80 + rank * 40;
                    const uint32_t b = BAR(wn ? B_WO : B_WO0), dst = sm + wobuf(wn) + rank * 2560;
                    mbar_expect_tx(b, 12800);
                    tma2d_mc(dst, &mo, col_main, row, b); tma2d_mc(dst + 5120, &mo, col_main + 32, row, b); tma2d_mc(dst + 10240, &mo2, col_tail, row, b);
                    wn++;
                }
                if (r >= PF0 && r < PF0 + 3 * PFN) { const int m = (r - PF0) / PFN; l2_prefetch((m == 0 ? wg : (m == 1 ? wu : wd)) + role * 8640 + (r - PF0 - m * PFN) * (8640 / PFN), 17280 / PFN); }
            }
            STAMPT(24, 256);
            if (fi >= 88) { mbar_wait(BAR(B_G2), 0); mbar_expect_tx(BAR(B_FD), 55296); tma3d(sm + OFF_WD, &md, (fi - 88) * 16, 0, 0, BAR(B_FD)); }
            return;
        }
        asm volatile("barrier.cluster.wait.aligned;" ::: "memory");
        const int tid = threadIdx.x, lane = tid & 31, fh = (lane >> 3) & 1;
        int gd = 0;
        if (warp == 9) {
            {
                uint32_t ta = sm + OFF_TAB + fh * 1280 + (lane >> 4) * 128 + (lane & 4) * 16 + (lane & 1) * 32 + (lane & 2) * 4;
                const uint4* tp = &S->tab[lane >> 3][lane & 7];
                pause_until(t_start, TDELAY);
#pragma unroll 1
                for (int e = 0; e < 5; e++) {
                    uint32_t w[4];
                    if (e > 1) mbar_wait(BAR(B_WE + 4 * e - 8), 0);
                    while (true) {
                        ldg4_rlx(w, tp);
                        if (!__any_sync(~0u, min(min(w[0], w[1]), min(w[2], w[3])) == 0) || ++gd > SPIN_LIMIT) break;
                        pause(P_TAB);
                    }
                    sts2(ta, w[0], w[1]); sts2(ta + 16, w[2], w[3]);
                    __syncwarp();
                    if (e == 0) { STAMPT(2, 288); if (lane == 0) sts1(sm + OFF_EP + EP_US + 8, ep0 << 22 & 0x40000000u); }
                    if (lane == 0) mbar_arrive(BAR(e ? B_TB - 1 + e : B_T0));
                    ta += 256; tp += 288;
                }
            }
            uint32_t h[5][4];
            while (ldg1_acq(&S->cnt) != inc(ep0) && ++gd < SPIN_LIMIT) __nanosleep(YSLEEP);
            __syncwarp();
            if (lane == 0) mbar_arrive(BAR(B_RDY));
            mbar_wait(BAR(HALO_GO), 0);
            pause(D_H);
            if ((ti & 7) == 0) {
#pragma unroll
                for (int s = 0; s < 20; s++) h[s >> 2][s & 3] = 0;
            } else {
                do {
#pragma unroll
                    for (int s = 0; s < 5; s++) ldg4_rlx(h[s], &X->halo[(role - 8 - (ti & 8)) * 160 + s * 32 + lane]);
                } while (__any_sync(~0u, min(min(min(h[0][0], h[1][0]), min(h[2][0], h[3][0])), h[4][0]) == 0) && ++gd < SPIN_LIMIT);
            }
            const uint32_t p8 = sm + OFF_P8 - 4096, va = p8 + 2048 + (lane & 7) * VP + (lane >> 3) * 16;
            sts4(p8 + 2048 + 1408 + lane * 16, h[0]); sts4(p8 + 1408 + lane * 16, h[1]); sts2(p8 + (lane >> 4) * 2048 + 1920 + (lane & 15) * 8, h[2][0], h[2][1]);
            stsm4(va, h[3]); stsm4(va + 64, h[4]); stsm2(va + 128, h[2][2], h[2][3]);
            __syncwarp();
            if (lane == 0) mbar_arrive(BAR(B_HL));
            STAMPT(19, 288);
            uint2* const rp = pinp((uint2*)&X->ra[(lane & 7) * 8][0] + ti);
            const uint2* const rq = pinp((const uint2*)&X->ra[grp * 8][0] + (lane & 15));
            const uint32_t tk0 = PIN(((ti & 7) * 128 + lane * 4) * 2 + (ti >> 3) + 1);
            mbar_wait(BAR(B_G3), 0);
            if (j == (ti & 7)) {
                lds4(h[0], sm + OFF_TAB + 1024 + lane * 16);
                const uint32_t k01 = max(h[0][0], h[0][1]), k = max(k01, max(h[0][2], h[0][3])), km = __reduce_max_sync(~0u, k);
                const uint32_t t = tk0 + (k01 == k ? (h[0][0] == k ? 0 : 2) : (h[0][2] == k ? 4 : 6)), tk = __reduce_min_sync(~0u, k == km ? t : ~0u);
                asm volatile("{.reg .pred p; setp.lt.u32 p, %2, 8; @p red.relaxed.gpu.global.max.u64 [%0], %1;}" ::"l"(rp), "l"((unsigned long long)tk << 32 | km), "r"(lane) : "memory");
            }
            pause(D_REC);
            uint32_t kwin;
            bool bad;
            do { ldg2_rlx(h[0], rq); bad = __any_sync(~0u, h[0][1] == 0); kwin = __reduce_max_sync(~0u, h[0][0]); gd++; } while (bad && gd < SPIN_LIMIT);
            {
                const uint32_t t = (h[0][1] - 1) & 2047, wi = (t & 1) * 64 + (t >> 5), wv[4] = {kwin, t, wi, wi * 320}, m = __ballot_sync(~0u, h[0][0] == kwin);
                if ((m & -m) == 1u << lane) { sts4(sm + OFF_EP + EP_US + 32, wv); mbar_arrive(BAR(B_WIN)); }
            }
            if (lane < 8 && role < 20) stg4_rlx(&S->tab[role][lane], 0u, 0u, 0u, 0u);
            return;
        }
        const int at = tid - 320;
        const int kg = at < 40 ? 80 * j + 2 * at : max(fi - 88, 0) * 16 + 2 * (at & 7);
        const uint32_t w2 = *(const uint32_t*)(wr + kg);
        mbar_wait(BAR(B_T0), 0);
        {
            uint4* p = &X->o[4 * 128 * 256] + role * RV + at;
#pragma unroll 1
            for (int r = 0; r < RV / 64; r++) {
                stg4_rlx(p, 0u, 0u, 0u, 0u);
                p += 64;
                __nanosleep(RSLEEP);
            }
        }
        bar_sync(5, 64);
        if (at == 0) { mbar_wait(BAR(B_TB), 0); }
        if (at == 0) asm volatile("red.release.gpu.global.add.u32 [%0], 1;" ::"l"(&S->cnt) : "memory");
        mbar_wait(BAR(B_RDY), 0);
        const uint32_t* const mp = (const uint32_t*)&S->tab[0][0] + ((kg >> 4) & 3) * 8 + (kg & 6) + ((kg >> 3) & 1);
        const int p = odd ? (at < 8 ? at + 32 : at - 8) : at, lm = min(lane, 9);
        const uint32_t a = sm + OFF_EP + (p & 3) * 48 + (p >> 2) * 4;
#pragma unroll 1
        for (int ph = 0; ph < 4; ph++) {
            uint32_t v, us;
            mbar_wait(BAR(ph < 2 ? TB_GO : TB_GO2), 0);
            while (true) {
                v = ldg1_rlx(mp + (ph < 2 ? 20 + ph + (kg >> 6) * 2 : 20 + ph * 10 + (kg >> 6)) * 288);
                us = ldg1_rlx(&S->tab[ph < 2 ? 20 + ph + lm * 2 : 20 + ph * 10 + lm][8]);
                if (!__any_sync(~0u, min(v, us) == 0) || ++gd > SPIN_LIMIT) break;
                __nanosleep(200);
            }
            if (at < 40) {
                sts1(a + ph * 192, v);
                if (ph == 1) {
                    const float u0 = blo(v) * blo(w2), u1 = bhi(v) * bhi(w2);
                    const uint32_t uh = pack2(u0, u1);
                    sts1(a + 768, 0x3f803f80u); sts1(a + 960, uh); sts1(a + 1152, pack2(u0 - blo(uh), u1 - bhi(uh)));
                }
            } else sts1(sm + OFF_EP + EP_GD + (at & 7) * 4, v);
            float t = lane < 10 ? __uint_as_float(us) : 0.f;
#pragma unroll
            for (int o = 1; o < 16; o <<= 1) t += __shfl_xor_sync(~0u, t, o);
            if (at == 0) sts1f(sm + OFF_EP + EP_US + 12 + ph * 4, t);
            __syncwarp();
            if (lane == 0 && ph) mbar_arrive(BAR(B_EP - 1 + ph));
        }
        STAMPT(20, 320);
    } else {
        asm volatile("setmaxnreg.inc.sync.aligned.u32 216;");
        asm volatile("barrier.cluster.wait.aligned;" ::: "memory");
        LANE_VARS
        const int tw = ti * 8 + warp;
        const uint32_t oo = tw * 4096 + j * 512 + lane * 16;
        const uint32_t pair = (uint32_t)(lane & 1) << 24;
        const uint32_t hi = lane >> 4, xa = sm + (warp * 16 + (lane & 15)) * 128 + ((hi ^ (lane & 7)) << 4);
        const uint32_t p8 = sm + OFF_P8 + warp * 2048, q8 = p8 - (warp ? 2048 : 4096), q9 = p8 - 2048 + (warp ? 16384 : 0);
        const uint32_t l16 = PIN(lane * 16), kt = PIN(hi * 16384 + (lane & 15) * 8), va = PIN(p8 + (lane & 7) * VP + (lane >> 3) * 16);
        const uint32_t vc = PIN(p8 + (lane & 7) * VP + fh * 16384 + hi * 16);
        const uint32_t vh = PIN((fh ? p8 : q9) + (lane & 7) * VP + hi * 16), kh = PIN((hi ? q9 : q8) + (lane & 15) * 8);
        const uint32_t mgt = PIN((2 * q > g ? 0xffffu : 0u) | (2 * q + 1 > g ? 0xffff0000u : 0u));
        uint32_t rr0, rr1, nn0, nn1;
        {
            float gA[2][4] = {}, gB[2][4] = {};
            uint32_t xb = sm + (warp * 16 + frow) * 128 + ((fh ^ (lane & 7)) << 4), one[16];
#pragma unroll
            for (int k = 0; k < 16; k++) one[k] = 0x3f803f80u + ((uint32_t)tid >> (12 + k));
            uint32_t a[10][4][4];
            const uint32_t xk[4] = {xb, xb ^ 32, xb ^ 64, xb ^ 96};
#pragma unroll
            for (int c = -1; c < 10; c++) {
                if (c < 9) {
                    mbar_wait(BAR(B_XF + c + 1), 0);
#pragma unroll
                    for (int k = 0; k < 4; k++) ldsm4(a[c + 1][k], xk[k] + (c + 1) * 16384);
                }
                if (c >= 0) {
#pragma unroll
                    for (int k = 0; k < 4; k++) {
                        const uint32_t* v = a[c][k];
                        uint32_t t[4];
#pragma unroll
                        for (int e = 0; e < 4; e++) asm volatile("mov.b32 %0, %1;" : "=r"(t[e]) : "r"(v[e]));
                        mma16(gA[k & 1], t[0], one[k * 4], t[1], one[k * 4 + 1], v[0], v[1]);
                        mma16(gB[k & 1], t[2], one[k * 4 + 2], t[3], one[k * 4 + 3], v[2], v[3]);
                    }
                }
            }
            const int src = (lane & ~3) | (g >> 1), e = g & 1;
            const float ss0 = __shfl_sync(~0u, e ? gA[0][1] + gA[1][1] : gA[0][0] + gA[1][0], src), ss1 = __shfl_sync(~0u, e ? gB[0][1] + gB[1][1] : gB[0][0] + gB[1][0], src);
            const float m0 = __shfl_sync(~0u, e ? gA[0][3] + gA[1][3] : gA[0][2] + gA[1][2], src) * (1.f / 640), m1 = __shfl_sync(~0u, e ? gB[0][3] + gB[1][3] : gB[0][2] + gB[1][2], src) * (1.f / 640);
            const float r0 = rbf(rsq(fmaxf(ss0 * (1.f / 640) - m0 * m0, 0.f) + 1e-5f)), r1 = rbf(rsq(fmaxf(ss1 * (1.f / 640) - m1 * m1, 0.f) + 1e-5f));
            rr0 = pack2(r0, r0); rr1 = pack2(r1, r1); nn0 = pack2(-m0 * r0, -m0 * r0); nn1 = pack2(-m1 * r1, -m1 * r1);
        }
        uint32_t xr[5][4];
#pragma unroll
        for (int s = 0; s < 5; s++) {
            const int ks = 5 * j + (odd ? (s == 4 ? 0 : s + 1) : s);
            ldsm4(xr[s], (xa ^ ((ks & 3) * 32)) + (ks >> 2) * 16384);
        }
        STAMP(0);
        mbar_wait(BAR(B_T0), 0);
        float acc[120];
#pragma unroll
        for (int i = 0; i < 120; i++) asm volatile("" : "=f"(acc[i]));
        {
            uint32_t a[2][2][4], raw[2][4], tt[2][4];
            uint32_t tb = sm + OFF_TAB + q * 16, xp = xa;
            auto load = [&](int u) {
                ldsm4(raw[0], xp ^ (u * 64)); ldsm4(raw[1], xp ^ (u * 64 + 32));
                lds4(tt[0], tb + u * 64 + 1280); lds4(tt[1], tb + u * 64);
            };
            auto xform = [&](uint32_t (*dst)[4]) {
#pragma unroll
                for (int h = 0; h < 2; h++) {
                    dst[h][0] = hf2(hf2(raw[h][0], rr0, nn0), tt[0][2 * h], tt[1][2 * h]); dst[h][1] = hf2(hf2(raw[h][1], rr1, nn1), tt[0][2 * h], tt[1][2 * h]);
                    dst[h][2] = hf2(hf2(raw[h][2], rr0, nn0), tt[0][2 * h + 1], tt[1][2 * h + 1]); dst[h][3] = hf2(hf2(raw[h][3], rr1, nn1), tt[0][2 * h + 1], tt[1][2 * h + 1]);
                }
            };
            const uint64_t dm0 = al ? mkdesc(SM0, 2048, 1024, 1) : mkdesc(SM0, 1024, 512, 2), dt0 = mkdesc(SM0 + 12288, 512, 256, 3);
            load(0); xform(a[0]);
            STAMP(3);
#pragma unroll 1
            for (int i2 = 0; i2 < 10; i2++) {
#pragma unroll
                for (int u = 0; u < 2; u++) {
                    const int it = i2 * 2 + u;
                    const uint32_t bo = wbuf(it) >> 4;
                    mbar_wait(BAR(B_WF + it), 0);
                    if (LAG && warp < 4 && i2 * 2 + u == 20 - LAG) bar_sync(4, 256);
                    wg_fence();
#pragma unroll
                    for (int h = 0; h < 2; h++) { wgmma_rs_n192(acc, a[u][h], dm0 + bo + h * 384, (u | h) ? 1 : i2); wgmma_rs_n48(acc + 96, a[u][h], dt0 + bo + h * 96, (u | h) ? 1 : i2); }
                    wg_commit();
                    if (LAG && u == 1 && warp >= 4 && i2 == 9) asm volatile("bar.arrive 4, 256;" ::: "memory");
                    if (u == 1) { xp += 16384; tb += 128; }
                    if (u == 1 && (i2 & 1) && i2 < 9) mbar_wait(BAR(B_TB + (i2 >> 1)), 0);
                    load(u ^ 1);
                    wg_wait<1>();
                    if (lane < 2 && (u == 1 || i2 > 0)) mbar_arrive_cl(pair + BAR0(B_WE - 1 + it));
                    xform(a[u ^ 1]);
                }
            }
        }
        uint32_t own[5][4], ab[3][7][4], sv, tc, fz = 0;
        const char* op[7];
        auto ldo = [&](int s, uint32_t (*dst)[4]) {
#pragma unroll
            for (int w = 0; w < 7; w++) ldg4_rlx(dst[w], op[w] + (4 - s) * 524288);
        };
        {
            uint32_t Q[10][2], K[2][10], V[2][10];
            mbar_wait(BAR(B_RDY), 0);
            const bool pub = warp == 7 && (~ti & 7);
            uint4* const hp = pinp(&X->halo[(role - (ti & 8)) * 160 + lane]);
            sv = lds1(sm + OFF_EP + EP_US + 8); tc = (sv ^ 0x40000000u) - 0x20000000u;
            wg_wait<0>();
            STAMP(4); STAMPT(18, 128);
#define ACC_IDX(t, m) (odd_ ? (t >= 2 ? m * 32 + (t - 2) * 4 : 96 + m * 8 + t * 4) : (t < 8 ? m * 32 + t * 4 : 96 + m * 8 + (t - 8) * 4))
#define PACK1(odd_v) { constexpr bool odd_ = odd_v; _Pragma("unroll") for (int t = 0; t < 10; t++) { \
                K[1][t] = pack2(acc[ACC_IDX(t, 1) + 2], acc[ACC_IDX(t, 1) + 3]); V[1][t] = pack2(acc[ACC_IDX(t, 2) + 2], acc[ACC_IDX(t, 2) + 3]); } }
#define PACK2(odd_v) { constexpr bool odd_ = odd_v; _Pragma("unroll") for (int t = 0; t < 10; t++) { \
                V[0][t] = pack2(acc[ACC_IDX(t, 2)], acc[ACC_IDX(t, 2) + 1]); \
                K[0][t] = pack2(acc[ACC_IDX(t, 1)], acc[ACC_IDX(t, 1) + 1]); \
                Q[t][0] = pack2(acc[ACC_IDX(t, 0)], acc[ACC_IDX(t, 0) + 1]); Q[t][1] = pack2(acc[ACC_IDX(t, 0) + 2], acc[ACC_IDX(t, 0) + 3]); } }
            if (odd) PACK1(true) else PACK1(false)
            if (pub) {
                K[1][0] = nz(K[1][0]); K[1][5] = nz(K[1][5]); K[1][2] = nz(K[1][2]); V[1][0] = nz(V[1][0]); V[1][4] = nz(V[1][4]);
                stg4_rlx(hp, K[1][0], K[1][1], K[1][3], K[1][4]); stg4_rlx(hp + 32, K[1][5], K[1][6], K[1][8], K[1][9]);
                stg4_rlx(hp + 96, V[1][0], V[1][1], V[1][2], V[1][3]); stg4_rlx(hp + 128, V[1][4], V[1][5], V[1][6], V[1][7]); stg4_rlx(hp + 64, K[1][2], K[1][7], V[1][8], V[1][9]);
            }
            uint32_t VT[5][4], KH[10];
            {
                const uint32_t k0[4] = {K[1][0], K[1][1], K[1][3], K[1][4]}, k1[4] = {K[1][5], K[1][6], K[1][8], K[1][9]};
                sts4(p8 + 16384 + 1408 + l16, k0); sts4(p8 + 1408 + l16, k1); sts2(p8 + 1920 + kt, K[1][2], K[1][7]);
                stsm4(va + 16384, V[1]); stsm4(va + 16384 + 64, V[1] + 4); stsm2(va + 16384 + 128, V[1][8], V[1][9]);
            }
            __syncwarp();
            if (lane == 0) mbar_arrive(BAR(B_HL + 1 + warp));
            if (odd) PACK2(true) else PACK2(false)
            stsm4(va, V[0]); stsm4(va + 64, V[0] + 4); stsm2(va + 128, V[0][8], V[0][9]);
            __syncwarp();
#pragma unroll
            for (int s = 0; s < 5; s++) ldsm4t(VT[s], vc + s * 32);
            float sb[4][4], sc[4][4];
            uint32_t qs[4][2];
#pragma unroll
            for (int h = 0; h < 4; h++) {
                const int ts = (h >> 1) * 5 + 2, ta = (h >> 1) * 5 + (h & 1) * 3;
                const bool mine = (q >> 1) == (h & 1);
                qs[h][0] = mine ? Q[ts][0] : 0u; qs[h][1] = mine ? Q[ts][1] : 0u;
                mma16c(sb[h], Q[ta][0], Q[ta][1], Q[ta + 1][0], Q[ta + 1][1], K[0][ta], K[0][ta + 1], 0.f, 0.f);
                mma16c(sc[h], Q[ta][0], Q[ta][1], Q[ta + 1][0], Q[ta + 1][1], K[1][ta], K[1][ta + 1], 0.f, 0.f);
                mma8(sb[h], qs[h][0], qs[h][1], K[0][ts]);
                mma8(sc[h], qs[h][0], qs[h][1], K[1][ts]);
            }
            const bool gt0 = mgt & 1, gt1 = (int)mgt < 0;
            auto half = [&](int h0, int h1, int e, float (*pv)[4], float (*cu)[4], uint32_t (*VT)[4]) {
                const float cs = 0.22360679774997896f * 1.4426950408889634f;
                uint32_t p[4];
                float t0[4], t1[4], m[4];
#pragma unroll
                for (int h = h0; h < h1; h++) { t0[h] = gt0 ? pv[h][2 * e] : cu[h][2 * e]; t1[h] = gt1 ? pv[h][2 * e + 1] : cu[h][2 * e + 1]; m[h] = fmaxf(t0[h], t1[h]); }
#pragma unroll
                for (int h = h0; h < h1; h++) m[h] = fmaxf(m[h], __shfl_xor_sync(~0u, m[h], 1));
#pragma unroll
                for (int h = h0; h < h1; h++) m[h] = fmaxf(m[h], __shfl_xor_sync(~0u, m[h], 2)) * -cs;
#pragma unroll
                for (int h = h0; h < h1; h++) p[h] = pack2(ex2(fmaf(t0[h], cs, m[h])), ex2(fmaf(t1[h], cs, m[h])));
#pragma unroll
                for (int pr = h0 / 2; pr < h1 / 2; pr++) {
                    const uint32_t a0 = p[2 * pr] & mgt, a1 = p[2 * pr + 1] & mgt, a2 = p[2 * pr] & ~mgt, a3 = p[2 * pr + 1] & ~mgt;
                    float l[4];
                    mma16c(l, a0, a1, a2, a3, 0x3f803f80u, 0x3f803f80u, 0.f, 0.f);
                    l[0] = rcp(l[0]); l[2] = rcp(l[2]);
#pragma unroll
                    for (int r = 0; r < 5; r++) {
                        const int t = pr * 5 + r;
                        float d[4];
                        mma16c(d, a0, a1, a2, a3, VT[t >> 1][(t & 1) * 2], VT[t >> 1][(t & 1) * 2 + 1], 0.f, 0.f);
                        const bool od = r == 2 ? (q & 2) : r > 2;
                        const float li = od ? l[2] : l[0];
                        own[t >> 1][(t & 1) * 2 + e] = pack2((od ? d[2] : d[0]) * li, (od ? d[3] : d[1]) * li);
                    }
                }
            };
            mbar_wait(BAR(B_HL + warp), 0);
            uint32_t VH[5][4];
            float sa[4][4];
            lds4(KH, q9 + 1408 + l16); lds4(KH + 4, q8 + 1408 + l16); lds2(KH + 8, kh + 1920);
#pragma unroll
            for (int s = 0; s < 5; s++) ldsm4t(VH[s], vh + s * 32);
            STAMP(5); STAMPT(25, 64);
            fz |= clock32();
            const float ninf = (tw & 63) == 0 ? -INFINITY : 0.f;
#pragma unroll
            for (int h = 0; h < 4; h++) {
                const int ta = (h >> 1) * 5 + (h & 1) * 3;
                mma16c(sa[h], Q[ta][0], Q[ta][1], Q[ta + 1][0], Q[ta + 1][1], KH[2 * h], KH[2 * h + 1], ninf, ninf);
                mma8(sa[h], qs[h][0], qs[h][1], KH[8 + (h >> 1)]);
            }
            auto sto = [&](int s) { own[s][0] = s ? tagw(own[s][0], tc) : nz(own[s][0]); stg4_rlx((char*)X->o + oo + (4 - s) * 524288, own[s][0], own[s][1], own[s][2], own[s][3]); };
            if (SPLIT == 1) {
                half(0, 2, 1, sb, sc, VT); half(0, 2, 0, sa, sb, VH);
                sto(0); sto(1);
                fz |= clock32();
                half(2, 4, 1, sb, sc, VT); half(2, 4, 0, sa, sb, VH);
                if (ELD) {
#pragma unroll
                    for (int w = 0; w < 7; w++) op[w] = (const char*)X->o + (oo ^ (w * 512 + 512));
                    fz |= clock32();
                    if (ELD == 4) sto(2);
                    ldo(0, ab[0]);
                    if (ELD == 2) ldo(1, ab[1]);
                }
                if (ELD != 4) sto(2);
                sto(3); sto(4);
            } else {
                half(0, 4, 1, sb, sc, VT); half(0, 4, 0, sa, sb, VH);
                sto(0); sto(1); sto(2); sto(3); sto(4);
            }
#pragma unroll
            for (int w = 0; w < 7; w++) op[w] = (const char*)X->o + (oo ^ (w * 512 + 512));
        }
        STAMP(6); STAMPT(21, 128); STAMPT(26, 64);
        float ac2[40];
#pragma unroll
        for (int i = 0; i < 40; i++) asm volatile("" : "=f"(ac2[i]));
        {
            const uint64_t d0 = mkdesc(SM0, 5120, 512, 2);
            mbar_wait(BAR(B_WO0), 0);
#pragma unroll
            for (int s = 1; s < 5; s++) own[s][0] -= tc;
            wg_fence();
#pragma unroll
            for (int s = 0; s < 5; s++) wgmma_rs_n80(ac2, own[s], d0 + (wobuf(0) >> 4) + s * 64, s);
            wg_commit();
            const uint32_t t6 = clock32();
            fz |= t6;
            if (!ELD) { pause_until(t6, D_O); ldo(0, ab[0]); }
            if (ELD == 3) ldo(1, ab[1]);
            mbar_wait(BAR(B_WO), 0);
#pragma unroll
            for (int s = 0; s < 5; s++) {
                uint32_t (*cur)[4] = ab[s % 3];
                if (s == 0) await7<0>(cur, op, fz, sv);
                else {
                    if (s == 1) await7<1>(cur, op, fz, sv); else if (s == 2) await7<2>(cur, op, fz, sv); else if (s == 3) await7<3>(cur, op, fz, sv); else await7<4>(cur, op, fz, sv);
#pragma unroll
                    for (int w = 0; w < 7; w++) cur[w][0] -= tc;
                }
                if (s == 0) { STAMP(7); STAMPT(1, 128); }
                wg_fence();
#pragma unroll
                for (int w = 1; w < 8; w++) wgmma_rs_n80(ac2, cur[w - 1], d0 + (wobuf(w) >> 4) + s * 64, 1);
                wg_commit();
                if (s < 3) { if (s) wg_wait<1>(); else fz |= clock32(); if (s == 0 && ELD != 2 && ELD != 3) ldo(1, ab[1]); if (s == 0 && D_2) pause_until(t6, D_2); ldo(s + 2, ab[(s + 2) % 3]); }
                if (s == FD_AT && lane == 0) mbar_arrive(BAR(B_G2));
            }
        }
        mbar_wait(BAR(B_EP), 0);
        uint32_t tga[12], tst[12];
        const uint32_t ep = sm + OFF_EP + q * 48;
#pragma unroll
        for (int s = 0; s < 3; s++) { lds4(tga + 4 * s, ep + s * 16); lds4(tst + 4 * s, ep + 768 + min(g, 2) * 192 + s * 16); }
        uint4* const sp0 = pinp(&X->stats[j][tw * 16 + g]);
        const int prow = (ti & 7) * 128 + warp * 16;
        const uint4* const sp = pinp(&X->stats[hi * 4][tw * 16 + (lane & 15)]);
        const int dsrc = PIN((lane & ~3) | (g >> 1));
        wg_wait<0>();
        if (lane == 0) mbar_arrive(BAR(B_G4));
        STAMP(8); STAMPT(23, 128);
        {
            float gA[2][4] = {}, gB[2][4] = {}, sd[4] = {};
#pragma unroll
            for (int s = 0; s < 5; s++) {
#pragma unroll
                for (int e = 0; e < 4; e++) xr[s][e] = hf2(tga[2 * s + (e >> 1)], pack2(ac2[s * 8 + e * 2], ac2[s * 8 + e * 2 + 1]), xr[s][e]);
                mma16(sd, xr[s][0], xr[s][1], xr[s][2], xr[s][3], tst[2 * s], tst[2 * s + 1]);
                mma8(gA[0], xr[s][0], xr[s][1], xr[s][0]); mma8(gB[0], xr[s][0], xr[s][1], xr[s][1]);
                mma8(gA[1], xr[s][2], xr[s][3], xr[s][2]); mma8(gB[1], xr[s][2], xr[s][3], xr[s][3]);
            }
            const float l0 = __shfl_down_sync(~0u, sd[0], 1), l1 = __shfl_down_sync(~0u, sd[2], 1);
            const float q0 = __shfl_sync(~0u, fsel(g & 1, gA[0][1] + gA[1][1], gA[0][0] + gA[1][0]), dsrc), q1 = __shfl_sync(~0u, fsel(g & 1, gB[0][3] + gB[1][3], gB[0][2] + gB[1][2]), dsrc);
            stg4_if(q == 0, sp0, __float_as_uint(sd[0]), __float_as_uint(sd[1] + l0), __float_as_uint(q0), 1u);
            stg4_if(q == 0, sp0 + 8, __float_as_uint(sd[2]), __float_as_uint(sd[3] + l1), __float_as_uint(q1), 1u);
        }
        const uint32_t t9 = clock32();
        STAMP(9);
        uint32_t fg[5][4], fu[5][4], tcb[12], tsb[12];
        uint32_t st[4][4];
        if (fi < 108) {
            mbar_wait(BAR(B_FG), 0);
#pragma unroll
            for (int s = 0; s < 5; s++) {
                const uint32_t off = sm + OFF_WG + (5 * warp + ((warp & 1) ? (s == 4 ? 0 : s + 1) : s)) * 1024 + frow * 64 + ((fh ^ ((lane >> 1) & 3)) << 4);
                ldsm4t(fg[s], off); ldsm4t(fu[s], off ^ 32);
            }
        }
        pause_until(t9, D_ST);
#pragma unroll
        for (int e = 0; e < 4; e++) ldg4_rlx(st[e], sp + e * 2056);
        mbar_wait(BAR(B_EP2), 0);
#pragma unroll
        for (int s = 0; s < 3; s++) { lds4(tcb + 4 * s, ep + 192 + s * 16); lds4(tsb + 4 * s, ep + 384 + s * 16); }
        int crow;
        {
            const float2 su = lds2f(sm + OFF_EP + EP_US + 16);
            int gd = 0;
            const uint32_t ka = PIN(sm + OFF_TAB + 1024 + warp * 64 + (lane & 15) * 4);
            gd = clock32() >> 31;
            float v[3];
            bool bad;
            while (true) {
                bad = __any_sync(~0u, (st[0][3] & st[1][3] & st[2][3] & st[3][3]) == 0);
#pragma unroll
                for (int e = 0; e < 3; e++) {
                    v[e] = (__uint_as_float(st[0][e]) + __uint_as_float(st[1][e])) + (__uint_as_float(st[2][e]) + __uint_as_float(st[3][e]));
                    v[e] += __shfl_xor_sync(~0u, v[e], 16);
                }
                if (!bad || ++gd > SPIN_LIMIT) break;
#pragma unroll
                for (int e = 0; e < 4; e++) ldg4_again(st[e], sp + e * 2056);
            }
            STAMP(10);
            const float m = v[0] * (1.f / 640), rs = rsq(fmaxf(fmaf(v[2], 1.f / 640, 1e-5f) - m * m, 1e-5f));
            const uint32_t key = fkey(fmaf(rs, fmaf(-m, su.x, v[1]), su.y));
            sts1(ka, key);
            __syncwarp();
            if (lane == 0) mbar_arrive(BAR(B_G3));
            gd = clock32() >> 31;
            crow = (__ffs(__ballot_sync(~0u, key == __reduce_max_sync(~0u, key))) - 1 + gd * 16) & 15;
            const uint32_t rn = pack2(rs, -m * rbf(rs)), a0 = __shfl_sync(~0u, rn, g), a1 = __shfl_sync(~0u, rn, g + 8);
            rr0 = __byte_perm(a0, 0, 0x1010); nn0 = __byte_perm(a0, 0, 0x3232); rr1 = __byte_perm(a1, 0, 0x1010); nn1 = __byte_perm(a1, 0, 0x3232);
        }
        {
            const bool up = crow >= 8;
            const uint32_t rr = up ? rr1 : rr0, nn = up ? nn1 : nn0;
            if (g == (crow & 7)) {
                uint4* cp = &X->cand[j][tw * 20 + q];
#pragma unroll
                for (int s = 0; s < 5; s++) {
                    const uint32_t xa_ = up ? xr[s][1] : xr[s][0], xb_ = up ? xr[s][3] : xr[s][2];
                    stg4_rlx(cp + s * 4, nz(hf2(hf2(xa_, rr, nn), tcb[2 * s], tsb[2 * s])), hf2(hf2(xb_, rr, nn), tcb[2 * s + 1], tsb[2 * s + 1]), xa_, xb_);
                }
            }
        }
        STAMP(11);
        const uint32_t stg = sm + 5 * WST + warp * 2560;
        {
            mbar_wait(BAR(B_EP3), 0);
#pragma unroll
            for (int s = 0; s < 3; s++) lds4(tga + 4 * s, ep + 576 + s * 16);
#pragma unroll
            for (int s = 0; s < 5; s++) {
#pragma unroll
                for (int e = 0; e < 4; e++) { const int t = 2 * s + (e >> 1); xr[s][e] = hf2(tga[t], hf2(hf2(xr[s][e], (e & 1) ? rr1 : rr0, (e & 1) ? nn1 : nn0), tcb[t], tsb[t]), xr[s][e]); }
            }
            mbar_wait(BAR(B_G4), 0);
#pragma unroll
            for (int s = 0; s < 5; s++) stsm4(stg + (lane & 15) * 160 + (odd ? (s == 4 ? 0 : s + 1) : s) * 32 + hi * 16, xr[s]);
            asm volatile("fence.proxy.async.shared::cta;" ::: "memory");
            __syncwarp();
            if (elect1()) tma3d_st(&mout, 80 * j, ti >> 3, prow + (~crow & 8), stg + (~crow & 8) * 160);
        }
        STAMP(12);
        const char* cp = (const char*)pinp(&X->cand[warp][q]);
        uint32_t* const ap0 = pinp((uint32_t*)&X->ra[fi >> 1][8 + (fi & 1) * 4] + (lane & 8) + (lane & 3) * 2 + ((lane >> 2) & 1));
        const uint32_t rw = PIN(sm + OFF_RED - 256 + (q * 4 + (g >> 1)) * 80 + warp * 8 + (g & 1) * 4), rd = PIN(sm + OFF_RED - 256 + (lane & 15) * 80);
        if (smem_u32(sm_raw) != sm) return;
        uint32_t wv[4]; int gd = 0;
        mbar_wait(BAR(B_WIN), 0);
        lds4(wv, sm + OFF_EP + EP_US + 32);
        const uint32_t kwin = wv[0];
        const int tokwin = wv[1], win = wv[2];
        STAMP(13);
        if (fi < 108) {
            uint32_t hb[5][2];
            float mine;
            bool bad;
            cp += wv[3];
            do {
#pragma unroll
                for (int s = 0; s < 5; s++) ldg2_rlx(hb[s], cp + s * 64);
                bad = __any_sync(~0u, min(min(min(hb[0][0], hb[1][0]), min(hb[2][0], hb[3][0])), hb[4][0]) == 0);
                float dg[2][4] = {}, du[2][4] = {};
#pragma unroll
                for (int s = 0; s < 5; s++) {
                    mma16(dg[s & 1], fg[s][0], fg[s][1], fg[s][2], fg[s][3], hb[s][0], hb[s][1]);
                    mma16(du[s & 1], fu[s][0], fu[s][1], fu[s][2], fu[s][3], hb[s][0], hb[s][1]);
                }
                mine = fsel(q & 2, fsel(q & 1, du[1][2], du[1][0]), fsel(q & 1, dg[1][2], dg[1][0])) + fsel(q & 2, fsel(q & 1, du[0][2], du[0][0]), fsel(q & 1, dg[0][2], dg[0][0]));
                sts1f(rw, mine);
                gd++;
            } while (bad && gd < SPIN_LIMIT);
            bar_sync(2, 256);
            if (warp == 0) {
                uint32_t v[4][4];
#pragma unroll
                for (int e = 0; e < 4; e++) lds4(v[e], rd + e * 16);
                float t[2];
#pragma unroll
                for (int e = 0; e < 2; e++)
                    t[e] = ((__uint_as_float(v[0][e]) + __uint_as_float(v[0][e + 2])) + (__uint_as_float(v[1][e]) + __uint_as_float(v[1][e + 2]))) +
                           ((__uint_as_float(v[2][e]) + __uint_as_float(v[2][e + 2])) + (__uint_as_float(v[3][e]) + __uint_as_float(v[3][e + 2])));
                uint32_t pr = pack2(t[0], t[1]);
                if (!(fi & 1)) pr = pack2(blo(pr) * sigm(blo(pr)), bhi(pr) * sigm(bhi(pr)));
                stg1_if(lane < 16, ap0, nz(pr));
            }
        }
        STAMP(14);
        if (win != tw) {
            if (elect1()) tma3d_st(&mout, 80 * j, ti >> 3, prow + (crow & 8), stg + (crow & 8) * 160);
        } else {
#pragma unroll 1
            for (int r = crow & 8; r <= (crow | 7); r++)
                if (r != crow && lane < 20) { uint32_t v[2]; lds2(v, stg + r * 160 + lane * 8); *(uint2*)(out + (size_t)((prow + r) * 2 + (ti >> 3)) * 640 + 80 * j + lane * 4) = make_uint2(v[0], v[1]); }
        }
        if (fi >= 88) {
            const int d = fi - 88, dj = d / 5, dm = d - dj * 5, sp = (dj & 1) ? (dm == 0 ? 4 : dm - 1) : dm;
            const int ks0 = min(warp * 14, 94);
            const uint32_t frag = frow * 32 + ((fh ^ ((lane >> 2) & 1)) << 4);
            uint32_t fd[14][4];
            mbar_wait(BAR(B_FD), 0);
#pragma unroll
            for (int s = 0; s < 14; s++) ldsm4t(fd[s], sm + OFF_WD + (ks0 + s) * 512 + frag);
            const float sf = sigm(rbf(__uint_as_float((kwin & 0x80000000u) ? kwin & 0x7fffffffu : ~kwin)));
            const uint32_t sg = PIN(pack2(sf, sf));
            const uint32_t gbd = lds1(sm + OFF_EP + EP_GD + (lane & 7) * 4);
            uint32_t* const op = (uint32_t*)(out + (size_t)tokwin * 640 + d * 16) + (lane & 7);
            uint32_t bsv[4], ag[4], au[4];
            const uint4* ap = &X->ra[(ks0 >> 1) + min(g, 6)][8 + q];
            const uint32_t keep = warp == 7 && g < 2 ? 0u : ~0u;
            const uint32_t as = PIN(sm + 7 * WST + warp * 512 + q * 16), aw = PIN(sm + 7 * WST + warp * 512 + g * 64 + (q & 1) * 32 + (q >> 1) * 8);
            const uint32_t yw = PIN(sm + OFF_TAB + ((q & 1) * 4 + (g >> 1)) * 80 + warp * 8 + (g & 1) * 4), yr = PIN(sm + OFF_TAB + (lane & 7) * 80);
            bool bad;
            do {
                ldg4_rlx(ag, ap); ldg4_rlx(au, ap + 4); ldg4_rlx(bsv, &X->cand[dj][win * 20 + sp * 4 + q]);
                bad = __any_sync(~0u, min(min(min(min(ag[0], ag[1]), min(ag[2], ag[3])), min(min(au[0], au[1]), min(au[2], au[3]))), bsv[0]) == 0);
                sts2(aw, hm2(ag[0], au[0]) & keep, hm2(ag[1], au[1]) & keep); sts2(aw + 16, hm2(ag[2], au[2]) & keep, hm2(ag[3], au[3]) & keep);
                gd++;
            } while (bad && gd < SPIN_LIMIT);
            STAMP(15);
            __syncwarp();
            float dy[4][4] = {};
            uint32_t av[7][4];
#pragma unroll
            for (int s = 0; s < 7; s++) lds4(av[s], as + s * 64);
#pragma unroll
            for (int s = 0; s < 7; s++) {
                mma16(dy[(2 * s) & 3], fd[2 * s][0], fd[2 * s][1], fd[2 * s][2], fd[2 * s][3], av[s][0], av[s][1]);
                mma16(dy[(2 * s + 1) & 3], fd[2 * s + 1][0], fd[2 * s + 1][1], fd[2 * s + 1][2], fd[2 * s + 1][3], av[s][2], av[s][3]);
            }
            sts1f(yw, (fsel(q & 1, dy[2][2], dy[2][0]) + fsel(q & 1, dy[3][2], dy[3][0])) + (fsel(q & 1, dy[0][2], dy[0][0]) + fsel(q & 1, dy[1][2], dy[1][0])));
            bar_sync(2, 256);
            if (warp == 0) {
                uint32_t v[4][4];
#pragma unroll
                for (int e = 0; e < 4; e++) lds4(v[e], yr + e * 16);
                float t[2];
#pragma unroll
                for (int e = 0; e < 2; e++)
                    t[e] = ((__uint_as_float(v[0][e]) + __uint_as_float(v[0][e + 2])) + (__uint_as_float(v[1][e]) + __uint_as_float(v[1][e + 2]))) +
                           ((__uint_as_float(v[2][e]) + __uint_as_float(v[2][e + 2])) + (__uint_as_float(v[3][e]) + __uint_as_float(v[3][e + 2])));
                const uint32_t hh = (lane & 4) ? bsv[1] : bsv[0], xx = (lane & 4) ? bsv[3] : bsv[2];
                if (lane < 8) *op = hf2(gbd, hf2(hm2(pack2(t[0], t[1]), sg), 0x3f803f80u, hh), xx);
            }
        }
        asm volatile("cp.async.bulk.commit_group;\ncp.async.bulk.wait_group.read 0;" ::: "memory");
        STAMP(16);
    }
}

typedef CUresult (*EncFn)(CUtensorMap*, CUtensorMapDataType, cuuint32_t, void*, const cuuint64_t*, const cuuint64_t*, const cuuint32_t*, const cuuint32_t*,
                          CUtensorMapInterleave, CUtensorMapSwizzle, CUtensorMapL2promotion, CUtensorMapFloatOOBfill);
static void make_map(EncFn enc, CUtensorMap* m, const void* base, int rank, const cuuint64_t* dims, const cuuint64_t* strides, const cuuint32_t* box, CUtensorMapSwizzle sw) {
    const cuuint32_t es[5] = {1, 1, 1, 1, 1};
    enc(m, CU_TENSOR_MAP_DATA_TYPE_BFLOAT16, rank, (void*)base, dims, strides, box, es, CU_TENSOR_MAP_INTERLEAVE_NONE, sw, CU_TENSOR_MAP_L2_PROMOTION_NONE, CU_TENSOR_MAP_FLOAT_OOB_FILL_NONE);
}

extern "C" void kernel_launch(void* const* d_in, const int* in_sizes, int n_in, void* d_out, int out_size) {
    typedef const __nv_bfloat16* P;
    P x = (P)d_in[0], wqkv = (P)d_in[1], wo = (P)d_in[2], wr = (P)d_in[4], wg = (P)d_in[5], wu = (P)d_in[6], wd = (P)d_in[7], c = (P)d_in[8], wmod = (P)d_in[9];
    void* fn = nullptr; cudaDriverEntryPointQueryResult qr;
    cudaGetDriverEntryPoint("cuTensorMapEncodeTiled", &fn, cudaEnableDefault, &qr);
    EncFn enc = (EncFn)fn;
    CUtensorMap mx, mw, mt, mo, mg, mu, md, mm, mw2, mout, mo2;
    { cuuint64_t d[] = {640, 2, 1024}, s[] = {1280, 2560}; cuuint32_t b[] = {64, 1, 128}; make_map(enc, &mx, x, 3, d, s, b, CU_TENSOR_MAP_SWIZZLE_128B); }
    { cuuint64_t d[] = {32, 640, 20, 3}, s[] = {3840, 64, 1280}; cuuint32_t b[] = {32, 16, 2, 3}; make_map(enc, &mw, wqkv, 4, d, s, b, CU_TENSOR_MAP_SWIZZLE_64B); }
    { cuuint64_t d[] = {640, 640, 3}, s[] = {3840, 1280}; cuuint32_t b[] = {16, 16, 3}; make_map(enc, &mt, wqkv, 3, d, s, b, CU_TENSOR_MAP_SWIZZLE_32B); }
    { cuuint64_t d[] = {640, 640}, s[] = {1280}; cuuint32_t b[] = {32, 40}; make_map(enc, &mo, wo, 2, d, s, b, CU_TENSOR_MAP_SWIZZLE_64B);
      b[0] = 16; make_map(enc, &mo2, wo, 2, d, s, b, CU_TENSOR_MAP_SWIZZLE_64B); }
    { cuuint64_t d[] = {1728, 640}, s[] = {3456}; cuuint32_t b[] = {32, 160}; make_map(enc, &mg, wg, 2, d, s, b, CU_TENSOR_MAP_SWIZZLE_64B); make_map(enc, &mu, wu, 2, d, s, b, CU_TENSOR_MAP_SWIZZLE_64B); }
    { cuuint64_t d[] = {640, 216, 8}, s[] = {1280, 1280 * 216}; cuuint32_t b[] = {16, 216, 8}; make_map(enc, &md, wd, 3, d, s, b, CU_TENSOR_MAP_SWIZZLE_32B); }
    { cuuint64_t d[] = {3840, 640}, s[] = {7680}; cuuint32_t b[] = {64, 80}; make_map(enc, &mm, wmod, 2, d, s, b, CU_TENSOR_MAP_SWIZZLE_128B); }
    { cuuint64_t d[] = {64, 640, 10, 3}, s[] = {3840, 128, 1280}; cuuint32_t b[] = {64, 16, 1, 3}; make_map(enc, &mw2, wqkv, 4, d, s, b, CU_TENSOR_MAP_SWIZZLE_128B); }
    { cuuint64_t d[] = {640, 2, 1024}, s[] = {1280, 2560}; cuuint32_t b[] = {80, 1, 8}; make_map(enc, &mout, d_out, 3, d, s, b, CU_TENSOR_MAP_SWIZZLE_NONE); }
    void* sp = nullptr;
    cudaGetSymbolAddress(&sp, g_s);
    cudaFuncSetAttribute(fused_kernel, cudaFuncAttributeMaxDynamicSharedMemorySize, SMEM_BYTES);
    fused_kernel<<<132, 384, SMEM_BYTES>>>(wmod, c, (Scratch*)sp, wqkv, wo, (__nv_bfloat16*)d_out, wr, wg, wu, wd, mm, mx, mw, mt, mo, mg, mu, md, mw2, mout, mo2);
}
```

```cpp
#include <cuda_runtime.h>
#include <cuda_bf16.h>
#include <cuda.h>
#include <stdint.h>

#define SPIN_LIMIT (1 << 17)

constexpr int RV = 704;
struct __align__(4096) Exch {
    uint4 o[5 * 128 * 256];
    uint4 halo[112 * 160];
    uint4 stats[8][2056];
    uint4 cand[8][128 * 20 + 8];
    uint4 ra[64][24];
    uint4 pad[128 * RV - (128 * 256 + 112 * 160 + 8 * 2056 + 8 * (128 * 20 + 8) + 64 * 24)];
};
struct __align__(4096) Scratch {
    Exch x;
    uint4 tab[60][72];
    unsigned cnt;
};
__device__ Scratch g_s;
#define STAMP(n)
#define STAMPT(n, t)

constexpr uint32_t OFF_W = 163840, WST = 15360;
constexpr uint32_t OFF_P8 = 131072, VP = 176;
constexpr uint32_t OFF_WD = 129024, OFF_WG = 184320;
constexpr uint32_t OFF_TAB = 225280;
constexpr uint32_t OFF_RED = OFF_TAB + 2560;
constexpr uint32_t OFF_EP = OFF_TAB + 4096;
constexpr uint32_t EP_GD = 1344, EP_US = 1376;
constexpr uint32_t OFF_BAR = OFF_EP + 1488;
constexpr uint32_t OFF_PROF = OFF_BAR + 640;
constexpr uint32_t SMEM_BYTES = OFF_PROF + 128;
enum { B_XF = 0, B_WF = 10, B_WO0 = 30, B_WO, B_FG, B_FD, B_TB, B_HL = B_TB + 4, B_G0 = B_HL + 8, B_RDY, B_WIN, B_EP, B_EP2, B_EP3, B_G2, B_G3, B_G4, B_WE = 55, B_T0 = B_WE + 19 };
#define WP0 -1
#define WP1 3
#define WOP 0
#define GUR 160
#define CPF 32
#define D_ST 400
#define D_REC 300
#define D_H 300
#define WO_MASK 0x1f5000
#define P_TAB 100
#define LAG 2
#define XWAIT 5
#define FD_AT 2
#define GU_MASK 0xaa00
#define TB_GO B_HL
#define TB_GO2 B_G2
#define TDELAY 3700
#define PFN 5
#define PF0 1
#define YSLEEP 300
#define MPF0 8
#define XDELAY 600
#define RSLEEP 40
#define HALO_GO B_G0
constexpr uint32_t SM0 = 1024;
#define BAR0(i) (SM0 + OFF_BAR + 8 * (i))
#define BAR(i) (sm + OFF_BAR + 8 * (i))

__device__ __forceinline__ uint32_t smem_u32(const void* p) { return (uint32_t)__cvta_generic_to_shared(p); }
__device__ __forceinline__ void mbar_init(uint32_t b, int cnt) { asm volatile("mbarrier.init.shared::cta.b64 [%0], %1;" ::"r"(b), "r"(cnt) : "memory"); }
__device__ __forceinline__ void mbar_expect_tx(uint32_t b, uint32_t bytes) { asm volatile("mbarrier.arrive.expect_tx.shared::cta.b64 _, [%0], %1;" ::"r"(b), "r"(bytes) : "memory"); }
__device__ __forceinline__ void mbar_arrive(uint32_t b) { asm volatile("mbarrier.arrive.shared::cta.b64 _, [%0];" ::"r"(b) : "memory"); }
__device__ __forceinline__ bool mbar_try(uint32_t b, uint32_t par) {
    uint32_t ok;
    asm volatile("{.reg .pred p; mbarrier.try_wait.parity.shared::cta.b64 p, [%1], %2; selp.u32 %0, 1, 0, p;}" : "=r"(ok) : "r"(b), "r"(par) : "memory");
    return ok;
}
__device__ __forceinline__ void mbar_wait(uint32_t b, uint32_t par) {
    asm volatile("{.reg .pred p;\nW: mbarrier.try_wait.parity.shared::cta.b64 p, [%0], %1;\n@!p bra W;}" ::"r"(b), "r"(par) : "memory");
}
__device__ __forceinline__ void bar_sync(int id, int n) { asm volatile("bar.sync %0, %1;" ::"r"(id), "r"(n) : "memory"); }
__device__ __forceinline__ void tma2d(uint32_t dst, const CUtensorMap* m, int c0, int c1, uint32_t bar) {
    asm volatile("cp.async.bulk.tensor.2d.shared::cluster.global.mbarrier::complete_tx::bytes [%0], [%1, {%3, %4}], [%2];" ::"r"(dst), "l"(m), "r"(bar), "r"(c0), "r"(c1) : "memory");
}
__device__ __forceinline__ void tma3d(uint32_t dst, const CUtensorMap* m, int c0, int c1, int c2, uint32_t bar) {
    asm volatile("cp.async.bulk.tensor.3d.shared::cluster.global.mbarrier::complete_tx::bytes [%0], [%1, {%3, %4, %5}], [%2];" ::"r"(dst), "l"(m), "r"(bar), "r"(c0), "r"(c1), "r"(c2) : "memory");
}
__device__ __forceinline__ void l2_prefetch(const void* p, uint32_t bytes) { asm volatile("cp.async.bulk.prefetch.L2.global [%0], %1;" ::"l"(p), "r"(bytes) : "memory"); }
__device__ __forceinline__ void wg_fence() { asm volatile("wgmma.fence.sync.aligned;" ::: "memory"); }
__device__ __forceinline__ void wg_commit() { asm volatile("wgmma.commit_group.sync.aligned;" ::: "memory"); }
template <int N> __device__ __forceinline__ void wg_wait() { asm volatile("wgmma.wait_group.sync.aligned %0;" ::"n"(N) : "memory"); }
__device__ __forceinline__ void ldsm4(uint32_t* r, uint32_t addr) { asm volatile("ldmatrix.sync.aligned.m8n8.x4.shared.b16 {%0,%1,%2,%3}, [%4];" : "=r"(r[0]), "=r"(r[1]), "=r"(r[2]), "=r"(r[3]) : "r"(addr) : "memory"); }
__device__ __forceinline__ void ldsm4t(uint32_t* r, uint32_t addr) { asm volatile("ldmatrix.sync.aligned.m8n8.x4.trans.shared.b16 {%0,%1,%2,%3}, [%4];" : "=r"(r[0]), "=r"(r[1]), "=r"(r[2]), "=r"(r[3]) : "r"(addr) : "memory"); }
__device__ __forceinline__ void stsm4(uint32_t addr, const uint32_t* r) { asm volatile("stmatrix.sync.aligned.m8n8.x4.shared.b16 [%4], {%0,%1,%2,%3};" ::"r"(r[0]), "r"(r[1]), "r"(r[2]), "r"(r[3]), "r"(addr) : "memory"); }
__device__ __forceinline__ void lds4(uint32_t* r, uint32_t addr) { asm volatile("ld.shared.v4.u32 {%0,%1,%2,%3}, [%4];" : "=r"(r[0]), "=r"(r[1]), "=r"(r[2]), "=r"(r[3]) : "r"(addr) : "memory"); }
__device__ __forceinline__ void sts4(uint32_t addr, const uint32_t* r) { asm volatile("st.shared.v4.u32 [%4], {%0,%1,%2,%3};" ::"r"(r[0]), "r"(r[1]), "r"(r[2]), "r"(r[3]), "r"(addr) : "memory"); }
__device__ __forceinline__ float2 lds2f(uint32_t addr) { float2 v; asm volatile("ld.shared.v2.f32 {%0,%1}, [%2];" : "=f"(v.x), "=f"(v.y) : "r"(addr) : "memory"); return v; }
__device__ __forceinline__ void sts1f(uint32_t addr, float v) { asm volatile("st.shared.f32 [%0], %1;" ::"r"(addr), "f"(v) : "memory"); }
__device__ __forceinline__ void sts1(uint32_t addr, uint32_t v) { asm volatile("st.shared.u32 [%0], %1;" ::"r"(addr), "r"(v) : "memory"); }
__device__ __forceinline__ void ldg4_rlx(uint32_t* r, const void* p) { asm volatile("{.reg .b128 t; ld.relaxed.gpu.global.b128 t, [%4]; mov.b128 {%0,%1,%2,%3}, t;}" : "=r"(r[0]), "=r"(r[1]), "=r"(r[2]), "=r"(r[3]) : "l"(p) : "memory"); }
__device__ __forceinline__ void ldg2_rlx(uint32_t* r, const void* p) { asm volatile("{.reg .b64 t; ld.relaxed.gpu.global.b64 t, [%2]; mov.b64 {%0,%1}, t;}" : "=r"(r[0]), "=r"(r[1]) : "l"(p) : "memory"); }
__device__ __forceinline__ uint32_t ldg1_rlx(const void* p) { uint32_t v; asm volatile("ld.relaxed.gpu.global.u32 %0, [%1];" : "=r"(v) : "l"(p) : "memory"); return v; }
__device__ __forceinline__ void stg4_rlx(void* p, uint32_t a, uint32_t b, uint32_t c, uint32_t d) { asm volatile("{.reg .b128 t; mov.b128 t, {%1,%2,%3,%4}; st.relaxed.gpu.global.b128 [%0], t;}" ::"l"(p), "r"(a), "r"(b), "r"(c), "r"(d) : "memory"); }
__device__ __forceinline__ void stg1_rlx(void* p, uint32_t a) { asm volatile("st.relaxed.gpu.global.u32 [%0], %1;" ::"l"(p), "r"(a) : "memory"); }
__device__ __forceinline__ uint64_t mkdesc(uint32_t addr, uint32_t lbo, uint32_t sbo, uint32_t sw) { return (uint64_t)((addr & 0x3FFFF) >> 4) | ((uint64_t)(lbo >> 4) << 16) | ((uint64_t)(sbo >> 4) << 32) | ((uint64_t)sw << 62); }
__device__ __forceinline__ uint32_t pack2(float lo, float hi) { uint32_t r; asm("cvt.rn.bf16x2.f32 %0, %1, %2;" : "=r"(r) : "f"(hi), "f"(lo)); return r; }
__device__ __forceinline__ float blo(uint32_t v) { return __uint_as_float(v << 16); }
__device__ __forceinline__ float bhi(uint32_t v) { return __uint_as_float(v & 0xffff0000u); }
__device__ __forceinline__ float rbf(float x) { return blo(pack2(x, 0.f)); }
__device__ __forceinline__ uint32_t hf2(uint32_t a, uint32_t b, uint32_t c) { uint32_t r; asm("fma.rn.bf16x2 %0, %1, %2, %3;" : "=r"(r) : "r"(a), "r"(b), "r"(c)); return r; }
__device__ __forceinline__ float ex2(float x) { float r; asm("ex2.approx.ftz.f32 %0, %1;" : "=f"(r) : "f"(x)); return r; }
__device__ __forceinline__ void mma16(float* d, uint32_t a0, uint32_t a1, uint32_t a2, uint32_t a3, uint32_t b0, uint32_t b1) {
    asm("mma.sync.aligned.m16n8k16.row.col.f32.bf16.bf16.f32 {%0,%1,%2,%3}, {%4,%5,%6,%7}, {%8,%9}, {%0,%1,%2,%3};"
                 : "+f"(d[0]), "+f"(d[1]), "+f"(d[2]), "+f"(d[3]) : "r"(a0), "r"(a1), "r"(a2), "r"(a3), "r"(b0), "r"(b1));
}
__device__ __forceinline__ void mma8(float* d, uint32_t a0, uint32_t a1, uint32_t b0) {
    asm("mma.sync.aligned.m16n8k8.row.col.f32.bf16.bf16.f32 {%0,%1,%2,%3}, {%4,%5}, {%6}, {%0,%1,%2,%3};"
                 : "+f"(d[0]), "+f"(d[1]), "+f"(d[2]), "+f"(d[3]) : "r"(a0), "r"(a1), "r"(b0));
}
__device__ __forceinline__ uint32_t fkey(float f) { const uint32_t u = __float_as_uint(f); return u ^ (((int)u >> 31) | 0x80000000u); }
__device__ __forceinline__ float rcp(float x) { float r; asm("rcp.approx.ftz.f32 %0, %1;" : "=f"(r) : "f"(x)); return r; }
__device__ __forceinline__ float sigm(float x) { return rcp(1.f + ex2(x * -1.4426950408889634f)); }
__device__ __forceinline__ void mma16c(float* d, uint32_t a0, uint32_t a1, uint32_t a2, uint32_t a3, uint32_t b0, uint32_t b1, float c0, float c1) {
    asm("mma.sync.aligned.m16n8k16.row.col.f32.bf16.bf16.f32 {%0,%1,%2,%3}, {%4,%5,%6,%7}, {%8,%9}, {%10,%11,%12,%12};"
                 : "=f"(d[0]), "=f"(d[1]), "=f"(d[2]), "=f"(d[3]) : "r"(a0), "r"(a1), "r"(a2), "r"(a3), "r"(b0), "r"(b1), "f"(c0), "f"(c1), "f"(0.f));
}
__device__ __forceinline__ void stsm2(uint32_t addr, uint32_t a, uint32_t b) { asm volatile("stmatrix.sync.aligned.m8n8.x2.shared.b16 [%2], {%0,%1};" ::"r"(a), "r"(b), "r"(addr) : "memory"); }
__device__ __forceinline__ void lds2(uint32_t* r, uint32_t addr) { asm volatile("ld.shared.v2.u32 {%0,%1}, [%2];" : "=r"(r[0]), "=r"(r[1]) : "r"(addr) : "memory"); }
__device__ __forceinline__ void sts2(uint32_t addr, uint32_t a, uint32_t b) { asm volatile("st.shared.v2.u32 [%2], {%0,%1};" ::"r"(a), "r"(b), "r"(addr) : "memory"); }
__device__ __forceinline__ uint32_t lds1(uint32_t addr) { uint32_t v; asm volatile("ld.shared.u32 %0, [%1];" : "=r"(v) : "r"(addr) : "memory"); return v; }
__device__ __forceinline__ bool elect1() { uint32_t p; asm volatile("{.reg .pred P; elect.sync _|P, 0xffffffff; selp.u32 %0, 1, 0, P;}" : "=r"(p)); return p; }
__device__ __forceinline__ void tma2d_mc(uint32_t dst, const CUtensorMap* m, int c0, int c1, uint32_t bar) {
    asm volatile("cp.async.bulk.tensor.2d.shared::cluster.global.mbarrier::complete_tx::bytes.multicast::cluster [%0], [%1, {%3, %4}], [%2], %5;" ::"r"(dst), "l"(m), "r"(bar), "r"(c0), "r"(c1), "h"((unsigned short)3) : "memory");
}
__device__ __forceinline__ void tma3d_mc(uint32_t dst, const CUtensorMap* m, int c0, int c1, int c2, uint32_t bar) {
    asm volatile("cp.async.bulk.tensor.3d.shared::cluster.global.mbarrier::complete_tx::bytes.multicast::cluster [%0], [%1, {%3, %4, %5}], [%2], %6;" ::"r"(dst), "l"(m), "r"(bar), "r"(c0), "r"(c1), "r"(c2), "h"((unsigned short)3) : "memory");
}
__device__ __forceinline__ void tma4d_mc(uint32_t dst, const CUtensorMap* m, int c0, int c1, int c2, int c3, uint32_t bar) {
    asm volatile("cp.async.bulk.tensor.4d.shared::cluster.global.mbarrier::complete_tx::bytes.multicast::cluster [%0], [%1, {%3, %4, %5, %6}], [%2], %7;" ::"r"(dst), "l"(m), "r"(bar), "r"(c0), "r"(c1), "r"(c2), "r"(c3), "h"((unsigned short)3) : "memory");
}
__device__ __forceinline__ void mbar_arrive_cl(uint32_t b) { asm volatile("mbarrier.arrive.shared::cluster.b64 _, [%0];" ::"r"(b) : "memory"); }
__device__ __forceinline__ uint32_t hm2(uint32_t a, uint32_t b) { uint32_t r; asm("mul.rn.bf16x2 %0, %1, %2;" : "=r"(r) : "r"(a), "r"(b)); return r; }
__device__ __forceinline__ uint32_t clock32() { uint32_t c; asm volatile("mov.u32 %0, %clock;" : "=r"(c)); return c; }
__device__ __forceinline__ float rsq(float x) { float r; asm("rsqrt.approx.ftz.f32 %0, %1;" : "=f"(r) : "f"(x)); return r; }
__device__ __forceinline__ void pause_until(uint32_t t0, uint32_t n) {
    asm volatile("{.reg .pred p; .reg .u32 t;\nP: mov.u32 t, %clock; sub.u32 t, t, %0; setp.lt.u32 p, t, %1;\n@p bra.uni P;}" ::"r"(t0), "r"(n) : "memory");
}
__device__ __forceinline__ void pause(uint32_t n) { if (n) { const uint32_t t = clock32(); while (clock32() - t < n) {} } }
__device__ __forceinline__ uint32_t wbuf(int it) {
    const uint32_t v = it < 4 ? it + 8 : (uint32_t)(0x8302418302b1a908ull >> (4 * it - 16)) & 15;
    return v * WST + (v >> 3) * (OFF_W - 8 * WST);
}
__device__ __forceinline__ uint32_t wobuf(int w) { return ((0x30241765u >> (4 * w)) & 7) * WST; }
__device__ __forceinline__ uint32_t inc(uint32_t v) { uint32_t r; asm volatile("{.reg .u32 t; or.b32 t, %1, 255; add.u32 %0, t, 1;}" : "=r"(r) : "r"(v)); return r; }
__device__ __forceinline__ uint32_t ldg1_acq(const void* p) { uint32_t v; asm volatile("ld.acquire.gpu.global.u32 %0, [%1];" : "=r"(v) : "l"(p) : "memory"); return v; }
__device__ __forceinline__ void tma3d_st(const CUtensorMap* m, int c0, int c1, int c2, uint32_t src) {
    asm volatile("cp.async.bulk.tensor.3d.global.shared::cta.bulk_group [%0, {%2, %3, %4}], [%1];" ::"l"(m), "r"(src), "r"(c0), "r"(c1), "r"(c2) : "memory");
}
__device__ __forceinline__ uint32_t nz(uint32_t v) { uint32_t r; asm("max.u32 %0, %1, 1;" : "=r"(r) : "r"(v)); return r; }
__device__ __forceinline__ uint32_t tagw(uint32_t w, uint32_t tc) { return ((w & 0x8000ffffu) | min(max(w & 0x7fff0000u, 0x20000000u), 0x5fff0000u)) + tc; }
template <int S_> __device__ __forceinline__ void await7(uint32_t (*r)[4], const char* const* p, uint32_t fz, uint32_t stale) {
    if (S_ == 0) asm volatile("{.reg .b128 t; .reg .pred p; .reg .u32 m, k, n;\nmov.u32 n, %clock; or.b32 n, n, %37; shr.u32 n, n, 31;\nL:\n"
        "min.u32 m, %0, %4; min.u32 m, m, %8; min.u32 m, m, %12; min.u32 m, m, %16; min.u32 m, m, %20; min.u32 m, m, %24;\n"
        "setp.eq.u32 p, m, 0; vote.sync.any.pred p, p, 0xffffffff; add.u32 n, n, 1; setp.lt.and.u32 p, n, %36, p;\n@!p bra.uni D;\n"
        "setp.eq.u32 p, %0, 0; mov.b128 t, {%0,%1,%2,%3}; @p ld.relaxed.gpu.global.b128 t, [%28+%35]; mov.b128 {%0,%1,%2,%3}, t;\n"
        "setp.eq.u32 p, %4, 0; mov.b128 t, {%4,%5,%6,%7}; @p ld.relaxed.gpu.global.b128 t, [%29+%35]; mov.b128 {%4,%5,%6,%7}, t;\n"
        "setp.eq.u32 p, %8, 0; mov.b128 t, {%8,%9,%10,%11}; @p ld.relaxed.gpu.global.b128 t, [%30+%35]; mov.b128 {%8,%9,%10,%11}, t;\n"
        "setp.eq.u32 p, %12, 0; mov.b128 t, {%12,%13,%14,%15}; @p ld.relaxed.gpu.global.b128 t, [%31+%35]; mov.b128 {%12,%13,%14,%15}, t;\n"
        "setp.eq.u32 p, %16, 0; mov.b128 t, {%16,%17,%18,%19}; @p ld.relaxed.gpu.global.b128 t, [%32+%35]; mov.b128 {%16,%17,%18,%19}, t;\n"
        "setp.eq.u32 p, %20, 0; mov.b128 t, {%20,%21,%22,%23}; @p ld.relaxed.gpu.global.b128 t, [%33+%35]; mov.b128 {%20,%21,%22,%23}, t;\n"
        "setp.eq.u32 p, %24, 0; mov.b128 t, {%24,%25,%26,%27}; @p ld.relaxed.gpu.global.b128 t, [%34+%35]; mov.b128 {%24,%25,%26,%27}, t;\n"
        "bra.uni L;\nD:}"
        : "+r"(r[0][0]), "+r"(r[0][1]), "+r"(r[0][2]), "+r"(r[0][3]), "+r"(r[1][0]), "+r"(r[1][1]), "+r"(r[1][2]), "+r"(r[1][3]), "+r"(r[2][0]), "+r"(r[2][1]), "+r"(r[2][2]), "+r"(r[2][3]), "+r"(r[3][0]), "+r"(r[3][1]), "+r"(r[3][2]), "+r"(r[3][3]), "+r"(r[4][0]), "+r"(r[4][1]), "+r"(r[4][2]), "+r"(r[4][3]), "+r"(r[5][0]), "+r"(r[5][1]), "+r"(r[5][2]), "+r"(r[5][3]), "+r"(r[6][0]), "+r"(r[6][1]), "+r"(r[6][2]), "+r"(r[6][3])
        : "l"(p[0]), "l"(p[1]), "l"(p[2]), "l"(p[3]), "l"(p[4]), "l"(p[5]), "l"(p[6]), "n"((4 - S_) * 524288), "n"(SPIN_LIMIT), "r"(fz), "r"(stale) : "memory");
    else asm volatile("{.reg .b128 t; .reg .pred p; .reg .u32 m, k, n;\nmov.u32 n, %clock; or.b32 n, n, %37; shr.u32 n, n, 31;\nL:\n"
        "xor.b32 m, %0, %38; xor.b32 k, %4, %38; and.b32 m, m, k; xor.b32 k, %8, %38; and.b32 m, m, k; xor.b32 k, %12, %38; and.b32 m, m, k; xor.b32 k, %16, %38; and.b32 m, m, k;\n"
        "xor.b32 k, %20, %38; and.b32 m, m, k; xor.b32 k, %24, %38; and.b32 m, m, k; and.b32 m, m, 0x40000000;\n"
        "setp.eq.u32 p, m, 0; vote.sync.any.pred p, p, 0xffffffff; add.u32 n, n, 1; setp.lt.and.u32 p, n, %36, p;\n@!p bra.uni D;\n"
        "xor.b32 k, %0, %38; and.b32 k, k, 0x40000000; setp.eq.u32 p, k, 0; mov.b128 t, {%0,%1,%2,%3}; @p ld.relaxed.gpu.global.b128 t, [%28+%35]; mov.b128 {%0,%1,%2,%3}, t;\n"
        "xor.b32 k, %4, %38; and.b32 k, k, 0x40000000; setp.eq.u32 p, k, 0; mov.b128 t, {%4,%5,%6,%7}; @p ld.relaxed.gpu.global.b128 t, [%29+%35]; mov.b128 {%4,%5,%6,%7}, t;\n"
        "xor.b32 k, %8, %38; and.b32 k, k, 0x40000000; setp.eq.u32 p, k, 0; mov.b128 t, {%8,%9,%10,%11}; @p ld.relaxed.gpu.global.b128 t, [%30+%35]; mov.b128 {%8,%9,%10,%11}, t;\n"
        "xor.b32 k, %12, %38; and.b32 k, k, 0x40000000; setp.eq.u32 p, k, 0; mov.b128 t, {%12,%13,%14,%15}; @p ld.relaxed.gpu.global.b128 t, [%31+%35]; mov.b128 {%12,%13,%14,%15}, t;\n"
        "xor.b32 k, %16, %38; and.b32 k, k, 0x40000000; setp.eq.u32 p, k, 0; mov.b128 t, {%16,%17,%18,%19}; @p ld.relaxed.gpu.global.b128 t, [%32+%35]; mov.b128 {%16,%17,%18,%19}, t;\n"
        "xor.b32 k, %20, %38; and.b32 k, k, 0x40000000; setp.eq.u32 p, k, 0; mov.b128 t, {%20,%21,%22,%23}; @p ld.relaxed.gpu.global.b128 t, [%33+%35]; mov.b128 {%20,%21,%22,%23}, t;\n"
        "xor.b32 k, %24, %38; and.b32 k, k, 0x40000000; setp.eq.u32 p, k, 0; mov.b128 t, {%24,%25,%26,%27}; @p ld.relaxed.gpu.global.b128 t, [%34+%35]; mov.b128 {%24,%25,%26,%27}, t;\n"
        "bra.uni L;\nD:}"
        : "+r"(r[0][0]), "+r"(r[0][1]), "+r"(r[0][2]), "+r"(r[0][3]), "+r"(r[1][0]), "+r"(r[1][1]), "+r"(r[1][2]), "+r"(r[1][3]), "+r"(r[2][0]), "+r"(r[2][1]), "+r"(r[2][2]), "+r"(r[2][3]), "+r"(r[3][0]), "+r"(r[3][1]), "+r"(r[3][2]), "+r"(r[3][3]), "+r"(r[4][0]), "+r"(r[4][1]), "+r"(r[4][2]), "+r"(r[4][3]), "+r"(r[5][0]), "+r"(r[5][1]), "+r"(r[5][2]), "+r"(r[5][3]), "+r"(r[6][0]), "+r"(r[6][1]), "+r"(r[6][2]), "+r"(r[6][3])
        : "l"(p[0]), "l"(p[1]), "l"(p[2]), "l"(p[3]), "l"(p[4]), "l"(p[5]), "l"(p[6]), "n"((4 - S_) * 524288), "n"(SPIN_LIMIT), "r"(fz), "r"(stale) : "memory");
}
template <class T> __device__ __forceinline__ T* pinp(T* p) { return (T*)__shfl_xor_sync(~0u, (unsigned long long)p, 0); }
__device__ __forceinline__ float fsel(bool c, float a, float b) { float r; asm("{.reg .pred p; setp.ne.u32 p, %3, 0; selp.f32 %0, %1, %2, p;}" : "=f"(r) : "f"(a), "f"(b), "r"((int)c)); return r; }
__device__ __forceinline__ void stg4_if(bool c, void* p, uint32_t a, uint32_t b, uint32_t d, uint32_t e) {
    asm volatile("{.reg .b128 t; .reg .pred p; setp.ne.u32 p, %5, 0; mov.b128 t, {%1,%2,%3,%4}; @p st.relaxed.gpu.global.b128 [%0], t;}" ::"l"(p), "r"(a), "r"(b), "r"(d), "r"(e), "r"((int)c) : "memory");
}
__device__ __forceinline__ void stg1_if(bool c, void* p, uint32_t a) {
    asm volatile("{.reg .pred p; setp.ne.u32 p, %2, 0; @p st.relaxed.gpu.global.u32 [%0], %1;}" ::"l"(p), "r"(a), "r"((int)c) : "memory");
}
__device__ __forceinline__ void ldg4_again(uint32_t* r, const void* p) {
    asm volatile("{.reg .b128 t; .reg .pred p; setp.eq.u32 p, %3, 0; mov.b128 t, {%0,%1,%2,%3}; @p ld.relaxed.gpu.global.b128 t, [%4]; mov.b128 {%0,%1,%2,%3}, t;}"
                 : "+r"(r[0]), "+r"(r[1]), "+r"(r[2]), "+r"(r[3]) : "l"(p) : "memory");
}
__device__ __forceinline__ void wgmma_rs_n192(float* d, const uint32_t* a, uint64_t bdesc, int accum) {
    asm volatile("{.reg .pred p; setp.ne.b32 p, %101, 0; wgmma.mma_async.sync.aligned.m64n192k16.f32.bf16.bf16 {%0,%1,%2,%3,%4,%5,%6,%7,%8,%9,%10,%11,%12,%13,%14,%15,%16,%17,%18,%19,%20,%21,%22,%23,%24,%25,%26,%27,%28,%29,%30,%31,%32,%33,%34,%35,%36,%37,%38,%39,%40,%41,%42,%43,%44,%45,%46,%47,%48,%49,%50,%51,%52,%53,%54,%55,%56,%57,%58,%59,%60,%61,%62,%63,%64,%65,%66,%67,%68,%69,%70,%71,%72,%73,%74,%75,%76,%77,%78,%79,%80,%81,%82,%83,%84,%85,%86,%87,%88,%89,%90,%91,%92,%93,%94,%95}, {%96,%97,%98,%99}, %100, p, 1, 1, 1;}"
        : "+f"(d[0]),"+f"(d[1]),"+f"(d[2]),"+f"(d[3]),"+f"(d[4]),"+f"(d[5]),"+f"(d[6]),"+f"(d[7]),"+f"(d[8]),"+f"(d[9]),"+f"(d[10]),"+f"(d[11]),"+f"(d[12]),"+f"(d[13]),"+f"(d[14]),"+f"(d[15]),"+f"(d[16]),"+f"(d[17]),"+f"(d[18]),"+f"(d[19]),"+f"(d[20]),"+f"(d[21]),"+f"(d[22]),"+f"(d[23]),"+f"(d[24]),"+f"(d[25]),"+f"(d[26]),"+f"(d[27]),"+f"(d[28]),"+f"(d[29]),"+f"(d[30]),"+f"(d[31]),"+f"(d[32]),"+f"(d[33]),"+f"(d[34]),"+f"(d[35]),"+f"(d[36]),"+f"(d[37]),"+f"(d[38]),"+f"(d[39]),"+f"(d[40]),"+f"(d[41]),"+f"(d[42]),"+f"(d[43]),"+f"(d[44]),"+f"(d[45]),"+f"(d[46]),"+f"(d[47]),"+f"(d[48]),"+f"(d[49]),"+f"(d[50]),"+f"(d[51]),"+f"(d[52]),"+f"(d[53]),"+f"(d[54]),"+f"(d[55]),"+f"(d[56]),"+f"(d[57]),"+f"(d[58]),"+f"(d[59]),"+f"(d[60]),"+f"(d[61]),"+f"(d[62]),"+f"(d[63]),"+f"(d[64]),"+f"(d[65]),"+f"(d[66]),"+f"(d[67]),"+f"(d[68]),"+f"(d[69]),"+f"(d[70]),"+f"(d[71]),"+f"(d[72]),"+f"(d[73]),"+f"(d[74]),"+f"(d[75]),"+f"(d[76]),"+f"(d[77]),"+f"(d[78]),"+f"(d[79]),"+f"(d[80]),"+f"(d[81]),"+f"(d[82]),"+f"(d[83]),"+f"(d[84]),"+f"(d[85]),"+f"(d[86]),"+f"(d[87]),"+f"(d[88]),"+f"(d[89]),"+f"(d[90]),"+f"(d[91]),"+f"(d[92]),"+f"(d[93]),"+f"(d[94]),"+f"(d[95])
        : "r"(a[0]), "r"(a[1]), "r"(a[2]), "r"(a[3]), "l"(bdesc), "r"(accum));
}
__device__ __forceinline__ void wgmma_rs_n48(float* d, const uint32_t* a, uint64_t bdesc, int accum) {
    asm volatile("{.reg .pred p; setp.ne.b32 p, %29, 0; wgmma.mma_async.sync.aligned.m64n48k16.f32.bf16.bf16 {%0,%1,%2,%3,%4,%5,%6,%7,%8,%9,%10,%11,%12,%13,%14,%15,%16,%17,%18,%19,%20,%21,%22,%23}, {%24,%25,%26,%27}, %28, p, 1, 1, 1;}"
        : "+f"(d[0]),"+f"(d[1]),"+f"(d[2]),"+f"(d[3]),"+f"(d[4]),"+f"(d[5]),"+f"(d[6]),"+f"(d[7]),"+f"(d[8]),"+f"(d[9]),"+f"(d[10]),"+f"(d[11]),"+f"(d[12]),"+f"(d[13]),"+f"(d[14]),"+f"(d[15]),"+f"(d[16]),"+f"(d[17]),"+f"(d[18]),"+f"(d[19]),"+f"(d[20]),"+f"(d[21]),"+f"(d[22]),"+f"(d[23])
        : "r"(a[0]), "r"(a[1]), "r"(a[2]), "r"(a[3]), "l"(bdesc), "r"(accum));
}
__device__ __forceinline__ void wgmma_rs_n80(float* d, const uint32_t* a, uint64_t bdesc, int accum) {
    asm volatile("{.reg .pred p; setp.ne.b32 p, %45, 0; wgmma.mma_async.sync.aligned.m64n80k16.f32.bf16.bf16 {%0,%1,%2,%3,%4,%5,%6,%7,%8,%9,%10,%11,%12,%13,%14,%15,%16,%17,%18,%19,%20,%21,%22,%23,%24,%25,%26,%27,%28,%29,%30,%31,%32,%33,%34,%35,%36,%37,%38,%39}, {%40,%41,%42,%43}, %44, p, 1, 1, 1;}"
        : "+f"(d[0]),"+f"(d[1]),"+f"(d[2]),"+f"(d[3]),"+f"(d[4]),"+f"(d[5]),"+f"(d[6]),"+f"(d[7]),"+f"(d[8]),"+f"(d[9]),"+f"(d[10]),"+f"(d[11]),"+f"(d[12]),"+f"(d[13]),"+f"(d[14]),"+f"(d[15]),"+f"(d[16]),"+f"(d[17]),"+f"(d[18]),"+f"(d[19]),"+f"(d[20]),"+f"(d[21]),"+f"(d[22]),"+f"(d[23]),"+f"(d[24]),"+f"(d[25]),"+f"(d[26]),"+f"(d[27]),"+f"(d[28]),"+f"(d[29]),"+f"(d[30]),"+f"(d[31]),"+f"(d[32]),"+f"(d[33]),"+f"(d[34]),"+f"(d[35]),"+f"(d[36]),"+f"(d[37]),"+f"(d[38]),"+f"(d[39])
        : "r"(a[0]), "r"(a[1]), "r"(a[2]), "r"(a[3]), "l"(bdesc), "r"(accum));
}

__global__ void __cluster_dims__(2, 1, 1) __launch_bounds__(384, 1)
fused_kernel(const __nv_bfloat16* __restrict__ wmod, const __nv_bfloat16* __restrict__ cvec, Scratch* __restrict__ S,
             const __nv_bfloat16* __restrict__ wqkv, const __nv_bfloat16* __restrict__ wo, __nv_bfloat16* __restrict__ out,
             const __nv_bfloat16* __restrict__ wr, const __nv_bfloat16* __restrict__ wg, const __nv_bfloat16* __restrict__ wu,
             const __nv_bfloat16* __restrict__ wd,
             const __grid_constant__ CUtensorMap mm, const __grid_constant__ CUtensorMap mx, const __grid_constant__ CUtensorMap mw,
             const __grid_constant__ CUtensorMap mt, const __grid_constant__ CUtensorMap mo, const __grid_constant__ CUtensorMap mg,
             const __grid_constant__ CUtensorMap mu, const __grid_constant__ CUtensorMap md,
             const __grid_constant__ CUtensorMap mw2, const __grid_constant__ CUtensorMap mout,
             const __grid_constant__ CUtensorMap mo2) {
    extern __shared__ __align__(1024) char sm_raw[];
    const int bid = blockIdx.x;
    const uint32_t sm = ((bid & 1) << 24) + SM0;
    STAMP(30);
    const uint32_t t_start = clock32();
    if (bid < CPF && threadIdx.x == 0)
        asm volatile("cp.async.bulk.prefetch.tensor.2d.L2.global [%0, {%1, %2}];" ::"l"(&mm), "r"((bid & 1) * 640 + (bid >> 4) * 64), "r"(((bid >> 1) & 7) * 80) : "memory");
    const int cl = bid >> 1, rank = bid & 1, c7 = ((cl - 36) * 37) >> 8;
    const int grp = cl < 4 ? 0 : (cl < 36 ? (cl - 4) & 7 : cl - 35 - 7 * c7);
    const int ti = grp * 2 + rank;
    auto ldx = [&](int c) { mbar_expect_tx(BAR(B_XF + c), 16384); tma3d(sm + c * 16384, &mx, c * 64, ti >> 3, (ti & 7) * 128, BAR(B_XF + c)); };
    if (threadIdx.x == 256 && bid < 128) {
        mbar_init(BAR(B_XF), 1); mbar_init(BAR(B_XF + 1), 1);
        pause_until(t_start, XDELAY);
        ldx(0); ldx(1);
        STAMPT(22, 256);
#pragma unroll
        for (int i = 2; i < 10; i++) mbar_init(BAR(B_XF + i), 1);
        mbar_init(BAR(B_T0), 1);
        asm volatile("fence.mbarrier_init.release.cluster;" ::: "memory");
        ldx(2); ldx(3); ldx(4);
    }
    const int warp = __shfl_sync(~0u, threadIdx.x >> 5, 0);

#define PIN(v) __shfl_xor_sync(~0u, (v), 0)
#define LANE_VARS const int tid = PIN(threadIdx.x), lane = tid & 31, g = lane >> 2, q = lane & 3; \
    const uint32_t frow = (lane & 7) + (lane >> 4) * 8, fh = (lane >> 3) & 1;
    if (bid >= 128) {
        LANE_VARS
        const int h = bid - 128;
        if (warp >= 8) {
            if (warp == 8) return;
            const int t = tid - 288;
            if (t < 90) stg4_rlx(&S->tab[(5 + t / 9) * 4 + h][t % 9], 0u, 0u, 0u, 0u);
            __syncwarp();
            asm volatile("bar.arrive 1, 352;" ::: "memory");
            bar_sync(2, 96);
            if (t == 0) asm volatile("red.release.gpu.global.add.u32 [%0], 32;" ::"l"(&S->cnt) : "memory");
            return;
        }
        const uint32_t slot = sm + warp * 20480, bar = BAR(warp * 2);
        auto column = [&](int job) {
            const int n = job * 4 + h;
            return job < 10 ? ((h & 1) ? (job < 5 ? 10 : 30) : (job < 5 ? 0 : 10)) + (n >> 1) : (n < 50 ? n - 10 : n);
        };
        auto load = [&](int job) {
            mbar_expect_tx(bar + (job & 1) * 8, 10240);
            tma2d(slot + (job & 1) * 10240, &mm, column(job) * 64, warp * 80, bar + (job & 1) * 8);
        };
        if (elect1()) { mbar_init(bar, 1); mbar_init(bar + 8, 1); load(0); }
        __syncwarp();
        uint32_t b[10];
#pragma unroll
        for (int s = 0; s < 10; s++) b[s] = ldg1_rlx((const uint32_t*)cvec + warp * 40 + s * 4 + q);
        if (lane < 8 && warp < 5) stg4_rlx(&S->tab[warp * 4 + h][lane], 0u, 0u, 0u, 0u);
#pragma unroll
        for (int s = 0; s < 10; s++) b[s] = pack2(blo(b[s]) * sigm(blo(b[s])), bhi(b[s]) * sigm(bhi(b[s])));
        const uint32_t fa = slot + frow * 128 + ((fh ^ (lane & 7)) << 4);
        const int c0 = (lane >> 3) * 16 + (lane & 1) * 8 + (lane & 6);
#pragma unroll 1
        for (int job = 0; job < 15; job++) {
            uint32_t w2 = 0;
            if (job >= 5) w2 = ldg1_rlx(wr + (column(job) % 10) * 64 + c0);

            mbar_wait(bar + (job & 1) * 8, (job >> 1) & 1);
            if (job == 0) { if (elect1()) load(1); __syncwarp(); }
            float d[4][4] = {};
#pragma unroll
            for (int s = 0; s < 5; s++) {
#pragma unroll
                for (int m = 0; m < 4; m++) { uint32_t a[4]; ldsm4t(a, (fa ^ (m * 32)) + (job & 1) * 10240 + s * 2048); mma16(d[m], a[0], a[1], a[2], a[3], b[2 * s], b[2 * s + 1]); }
            }
            const uint32_t red = sm + OFF_W + (job & 1) * 2048;
            sts1f(red + (warp * 64 + q * 8 + g) * 4, q == 0 ? d[0][0] : (q == 1 ? d[0][2] : (q == 2 ? d[1][0] : d[1][2])));
            sts1f(red + (warp * 64 + 32 + q * 8 + g) * 4, q == 0 ? d[2][0] : (q == 1 ? d[2][2] : (q == 2 ? d[3][0] : d[3][2])));
            __syncwarp();
            if (job < 13 && elect1()) load(job + 2);
            __syncwarp();
            bar_sync(0, 256);
            if (job == 5) bar_sync(1, 352);
            if (warp == (job & 7)) {
                float y0 = 0.f, y1 = 0.f;
#pragma unroll
                for (int w = 0; w < 8; w++) { const float2 v = lds2f(red + (w * 64 + c0) * 4); y0 += v.x; y1 += v.y; }
                const uint32_t t = hf2(pack2(y0, y1), 0x3f803f80u, ((h & 1) && job < 10) ? 0x3f803f80u : 0x80008000u);
                uint32_t* const p = (uint32_t*)&S->tab[job * 4 + h][0];
                stg1_rlx(p + lane, nz(t));
                float dot = fmaf(blo(t), blo(w2), bhi(t) * bhi(w2));
#pragma unroll
                for (int o = 16; o; o >>= 1) dot += __shfl_xor_sync(~0u, dot, o);
                if (lane == 0) stg1_rlx(p + 32, dot == 0.f ? 0x80000000u : __float_as_uint(dot));
            }
            if (job == 0) STAMP(27);
            if (job == 8) STAMP(28);
        }
        STAMP(17);
        return;
    }
    uint32_t ep0;
    if (__builtin_expect(warp == 8, 1)) {
        asm volatile("barrier.cluster.arrive.relaxed.aligned;" ::: "memory");
        if (elect1()) {
#pragma unroll 1
            for (int c = 5; c < 10; c++) ldx(c);
        }
        __syncwarp();
    } else {
        if (warp < 8) {
            if (elect1()) {
#pragma unroll
                for (int i = 0; i < 8; i++) { const int b = B_WF + warp * 8 + i; mbar_init(BAR(b), b >= B_WE ? 16 : (b >= B_G2 ? 8 : (b >= B_EP ? 2 : (b == B_WO ? 7 : 1)))); }
                asm volatile("fence.mbarrier_init.release.cluster;" ::: "memory");
            }
            __syncwarp();
        }
        if (warp == 9) ep0 = ldg1_rlx(&S->cnt);
        asm volatile("barrier.cluster.arrive.relaxed.aligned;" ::: "memory");
    }
    const int sl = cl < 4 ? 4 + cl : (cl < 36 ? (cl - 4) >> 3 : 4 + c7);
    const int j = sl ^ (((sl + 2) >> 2) & 1), role = ti * 8 + j, odd = j & 1;
    const int fi = j * 16 + ti;
    const int al = ((j + 1) & 2) == 0;
    Exch* const X = &S->x;
    if (warp >= 8) {
        asm volatile("setmaxnreg.dec.sync.aligned.u32 72;");
        if (warp == 8) {
            asm volatile("barrier.cluster.wait.aligned;" ::: "memory");
            if (!elect1()) return;
            const int col_main = 80 * j + 16 * odd, col_tail = 80 * j + (odd ? 0 : 64);
            auto load_w = [&](int it) {
                const uint32_t b = BAR(B_WF + it), dst = sm + wbuf(it) + rank * 6144;
                mbar_expect_tx(b, WST);
                tma4d_mc(dst, al ? &mw2 : &mw, 0, it * 32 + rank * 16, col_main >> (5 + al), 0, b);
                tma3d_mc(dst + 12288 - rank * 4608, &mt, col_tail, it * 32 + rank * 16, 0, b);
            };
            int it = 0, wn = 0, gn = 0;
#pragma unroll 1
            for (int r = -2; r < 19; r++) {
                if (r == -1) mbar_wait(BAR(B_XF + XWAIT), 0);
                if (r >= 0) mbar_wait(BAR(B_WE + r), 0);
                const int lim = min(r < 2 ? (r == 1 ? 7 : 2 * r + 6) : r + 7, 20);
#pragma unroll 1
                for (; it < lim; it++) load_w(it);
                if (r == WP0 || r == WP1) l2_prefetch(wqkv + (size_t)((r == WP0 ? 128 : 384) + role * 2) * 1920, 2 * 3840);
                if (r == WOP) l2_prefetch(wo + role * 3200, 6400);
                if (r >= MPF0 && r < MPF0 + 10) l2_prefetch(wmod + (size_t)(role * 5 + ((r - MPF0) >> 1)) * 3840 + 1920 + (r & 1) * 1280, 1280);
                if (((GU_MASK >> (r + 2)) & 1) && fi < 108) { if (gn == 0) mbar_expect_tx(BAR(B_FG), 40960); tma2d(sm + OFF_WG + gn * GUR * 64, (fi & 1) ? &mu : &mg, (fi >> 1) * 32, gn * GUR, BAR(B_FG)); gn++; }
#pragma unroll 1
                for (int n = ((WO_MASK >> (r + 2)) & 1) + (r == 14); n > 0; n--) {
                    const int row = (j ^ wn) * 80 + rank * 40;
                    const uint32_t b = BAR(wn ? B_WO : B_WO0), dst = sm + wobuf(wn) + rank * 2560;
                    mbar_expect_tx(b, 12800);
                    tma2d_mc(dst, &mo, col_main, row, b); tma2d_mc(dst + 5120, &mo, col_main + 32, row, b); tma2d_mc(dst + 10240, &mo2, col_tail, row, b);
                    wn++;
                }
                if (r >= PF0 && r < PF0 + 3 * PFN) { const int m = (r - PF0) / PFN; l2_prefetch((m == 0 ? wg : (m == 1 ? wu : wd)) + role * 8640 + (r - PF0 - m * PFN) * (8640 / PFN), 17280 / PFN); }
            }
            STAMPT(24, 256);
            if (fi >= 88) { mbar_wait(BAR(B_G2), 0); mbar_expect_tx(BAR(B_FD), 55296); tma3d(sm + OFF_WD, &md, (fi - 88) * 16, 0, 0, BAR(B_FD)); }
            return;
        }
        asm volatile("barrier.cluster.wait.aligned;" ::: "memory");
        const int tid = threadIdx.x, lane = tid & 31, fh = (lane >> 3) & 1;
        int gd = 0;
        if (warp == 9) {
            {
                uint32_t ta = sm + OFF_TAB + fh * 1280 + (lane >> 4) * 128 + (lane & 4) * 16 + (lane & 1) * 32 + (lane & 2) * 4;
                const uint4* tp = &S->tab[lane >> 3][lane & 7];
                pause_until(t_start, TDELAY);
#pragma unroll 1
                for (int e = 0; e < 5; e++) {
                    uint32_t w[4];
                    if (e > 1) mbar_wait(BAR(B_WE + 4 * e - 8), 0);
                    while (true) {
                        ldg4_rlx(w, tp);
                        if (!__any_sync(~0u, min(min(w[0], w[1]), min(w[2], w[3])) == 0) || ++gd > SPIN_LIMIT) break;
                        pause(P_TAB);
                    }
                    sts2(ta, w[0], w[1]); sts2(ta + 16, w[2], w[3]);
                    __syncwarp();
                    if (e == 0) { STAMPT(2, 288); if (lane == 0) sts1(sm + OFF_EP + EP_US + 8, ep0 << 22 & 0x40000000u); }
                    if (lane == 0) mbar_arrive(BAR(e ? B_TB - 1 + e : B_T0));
                    ta += 256; tp += 288;
                }
            }
            uint32_t h[5][4];
            while (ldg1_acq(&S->cnt) != inc(ep0) && ++gd < SPIN_LIMIT) __nanosleep(YSLEEP);
            __syncwarp();
            if (lane == 0) mbar_arrive(BAR(B_RDY));
            mbar_wait(BAR(HALO_GO), 0);
            pause(D_H);
            if ((ti & 7) == 0) {
#pragma unroll
                for (int s = 0; s < 20; s++) h[s >> 2][s & 3] = 0;
            } else {
                do {
#pragma unroll
                    for (int s = 0; s < 5; s++) ldg4_rlx(h[s], &X->halo[(role - 8 - (ti & 8)) * 160 + s * 32 + lane]);
                } while (__any_sync(~0u, min(min(min(h[0][0], h[1][0]), min(h[2][0], h[3][0])), h[4][0]) == 0) && ++gd < SPIN_LIMIT);
            }
            const uint32_t p8 = sm + OFF_P8 - 4096, va = p8 + 2048 + (lane & 7) * VP + (lane >> 3) * 16;
            sts4(p8 + 2048 + 1408 + lane * 16, h[0]); sts4(p8 + 1408 + lane * 16, h[1]); sts2(p8 + (lane >> 4) * 2048 + 1920 + (lane & 15) * 8, h[2][0], h[2][1]);
            stsm4(va, h[3]); stsm4(va + 64, h[4]); stsm2(va + 128, h[2][2], h[2][3]);
            __syncwarp();
            if (lane == 0) mbar_arrive(BAR(B_HL));
            STAMPT(19, 288);
            uint2* const rp = pinp((uint2*)&X->ra[(lane & 7) * 8][0] + ti);
            const uint2* const rq = pinp((const uint2*)&X->ra[grp * 8][0] + (lane & 15));
            const uint32_t tk0 = PIN(((ti & 7) * 128 + lane * 4) * 2 + (ti >> 3) + 1);
            mbar_wait(BAR(B_G3), 0);
            if (j == (ti & 7)) {
                lds4(h[0], sm + OFF_TAB + 1024 + lane * 16);
                const uint32_t k01 = max(h[0][0], h[0][1]), k = max(k01, max(h[0][2], h[0][3])), km = __reduce_max_sync(~0u, k);
                const uint32_t t = tk0 + (k01 == k ? (h[0][0] == k ? 0 : 2) : (h[0][2] == k ? 4 : 6)), tk = __reduce_min_sync(~0u, k == km ? t : ~0u);
                asm volatile("{.reg .pred p; setp.lt.u32 p, %2, 8; @p red.relaxed.gpu.global.max.u64 [%0], %1;}" ::"l"(rp), "l"((unsigned long long)tk << 32 | km), "r"(lane) : "memory");
            }
            pause(D_REC);
            uint32_t kwin;
            bool bad;
            do { ldg2_rlx(h[0], rq); bad = __any_sync(~0u, h[0][1] == 0); kwin = __reduce_max_sync(~0u, h[0][0]); gd++; } while (bad && gd < SPIN_LIMIT);
            {
                const uint32_t t = (h[0][1] - 1) & 2047, wi = (t & 1) * 64 + (t >> 5), wv[4] = {kwin, t, wi, wi * 320}, m = __ballot_sync(~0u, h[0][0] == kwin);
                if ((m & -m) == 1u << lane) { sts4(sm + OFF_EP + EP_US + 32, wv); mbar_arrive(BAR(B_WIN)); }
            }
            if (lane < 8 && role < 20) stg4_rlx(&S->tab[role][lane], 0u, 0u, 0u, 0u);
            return;
        }
        const int at = tid - 320;
        const int kg = at < 40 ? 80 * j + 2 * at : max(fi - 88, 0) * 16 + 2 * (at & 7);
        const uint32_t w2 = *(const uint32_t*)(wr + kg);
        mbar_wait(BAR(B_T0), 0);
        {
            uint4* p = &X->o[4 * 128 * 256] + role * RV + at;
#pragma unroll 1
            for (int r = 0; r < RV / 64; r++) {
                stg4_rlx(p, 0u, 0u, 0u, 0u);
                p += 64;
                __nanosleep(RSLEEP);
            }
        }
        bar_sync(5, 64);
        if (at == 0) { mbar_wait(BAR(B_TB), 0); }
        if (at == 0) asm volatile("red.release.gpu.global.add.u32 [%0], 1;" ::"l"(&S->cnt) : "memory");
        mbar_wait(BAR(B_RDY), 0);
        const uint32_t* const mp = (const uint32_t*)&S->tab[0][0] + ((kg >> 4) & 3) * 8 + (kg & 6) + ((kg >> 3) & 1);
        const int p = odd ? (at < 8 ? at + 32 : at - 8) : at, lm = min(lane, 9);
        const uint32_t a = sm + OFF_EP + (p & 3) * 48 + (p >> 2) * 4;
#pragma unroll 1
        for (int ph = 0; ph < 4; ph++) {
            uint32_t v, us;
            mbar_wait(BAR(ph < 2 ? TB_GO : TB_GO2), 0);
            while (true) {
                v = ldg1_rlx(mp + (ph < 2 ? 20 + ph + (kg >> 6) * 2 : 20 + ph * 10 + (kg >> 6)) * 288);
                us = ldg1_rlx(&S->tab[ph < 2 ? 20 + ph + lm * 2 : 20 + ph * 10 + lm][8]);
                if (!__any_sync(~0u, min(v, us) == 0) || ++gd > SPIN_LIMIT) break;
                __nanosleep(200);
            }
            if (at < 40) {
                sts1(a + ph * 192, v);
                if (ph == 1) {
                    const float u0 = blo(v) * blo(w2), u1 = bhi(v) * bhi(w2);
                    const uint32_t uh = pack2(u0, u1);
                    sts1(a + 768, 0x3f803f80u); sts1(a + 960, uh); sts1(a + 1152, pack2(u0 - blo(uh), u1 - bhi(uh)));
                }
            } else sts1(sm + OFF_EP + EP_GD + (at & 7) * 4, v);
            float t = lane < 10 ? __uint_as_float(us) : 0.f;
#pragma unroll
            for (int o = 1; o < 16; o <<= 1) t += __shfl_xor_sync(~0u, t, o);
            if (at == 0) sts1f(sm + OFF_EP + EP_US + 12 + ph * 4, t);
            __syncwarp();
            if (lane == 0 && ph) mbar_arrive(BAR(B_EP - 1 + ph));
        }
        STAMPT(20, 320);
    } else {
        asm volatile("setmaxnreg.inc.sync.aligned.u32 216;");
        asm volatile("barrier.cluster.wait.aligned;" ::: "memory");
        LANE_VARS
        const int tw = ti * 8 + warp;
        const uint32_t oo = tw * 4096 + j * 512 + lane * 16;
        const uint32_t pair = (uint32_t)(lane & 1) << 24;
        const uint32_t hi = lane >> 4, xa = sm + (warp * 16 + (lane & 15)) * 128 + ((hi ^ (lane & 7)) << 4);
        const uint32_t p8 = sm + OFF_P8 + warp * 2048, q8 = p8 - (warp ? 2048 : 4096), q9 = p8 - 2048 + (warp ? 16384 : 0);
        const uint32_t l16 = PIN(lane * 16), kt = PIN(hi * 16384 + (lane & 15) * 8), va = PIN(p8 + (lane & 7) * VP + (lane >> 3) * 16);
        const uint32_t vc = PIN(p8 + (lane & 7) * VP + fh * 16384 + hi * 16);
        const uint32_t vh = PIN((fh ? p8 : q9) + (lane & 7) * VP + hi * 16), kh = PIN((hi ? q9 : q8) + (lane & 15) * 8);
        const uint32_t mgt = PIN((2 * q > g ? 0xffffu : 0u) | (2 * q + 1 > g ? 0xffff0000u : 0u));
        uint32_t rr0, rr1, nn0, nn1;
        {
            float gA[2][4] = {}, gB[2][4] = {};
            uint32_t xb = sm + (warp * 16 + frow) * 128 + ((fh ^ (lane & 7)) << 4), one[16];
#pragma unroll
            for (int k = 0; k < 16; k++) one[k] = 0x3f803f80u + ((uint32_t)tid >> (12 + k));
            uint32_t a[10][4][4];
            const uint32_t xk[4] = {xb, xb ^ 32, xb ^ 64, xb ^ 96};
#pragma unroll
            for (int c = -1; c < 10; c++) {
                if (c < 9) {
                    mbar_wait(BAR(B_XF + c + 1), 0);
#pragma unroll
                    for (int k = 0; k < 4; k++) ldsm4(a[c + 1][k], xk[k] + (c + 1) * 16384);
                }
                if (c >= 0) {
#pragma unroll
                    for (int k = 0; k < 4; k++) {
                        const uint32_t* v = a[c][k];
                        uint32_t t[4];
#pragma unroll
                        for (int e = 0; e < 4; e++) asm volatile("mov.b32 %0, %1;" : "=r"(t[e]) : "r"(v[e]));
                        mma16(gA[k & 1], t[0], one[k * 4], t[1], one[k * 4 + 1], v[0], v[1]);
                        mma16(gB[k & 1], t[2], one[k * 4 + 2], t[3], one[k * 4 + 3], v[2], v[3]);
                    }
                }
            }
            const int src = (lane & ~3) | (g >> 1), e = g & 1;
            const float ss0 = __shfl_sync(~0u, e ? gA[0][1] + gA[1][1] : gA[0][0] + gA[1][0], src), ss1 = __shfl_sync(~0u, e ? gB[0][1] + gB[1][1] : gB[0][0] + gB[1][0], src);
            const float m0 = __shfl_sync(~0u, e ? gA[0][3] + gA[1][3] : gA[0][2] + gA[1][2], src) * (1.f / 640), m1 = __shfl_sync(~0u, e ? gB[0][3] + gB[1][3] : gB[0][2] + gB[1][2], src) * (1.f / 640);
            const float r0 = rbf(rsq(fmaxf(ss0 * (1.f / 640) - m0 * m0, 0.f) + 1e-5f)), r1 = rbf(rsq(fmaxf(ss1 * (1.f / 640) - m1 * m1, 0.f) + 1e-5f));
            rr0 = pack2(r0, r0); rr1 = pack2(r1, r1); nn0 = pack2(-m0 * r0, -m0 * r0); nn1 = pack2(-m1 * r1, -m1 * r1);
        }
        uint32_t xr[5][4];
#pragma unroll
        for (int s = 0; s < 5; s++) {
            const int ks = 5 * j + (odd ? (s == 4 ? 0 : s + 1) : s);
            ldsm4(xr[s], (xa ^ ((ks & 3) * 32)) + (ks >> 2) * 16384);
        }
        STAMP(0);
        mbar_wait(BAR(B_T0), 0);
        float acc[120];
#pragma unroll
        for (int i = 0; i < 120; i++) asm volatile("" : "=f"(acc[i]));
        {
            uint32_t a[2][2][4], raw[2][4], tt[2][4];
            uint32_t tb = sm + OFF_TAB + q * 16, xp = xa;
            auto load = [&](int u) {
                ldsm4(raw[0], xp ^ (u * 64)); ldsm4(raw[1], xp ^ (u * 64 + 32));
                lds4(tt[0], tb + u * 64 + 1280); lds4(tt[1], tb + u * 64);
            };
            auto xform = [&](uint32_t (*dst)[4]) {
#pragma unroll
                for (int h = 0; h < 2; h++) {
                    dst[h][0] = hf2(hf2(raw[h][0], rr0, nn0), tt[0][2 * h], tt[1][2 * h]); dst[h][1] = hf2(hf2(raw[h][1], rr1, nn1), tt[0][2 * h], tt[1][2 * h]);
                    dst[h][2] = hf2(hf2(raw[h][2], rr0, nn0), tt[0][2 * h + 1], tt[1][2 * h + 1]); dst[h][3] = hf2(hf2(raw[h][3], rr1, nn1), tt[0][2 * h + 1], tt[1][2 * h + 1]);
                }
            };
            const uint64_t dm0 = al ? mkdesc(SM0, 2048, 1024, 1) : mkdesc(SM0, 1024, 512, 2), dt0 = mkdesc(SM0 + 12288, 512, 256, 3);
            load(0); xform(a[0]);
            STAMP(3);
#pragma unroll 1
            for (int i2 = 0; i2 < 10; i2++) {
#pragma unroll
                for (int u = 0; u < 2; u++) {
                    const int it = i2 * 2 + u;
                    const uint32_t bo = wbuf(it) >> 4;
                    mbar_wait(BAR(B_WF + it), 0);
                    if (LAG && warp < 4 && i2 * 2 + u == 20 - LAG) bar_sync(4, 256);
                    wg_fence();
#pragma unroll
                    for (int h = 0; h < 2; h++) { wgmma_rs_n192(acc, a[u][h], dm0 + bo + h * 384, (u | h) ? 1 : i2); wgmma_rs_n48(acc + 96, a[u][h], dt0 + bo + h * 96, (u | h) ? 1 : i2); }
                    wg_commit();
                    if (LAG && u == 1 && warp >= 4 && i2 == 9) asm volatile("bar.arrive 4, 256;" ::: "memory");
                    if (u == 1) { xp += 16384; tb += 128; }
                    if (u == 1 && (i2 & 1) && i2 < 9) mbar_wait(BAR(B_TB + (i2 >> 1)), 0);
                    load(u ^ 1);
                    wg_wait<1>();
                    if (lane < 2 && (u == 1 || i2 > 0)) mbar_arrive_cl(pair + BAR0(B_WE - 1 + it));
                    xform(a[u ^ 1]);
                }
            }
        }
        uint32_t own[5][4], ab[3][7][4], sv, tc, fz = 0;
        const char* op[7];
        auto ldo = [&](int s, uint32_t (*dst)[4]) {
#pragma unroll
            for (int w = 0; w < 7; w++) ldg4_rlx(dst[w], op[w] + (4 - s) * 524288);
        };
        {
            uint32_t Q[10][2], K[2][10], V[2][10];
            mbar_wait(BAR(B_RDY), 0);
            const bool pub = warp == 7 && (~ti & 7);
            uint4* const hp = pinp(&X->halo[(role - (ti & 8)) * 160 + lane]);
            sv = lds1(sm + OFF_EP + EP_US + 8); tc = (sv ^ 0x40000000u) - 0x20000000u;
            wg_wait<0>();
            STAMP(4); STAMPT(18, 128);
#define ACC_IDX(t, m) (odd_ ? (t >= 2 ? m * 32 + (t - 2) * 4 : 96 + m * 8 + t * 4) : (t < 8 ? m * 32 + t * 4 : 96 + m * 8 + (t - 8) * 4))
#define PACK1(odd_v) { constexpr bool odd_ = odd_v; _Pragma("unroll") for (int t = 0; t < 10; t++) { \
                K[1][t] = pack2(acc[ACC_IDX(t, 1) + 2], acc[ACC_IDX(t, 1) + 3]); V[1][t] = pack2(acc[ACC_IDX(t, 2) + 2], acc[ACC_IDX(t, 2) + 3]); } }
#define PACK2(odd_v) { constexpr bool odd_ = odd_v; _Pragma("unroll") for (int t = 0; t < 10; t++) { \
                V[0][t] = pack2(acc[ACC_IDX(t, 2)], acc[ACC_IDX(t, 2) + 1]); \
                K[0][t] = pack2(acc[ACC_IDX(t, 1)], acc[ACC_IDX(t, 1) + 1]); \
                Q[t][0] = pack2(acc[ACC_IDX(t, 0)], acc[ACC_IDX(t, 0) + 1]); Q[t][1] = pack2(acc[ACC_IDX(t, 0) + 2], acc[ACC_IDX(t, 0) + 3]); } }
            if (odd) PACK1(true) else PACK1(false)
            if (pub) {
                K[1][0] = nz(K[1][0]); K[1][5] = nz(K[1][5]); K[1][2] = nz(K[1][2]); V[1][0] = nz(V[1][0]); V[1][4] = nz(V[1][4]);
                stg4_rlx(hp, K[1][0], K[1][1], K[1][3], K[1][4]); stg4_rlx(hp + 32, K[1][5], K[1][6], K[1][8], K[1][9]);
                stg4_rlx(hp + 96, V[1][0], V[1][1], V[1][2], V[1][3]); stg4_rlx(hp + 128, V[1][4], V[1][5], V[1][6], V[1][7]); stg4_rlx(hp + 64, K[1][2], K[1][7], V[1][8], V[1][9]);
            }
            uint32_t VT[5][4], KH[10];
            {
                const uint32_t k0[4] = {K[1][0], K[1][1], K[1][3], K[1][4]}, k1[4] = {K[1][5], K[1][6], K[1][8], K[1][9]};
                sts4(p8 + 16384 + 1408 + l16, k0); sts4(p8 + 1408 + l16, k1); sts2(p8 + 1920 + kt, K[1][2], K[1][7]);
                stsm4(va + 16384, V[1]); stsm4(va + 16384 + 64, V[1] + 4); stsm2(va + 16384 + 128, V[1][8], V[1][9]);
            }
            __syncwarp();
            if (lane == 0) mbar_arrive(BAR(B_HL + 1 + warp));
            if (odd) PACK2(true) else PACK2(false)
            stsm4(va, V[0]); stsm4(va + 64, V[0] + 4); stsm2(va + 128, V[0][8], V[0][9]);
            __syncwarp();
#pragma unroll
            for (int s = 0; s < 5; s++) ldsm4t(VT[s], vc + s * 32);
            float sb[4][4], sc[4][4];
            uint32_t qs[4][2];
#pragma unroll
            for (int h = 0; h < 4; h++) {
                const int ts = (h >> 1) * 5 + 2, ta = (h >> 1) * 5 + (h & 1) * 3;
                const bool mine = (q >> 1) == (h & 1);
                qs[h][0] = mine ? Q[ts][0] : 0u; qs[h][1] = mine ? Q[ts][1] : 0u;
                mma16c(sb[h], Q[ta][0], Q[ta][1], Q[ta + 1][0], Q[ta + 1][1], K[0][ta], K[0][ta + 1], 0.f, 0.f);
                mma16c(sc[h], Q[ta][0], Q[ta][1], Q[ta + 1][0], Q[ta + 1][1], K[1][ta], K[1][ta + 1], 0.f, 0.f);
                mma8(sb[h], qs[h][0], qs[h][1], K[0][ts]);
                mma8(sc[h], qs[h][0], qs[h][1], K[1][ts]);
            }
            const bool gt0 = mgt & 1, gt1 = (int)mgt < 0;
            uint32_t p[2][4];
            auto probs = [&](int h0, int h1, int e, float (*pv)[4], float (*cu)[4]) {
                const float cs = 0.22360679774997896f * 1.4426950408889634f;
                float t0[4], t1[4], m[4];
#pragma unroll
                for (int h = h0; h < h1; h++) { t0[h] = gt0 ? pv[h][2 * e] : cu[h][2 * e]; t1[h] = gt1 ? pv[h][2 * e + 1] : cu[h][2 * e + 1]; m[h] = fmaxf(t0[h], t1[h]); }
#pragma unroll
                for (int h = h0; h < h1; h++) m[h] = fmaxf(m[h], __shfl_xor_sync(~0u, m[h], 1));
#pragma unroll
                for (int h = h0; h < h1; h++) m[h] = fmaxf(m[h], __shfl_xor_sync(~0u, m[h], 2)) * -cs;
#pragma unroll
                for (int h = h0; h < h1; h++) p[e][h] = pack2(ex2(fmaf(t0[h], cs, m[h])), ex2(fmaf(t1[h], cs, m[h])));
            };
            auto pv = [&](int pr, int e, uint32_t (*vt)[4]) {
                const uint32_t a0 = p[e][2 * pr] & mgt, a1 = p[e][2 * pr + 1] & mgt, a2 = p[e][2 * pr] & ~mgt, a3 = p[e][2 * pr + 1] & ~mgt;
                float l[4];
                mma16c(l, a0, a1, a2, a3, 0x3f803f80u, 0x3f803f80u, 0.f, 0.f);
                l[0] = rcp(l[0]); l[2] = rcp(l[2]);
#pragma unroll
                for (int r = 0; r < 5; r++) {
                    const int t = pr * 5 + r;
                    float d[4];
                    mma16c(d, a0, a1, a2, a3, vt[t >> 1][(t & 1) * 2], vt[t >> 1][(t & 1) * 2 + 1], 0.f, 0.f);
                    const bool od = r == 2 ? (q & 2) : r > 2;
                    const float li = od ? l[2] : l[0];
                    own[t >> 1][(t & 1) * 2 + e] = pack2((od ? d[2] : d[0]) * li, (od ? d[3] : d[1]) * li);
                }
            };
            mbar_wait(BAR(B_HL + warp), 0);
            uint32_t VH[5][4];
            float sa[4][4];
            lds4(KH, q9 + 1408 + l16); lds4(KH + 4, q8 + 1408 + l16); lds2(KH + 8, kh + 1920);
#pragma unroll
            for (int s = 0; s < 5; s++) ldsm4t(VH[s], vh + s * 32);
            STAMP(5); STAMPT(25, 64);
            fz |= clock32();
            const float ninf = (tw & 63) == 0 ? -INFINITY : 0.f;
#pragma unroll
            for (int h = 0; h < 4; h++) {
                const int ta = (h >> 1) * 5 + (h & 1) * 3;
                mma16c(sa[h], Q[ta][0], Q[ta][1], Q[ta + 1][0], Q[ta + 1][1], KH[2 * h], KH[2 * h + 1], ninf, ninf);
                mma8(sa[h], qs[h][0], qs[h][1], KH[8 + (h >> 1)]);
            }
            auto sto = [&](int s) { own[s][0] = s ? tagw(own[s][0], tc) : nz(own[s][0]); stg4_rlx((char*)X->o + oo + (4 - s) * 524288, own[s][0], own[s][1], own[s][2], own[s][3]); };
            probs(0, 2, 1, sb, sc); probs(0, 2, 0, sa, sb);
            pv(0, 1, VT); pv(0, 0, VH);
            sto(0); sto(1);
            fz |= clock32();
            probs(2, 4, 1, sb, sc); probs(2, 4, 0, sa, sb);
            pv(1, 1, VT); pv(1, 0, VH);
#pragma unroll
            for (int w = 0; w < 7; w++) op[w] = (const char*)X->o + (oo ^ (w * 512 + 512));
            fz |= clock32();
            sto(2); ldo(0, ab[0]); sto(3); sto(4);
        }
        STAMP(6); STAMPT(21, 128); STAMPT(26, 64);
        float ac2[40];
#pragma unroll
        for (int i = 0; i < 40; i++) asm volatile("" : "=f"(ac2[i]));
        {
            const uint64_t d0 = mkdesc(SM0, 5120, 512, 2);
            mbar_wait(BAR(B_WO0), 0);
#pragma unroll
            for (int s = 1; s < 5; s++) own[s][0] -= tc;
            wg_fence();
#pragma unroll
            for (int s = 0; s < 5; s++) wgmma_rs_n80(ac2, own[s], d0 + (wobuf(0) >> 4) + s * 64, s);
            wg_commit();
            fz |= clock32();
            mbar_wait(BAR(B_WO), 0);
#pragma unroll
            for (int s = 0; s < 5; s++) {
                uint32_t (*cur)[4] = ab[s % 3];
                if (s == 0) await7<0>(cur, op, fz, sv);
                else {
                    if (s == 1) await7<1>(cur, op, fz, sv); else if (s == 2) await7<2>(cur, op, fz, sv); else if (s == 3) await7<3>(cur, op, fz, sv); else await7<4>(cur, op, fz, sv);
#pragma unroll
                    for (int w = 0; w < 7; w++) cur[w][0] -= tc;
                }
                if (s == 0) { STAMP(7); STAMPT(1, 128); }
                wg_fence();
#pragma unroll
                for (int w = 1; w < 8; w++) wgmma_rs_n80(ac2, cur[w - 1], d0 + (wobuf(w) >> 4) + s * 64, 1);
                wg_commit();
                if (s < 3) { if (s) wg_wait<1>(); else fz |= clock32(); if (s == 0) ldo(1, ab[1]); ldo(s + 2, ab[(s + 2) % 3]); }
                if (s == FD_AT && lane == 0) mbar_arrive(BAR(B_G2));
            }
        }
        mbar_wait(BAR(B_EP), 0);
        uint32_t tga[12], tst[12];
        const uint32_t ep = sm + OFF_EP + q * 48;
#pragma unroll
        for (int s = 0; s < 3; s++) { lds4(tga + 4 * s, ep + s * 16); lds4(tst + 4 * s, ep + 768 + min(g, 2) * 192 + s * 16); }
        uint4* const sp0 = pinp(&X->stats[j][tw * 16 + g]);
        const int prow = (ti & 7) * 128 + warp * 16;
        const uint4* const sp = pinp(&X->stats[hi * 4][tw * 16 + (lane & 15)]);
        const int dsrc = PIN((lane & ~3) | (g >> 1));
        wg_wait<0>();
        if (lane == 0) mbar_arrive(BAR(B_G4));
        STAMP(8); STAMPT(23, 128);
        {
            float gA[2][4] = {}, gB[2][4] = {}, sd[4] = {};
#pragma unroll
            for (int s = 0; s < 5; s++) {
#pragma unroll
                for (int e = 0; e < 4; e++) xr[s][e] = hf2(tga[2 * s + (e >> 1)], pack2(ac2[s * 8 + e * 2], ac2[s * 8 + e * 2 + 1]), xr[s][e]);
                mma16(sd, xr[s][0], xr[s][1], xr[s][2], xr[s][3], tst[2 * s], tst[2 * s + 1]);
                mma8(gA[0], xr[s][0], xr[s][1], xr[s][0]); mma8(gB[0], xr[s][0], xr[s][1], xr[s][1]);
                mma8(gA[1], xr[s][2], xr[s][3], xr[s][2]); mma8(gB[1], xr[s][2], xr[s][3], xr[s][3]);
            }
            const float l0 = __shfl_down_sync(~0u, sd[0], 1), l1 = __shfl_down_sync(~0u, sd[2], 1);
            const float q0 = __shfl_sync(~0u, fsel(g & 1, gA[0][1] + gA[1][1], gA[0][0] + gA[1][0]), dsrc), q1 = __shfl_sync(~0u, fsel(g & 1, gB[0][3] + gB[1][3], gB[0][2] + gB[1][2]), dsrc);
            stg4_if(q == 0, sp0, __float_as_uint(sd[0]), __float_as_uint(sd[1] + l0), __float_as_uint(q0), 1u);
            stg4_if(q == 0, sp0 + 8, __float_as_uint(sd[2]), __float_as_uint(sd[3] + l1), __float_as_uint(q1), 1u);
        }
        const uint32_t t9 = clock32();
        STAMP(9);
        uint32_t fg[5][4], fu[5][4], tcb[12], tsb[12];
        uint32_t st[4][4];
        if (fi < 108) {
            mbar_wait(BAR(B_FG), 0);
#pragma unroll
            for (int s = 0; s < 5; s++) {
                const uint32_t off = sm + OFF_WG + (5 * warp + ((warp & 1) ? (s == 4 ? 0 : s + 1) : s)) * 1024 + frow * 64 + ((fh ^ ((lane >> 1) & 3)) << 4);
                ldsm4t(fg[s], off); ldsm4t(fu[s], off ^ 32);
            }
        }
        pause_until(t9, D_ST);
#pragma unroll
        for (int e = 0; e < 4; e++) ldg4_rlx(st[e], sp + e * 2056);
        mbar_wait(BAR(B_EP2), 0);
#pragma unroll
        for (int s = 0; s < 3; s++) { lds4(tcb + 4 * s, ep + 192 + s * 16); lds4(tsb + 4 * s, ep + 384 + s * 16); }
        int crow;
        {
            const float2 su = lds2f(sm + OFF_EP + EP_US + 16);
            int gd = 0;
            const uint32_t ka = PIN(sm + OFF_TAB + 1024 + warp * 64 + (lane & 15) * 4);
            gd = clock32() >> 31;
            float v[3];
            bool bad;
            while (true) {
                bad = __any_sync(~0u, (st[0][3] & st[1][3] & st[2][3] & st[3][3]) == 0);
#pragma unroll
                for (int e = 0; e < 3; e++) {
                    v[e] = (__uint_as_float(st[0][e]) + __uint_as_float(st[1][e])) + (__uint_as_float(st[2][e]) + __uint_as_float(st[3][e]));
                    v[e] += __shfl_xor_sync(~0u, v[e], 16);
                }
                if (!bad || ++gd > SPIN_LIMIT) break;
#pragma unroll
                for (int e = 0; e < 4; e++) ldg4_again(st[e], sp + e * 2056);
            }
            STAMP(10);
            const float m = v[0] * (1.f / 640), rs = rsq(fmaxf(fmaf(v[2], 1.f / 640, 1e-5f) - m * m, 1e-5f));
            const uint32_t key = fkey(fmaf(rs, fmaf(-m, su.x, v[1]), su.y));
            sts1(ka, key);
            __syncwarp();
            if (lane == 0) mbar_arrive(BAR(B_G3));
            gd = clock32() >> 31;
            crow = (__ffs(__ballot_sync(~0u, key == __reduce_max_sync(~0u, key))) - 1 + gd * 16) & 15;
            const uint32_t rn = pack2(rs, -m * rbf(rs)), a0 = __shfl_sync(~0u, rn, g), a1 = __shfl_sync(~0u, rn, g + 8);
            rr0 = __byte_perm(a0, 0, 0x1010); nn0 = __byte_perm(a0, 0, 0x3232); rr1 = __byte_perm(a1, 0, 0x1010); nn1 = __byte_perm(a1, 0, 0x3232);
        }
        {
            const bool up = crow >= 8;
            const uint32_t rr = up ? rr1 : rr0, nn = up ? nn1 : nn0;
            if (g == (crow & 7)) {
                uint4* cp = &X->cand[j][tw * 20 + q];
#pragma unroll
                for (int s = 0; s < 5; s++) {
                    const uint32_t xa_ = up ? xr[s][1] : xr[s][0], xb_ = up ? xr[s][3] : xr[s][2];
                    stg4_rlx(cp + s * 4, nz(hf2(hf2(xa_, rr, nn), tcb[2 * s], tsb[2 * s])), hf2(hf2(xb_, rr, nn), tcb[2 * s + 1], tsb[2 * s + 1]), xa_, xb_);
                }
            }
        }
        STAMP(11);
        const uint32_t stg = sm + 5 * WST + warp * 2560;
        {
            mbar_wait(BAR(B_EP3), 0);
#pragma unroll
            for (int s = 0; s < 3; s++) lds4(tga + 4 * s, ep + 576 + s * 16);
#pragma unroll
            for (int s = 0; s < 5; s++) {
#pragma unroll
                for (int e = 0; e < 4; e++) { const int t = 2 * s + (e >> 1); xr[s][e] = hf2(tga[t], hf2(hf2(xr[s][e], (e & 1) ? rr1 : rr0, (e & 1) ? nn1 : nn0), tcb[t], tsb[t]), xr[s][e]); }
            }
            mbar_wait(BAR(B_G4), 0);
#pragma unroll
            for (int s = 0; s < 5; s++) stsm4(stg + (lane & 15) * 160 + (odd ? (s == 4 ? 0 : s + 1) : s) * 32 + hi * 16, xr[s]);
            asm volatile("fence.proxy.async.shared::cta;" ::: "memory");
            __syncwarp();
            if (elect1()) tma3d_st(&mout, 80 * j, ti >> 3, prow + (~crow & 8), stg + (~crow & 8) * 160);
        }
        STAMP(12);
        const char* cp = (const char*)pinp(&X->cand[warp][q]);
        uint32_t* const ap0 = pinp((uint32_t*)&X->ra[fi >> 1][8 + (fi & 1) * 4] + (lane & 8) + (lane & 3) * 2 + ((lane >> 2) & 1));
        const uint32_t rw = PIN(sm + OFF_RED - 256 + (q * 4 + (g >> 1)) * 80 + warp * 8 + (g & 1) * 4), rd = PIN(sm + OFF_RED - 256 + (lane & 15) * 80);
        if (smem_u32(sm_raw) != sm) return;
        uint32_t wv[4]; int gd = 0;
        mbar_wait(BAR(B_WIN), 0);
        lds4(wv, sm + OFF_EP + EP_US + 32);
        const uint32_t kwin = wv[0];
        const int tokwin = wv[1], win = wv[2];
        STAMP(13);
        if (fi < 108) {
            uint32_t hb[5][2];
            float mine;
            bool bad;
            cp += wv[3];
            do {
#pragma unroll
                for (int s = 0; s < 5; s++) ldg2_rlx(hb[s], cp + s * 64);
                bad = __any_sync(~0u, min(min(min(hb[0][0], hb[1][0]), min(hb[2][0], hb[3][0])), hb[4][0]) == 0);
                float dg[2][4] = {}, du[2][4] = {};
#pragma unroll
                for (int s = 0; s < 5; s++) {
                    mma16(dg[s & 1], fg[s][0], fg[s][1], fg[s][2], fg[s][3], hb[s][0], hb[s][1]);
                    mma16(du[s & 1], fu[s][0], fu[s][1], fu[s][2], fu[s][3], hb[s][0], hb[s][1]);
                }
                mine = fsel(q & 2, fsel(q & 1, du[1][2], du[1][0]), fsel(q & 1, dg[1][2], dg[1][0])) + fsel(q & 2, fsel(q & 1, du[0][2], du[0][0]), fsel(q & 1, dg[0][2], dg[0][0]));
                sts1f(rw, mine);
                gd++;
            } while (bad && gd < SPIN_LIMIT);
            bar_sync(2, 256);
            if (warp == 0) {
                uint32_t v[4][4];
#pragma unroll
                for (int e = 0; e < 4; e++) lds4(v[e], rd + e * 16);
                float t[2];
#pragma unroll
                for (int e = 0; e < 2; e++)
                    t[e] = ((__uint_as_float(v[0][e]) + __uint_as_float(v[0][e + 2])) + (__uint_as_float(v[1][e]) + __uint_as_float(v[1][e + 2]))) +
                           ((__uint_as_float(v[2][e]) + __uint_as_float(v[2][e + 2])) + (__uint_as_float(v[3][e]) + __uint_as_float(v[3][e + 2])));
                uint32_t pr = pack2(t[0], t[1]);
                if (!(fi & 1)) pr = pack2(blo(pr) * sigm(blo(pr)), bhi(pr) * sigm(bhi(pr)));
                stg1_if(lane < 16, ap0, nz(pr));
            }
        }
        STAMP(14);
        if (win != tw) {
            if (elect1()) tma3d_st(&mout, 80 * j, ti >> 3, prow + (crow & 8), stg + (crow & 8) * 160);
        } else {
#pragma unroll 1
            for (int r = crow & 8; r <= (crow | 7); r++)
                if (r != crow && lane < 20) { uint32_t v[2]; lds2(v, stg + r * 160 + lane * 8); *(uint2*)(out + (size_t)((prow + r) * 2 + (ti >> 3)) * 640 + 80 * j + lane * 4) = make_uint2(v[0], v[1]); }
        }
        if (fi >= 88) {
            const int d = fi - 88, dj = d / 5, dm = d - dj * 5, sp = (dj & 1) ? (dm == 0 ? 4 : dm - 1) : dm;
            const int ks0 = min(warp * 14, 94);
            const uint32_t frag = frow * 32 + ((fh ^ ((lane >> 2) & 1)) << 4);
            uint32_t fd[14][4];
            mbar_wait(BAR(B_FD), 0);
#pragma unroll
            for (int s = 0; s < 14; s++) ldsm4t(fd[s], sm + OFF_WD + (ks0 + s) * 512 + frag);
            const float sf = sigm(rbf(__uint_as_float((kwin & 0x80000000u) ? kwin & 0x7fffffffu : ~kwin)));
            const uint32_t sg = PIN(pack2(sf, sf));
            const uint32_t gbd = lds1(sm + OFF_EP + EP_GD + (lane & 7) * 4);
            uint32_t* const op = (uint32_t*)(out + (size_t)tokwin * 640 + d * 16) + (lane & 7);
            uint32_t bsv[4], ag[4], au[4];
            const uint4* ap = &X->ra[(ks0 >> 1) + min(g, 6)][8 + q];
            const uint32_t keep = warp == 7 && g < 2 ? 0u : ~0u;
            const uint32_t as = PIN(sm + 7 * WST + warp * 512 + q * 16), aw = PIN(sm + 7 * WST + warp * 512 + g * 64 + (q & 1) * 32 + (q >> 1) * 8);
            const uint32_t yw = PIN(sm + OFF_TAB + ((q & 1) * 4 + (g >> 1)) * 80 + warp * 8 + (g & 1) * 4), yr = PIN(sm + OFF_TAB + (lane & 7) * 80);
            bool bad;
            do {
                ldg4_rlx(ag, ap); ldg4_rlx(au, ap + 4); ldg4_rlx(bsv, &X->cand[dj][win * 20 + sp * 4 + q]);
                bad = __any_sync(~0u, min(min(min(min(ag[0], ag[1]), min(ag[2], ag[3])), min(min(au[0], au[1]), min(au[2], au[3]))), bsv[0]) == 0);
                sts2(aw, hm2(ag[0], au[0]) & keep, hm2(ag[1], au[1]) & keep); sts2(aw + 16, hm2(ag[2], au[2]) & keep, hm2(ag[3], au[3]) & keep);
                gd++;
            } while (bad && gd < SPIN_LIMIT);
            STAMP(15);
            __syncwarp();
            float dy[4][4] = {};
            uint32_t av[7][4];
#pragma unroll
            for (int s = 0; s < 7; s++) lds4(av[s], as + s * 64);
#pragma unroll
            for (int s = 0; s < 7; s++) {
                mma16(dy[(2 * s) & 3], fd[2 * s][0], fd[2 * s][1], fd[2 * s][2], fd[2 * s][3], av[s][0], av[s][1]);
                mma16(dy[(2 * s + 1) & 3], fd[2 * s + 1][0], fd[2 * s + 1][1], fd[2 * s + 1][2], fd[2 * s + 1][3], av[s][2], av[s][3]);
            }
            sts1f(yw, (fsel(q & 1, dy[2][2], dy[2][0]) + fsel(q & 1, dy[3][2], dy[3][0])) + (fsel(q & 1, dy[0][2], dy[0][0]) + fsel(q & 1, dy[1][2], dy[1][0])));
            bar_sync(2, 256);
            if (warp == 0) {
                uint32_t v[4][4];
#pragma unroll
                for (int e = 0; e < 4; e++) lds4(v[e], yr + e * 16);
                float t[2];
#pragma unroll
                for (int e = 0; e < 2; e++)
                    t[e] = ((__uint_as_float(v[0][e]) + __uint_as_float(v[0][e + 2])) + (__uint_as_float(v[1][e]) + __uint_as_float(v[1][e + 2]))) +
                           ((__uint_as_float(v[2][e]) + __uint_as_float(v[2][e + 2])) + (__uint_as_float(v[3][e]) + __uint_as_float(v[3][e + 2])));
                const uint32_t hh = (lane & 4) ? bsv[1] : bsv[0], xx = (lane & 4) ? bsv[3] : bsv[2];
                if (lane < 8) *op = hf2(gbd, hf2(hm2(pack2(t[0], t[1]), sg), 0x3f803f80u, hh), xx);
            }
        }
        asm volatile("cp.async.bulk.commit_group;\ncp.async.bulk.wait_group.read 0;" ::: "memory");
        STAMP(16);
    }
}

typedef CUresult (*EncFn)(CUtensorMap*, CUtensorMapDataType, cuuint32_t, void*, const cuuint64_t*, const cuuint64_t*, const cuuint32_t*, const cuuint32_t*,
                          CUtensorMapInterleave, CUtensorMapSwizzle, CUtensorMapL2promotion, CUtensorMapFloatOOBfill);
static void make_map(EncFn enc, CUtensorMap* m, const void* base, int rank, const cuuint64_t* dims, const cuuint64_t* strides, const cuuint32_t* box, CUtensorMapSwizzle sw) {
    const cuuint32_t es[5] = {1, 1, 1, 1, 1};
    enc(m, CU_TENSOR_MAP_DATA_TYPE_BFLOAT16, rank, (void*)base, dims, strides, box, es, CU_TENSOR_MAP_INTERLEAVE_NONE, sw, CU_TENSOR_MAP_L2_PROMOTION_NONE, CU_TENSOR_MAP_FLOAT_OOB_FILL_NONE);
}

extern "C" void kernel_launch(void* const* d_in, const int* in_sizes, int n_in, void* d_out, int out_size) {
    typedef const __nv_bfloat16* P;
    P x = (P)d_in[0], wqkv = (P)d_in[1], wo = (P)d_in[2], wr = (P)d_in[4], wg = (P)d_in[5], wu = (P)d_in[6], wd = (P)d_in[7], c = (P)d_in[8], wmod = (P)d_in[9];
    void* fn = nullptr; cudaDriverEntryPointQueryResult qr;
    cudaGetDriverEntryPoint("cuTensorMapEncodeTiled", &fn, cudaEnableDefault, &qr);
    EncFn enc = (EncFn)fn;
    CUtensorMap mx, mw, mt, mo, mg, mu, md, mm, mw2, mout, mo2;
    { cuuint64_t d[] = {640, 2, 1024}, s[] = {1280, 2560}; cuuint32_t b[] = {64, 1, 128}; make_map(enc, &mx, x, 3, d, s, b, CU_TENSOR_MAP_SWIZZLE_128B); }
    { cuuint64_t d[] = {32, 640, 20, 3}, s[] = {3840, 64, 1280}; cuuint32_t b[] = {32, 16, 2, 3}; make_map(enc, &mw, wqkv, 4, d, s, b, CU_TENSOR_MAP_SWIZZLE_64B); }
    { cuuint64_t d[] = {640, 640, 3}, s[] = {3840, 1280}; cuuint32_t b[] = {16, 16, 3}; make_map(enc, &mt, wqkv, 3, d, s, b, CU_TENSOR_MAP_SWIZZLE_32B); }
    { cuuint64_t d[] = {640, 640}, s[] = {1280}; cuuint32_t b[] = {32, 40}; make_map(enc, &mo, wo, 2, d, s, b, CU_TENSOR_MAP_SWIZZLE_64B);
      b[0] = 16; make_map(enc, &mo2, wo, 2, d, s, b, CU_TENSOR_MAP_SWIZZLE_64B); }
    { cuuint64_t d[] = {1728, 640}, s[] = {3456}; cuuint32_t b[] = {32, GUR}; make_map(enc, &mg, wg, 2, d, s, b, CU_TENSOR_MAP_SWIZZLE_64B); make_map(enc, &mu, wu, 2, d, s, b, CU_TENSOR_MAP_SWIZZLE_64B); }
    { cuuint64_t d[] = {640, 216, 8}, s[] = {1280, 1280 * 216}; cuuint32_t b[] = {16, 216, 8}; make_map(enc, &md, wd, 3, d, s, b, CU_TENSOR_MAP_SWIZZLE_32B); }
    { cuuint64_t d[] = {3840, 640}, s[] = {7680}; cuuint32_t b[] = {64, 80}; make_map(enc, &mm, wmod, 2, d, s, b, CU_TENSOR_MAP_SWIZZLE_128B); }
    { cuuint64_t d[] = {64, 640, 10, 3}, s[] = {3840, 128, 1280}; cuuint32_t b[] = {64, 16, 1, 3}; make_map(enc, &mw2, wqkv, 4, d, s, b, CU_TENSOR_MAP_SWIZZLE_128B); }
    { cuuint64_t d[] = {640, 2, 1024}, s[] = {1280, 2560}; cuuint32_t b[] = {80, 1, 8}; make_map(enc, &mout, d_out, 3, d, s, b, CU_TENSOR_MAP_SWIZZLE_NONE); }
    void* sp = nullptr;
    cudaGetSymbolAddress(&sp, g_s);
    cudaFuncSetAttribute(fused_kernel, cudaFuncAttributeMaxDynamicSharedMemorySize, SMEM_BYTES);
    fused_kernel<<<132, 384, SMEM_BYTES>>>(wmod, c, (Scratch*)sp, wqkv, wo, (__nv_bfloat16*)d_out, wr, wg, wu, wd, mm, mx, mw, mt, mo, mg, mu, md, mw2, mout, mo2);
}
```
